```python
import torch

def _softmax(x, axis=-1):
    return torch.softmax(x, dim=axis)
def _gelu(x):
    return torch.nn.functional.gelu(x, approximate="tanh")
def _silu(x):
    return torch.nn.functional.silu(x)
def _sigmoid(x):
    return torch.sigmoid(x)
def _layernorm(x, axis=-1, eps=1e-5):
    m = x.mean(dim=axis, keepdim=True)
    v = x.var(dim=axis, keepdim=True, unbiased=False)
    return (x - m) / torch.sqrt(v + eps)
def _scatter_add(tgt, idx, src, axis=0):
    return tgt.clone().index_add_(axis, idx, src)
def _segment_sum(src, seg, n):
    out = torch.zeros((n,) + src.shape[1:], dtype=src.dtype)
    return out.index_add_(0, seg, src)
def _pad(x, pw):
    flat = tuple(v for pair in reversed(pw) for v in pair)
    return torch.nn.functional.pad(x, flat)

kernel_name = 'gated_mix__sliding_block__dense_activation_relu__prompt'

def setup_inputs():

    _w = (lambda a: (lambda t: t.to(torch.bfloat16) if t.is_floating_point() else t)(torch.as_tensor(a)))
    def _A_setup():
        B, S, D = 1, 2048, 512
        return {
            "x": _w((lambda *s: torch.randn(*s, dtype=torch.bfloat16) * 0.05)(B, S, D)),
            "wqkv": _w((lambda *s: torch.randn(*s, dtype=torch.bfloat16) * 1.6)(D, 3 * D)),
            "wo": _w((lambda *s: torch.randn(*s, dtype=torch.bfloat16) * 0.05)(D, D)),
        }
    _A_in = _A_setup()

    def _B_setup():
        B, S, D, Dff = 1, 2048, 512, 1792
        return {
            "x": _w((lambda *s: torch.randn(*s, dtype=torch.bfloat16) * 0.05)(B, S, D)),
            "w1": _w((lambda *s: torch.randn(*s, dtype=torch.bfloat16) * 0.2)(D, Dff)),
            "w2": _w((lambda *s: torch.randn(*s, dtype=torch.bfloat16) * 0.2)(Dff, D)),
        }
    _B_in = _B_setup()

    return {
        "A_x": _A_in["x"],
        "A_wqkv": _A_in["wqkv"],
        "A_wo": _A_in["wo"],
        "B_x": _B_in["x"],
        "B_w1": _B_in["w1"],
        "B_w2": _B_in["w2"],
        "gate_w": _w((lambda *s: torch.randn(*s, dtype=torch.bfloat16) * 0.05)(512) * 16.0),
    }

def reference(A_x, A_wqkv, A_wo, B_x, B_w1, B_w2, gate_w):
    def _A_ref(x, wqkv, wo):
        B, S, D = x.shape
        H = 32; Dh = D // H; W = 256
        qkv = (lambda x, *d: x.permute(*d))((x @ wqkv).reshape(B, S, 3, H, Dh), 2, 0, 3, 1, 4)
        q, k, v = qkv[0], qkv[1], qkv[2]
        scores = torch.einsum("bhqd,bhkd->bhqk", q, k) * (Dh ** -0.5)
        idx = torch.arange(S)
        mask = (idx[:, None] - idx[None, :] >= 0) & (idx[:, None] - idx[None, :] < W)
        scores = torch.where(mask[None, None], scores, -1e9)
        p = _softmax(scores, axis=-1)
        o = torch.einsum("bhqk,bhkd->bhqd", p, v)
        return (lambda x, *d: x.permute(*d))(o, 0, 2, 1, 3).reshape(B, S, D) @ wo

    def _B_ref(x, w1, w2):
        h = torch.einsum("bsd,df->bsf", x, w1)
        zero = torch.zeros_like(h)
        h = torch.maximum(h, zero)
        return torch.einsum("bsf,fd->bsd", h, w2)

    x = A_x
    g = _sigmoid((x * gate_w).sum(-1, keepdims=True))
    a = _A_ref(x, A_wqkv, A_wo)
    b = _B_ref(x, B_w1, B_w2)
    return g * a + (1 - g) * b
```

```cpp
#include <cuda_runtime.h>
#include <cuda_bf16.h>
#include <cuda.h>
#include <stdint.h>

namespace {

constexpr int RING = 6;
constexpr int SLOT = 16384;
constexpr uint32_t X_OFF = 0;
constexpr uint32_t RING_OFF = 131072;
constexpr uint32_t BAR_OFF = RING_OFF + RING * SLOT;
constexpr uint32_t B_FULL = BAR_OFF, B_EMPTY = BAR_OFF + 64, B_XFULL = BAR_OFF + 128, B_GREADY = BAR_OFF + 192,
                   B_EREADY = BAR_OFF + 200, B_KVDONE = BAR_OFF + 208, B_PDONE = BAR_OFF + 216;
constexpr uint32_t EPOCH_OFF = BAR_OFF + 256;
constexpr uint32_t G_OFF = BAR_OFF + 512;
constexpr uint32_t SMEM_BYTES = BAR_OFF + 1024;

constexpr int N_QKV = 16, N_FFN1 = 16, N_KV = 8, N_FFN2 = 18;
constexpr int S_FFN1 = N_QKV, S_KV = S_FFN1 + N_FFN1, S_FFN2 = S_KV + N_KV, S_END = S_FFN2 + N_FFN2;

__device__ uint4 g_kf[32 * 128 * 32];
__device__ uint4 g_vf[32 * 128 * 32];
__device__ uint4 g_part[16 * 8 * 4 * 8 * 8 * 32];
__device__ unsigned g_ticket;
__device__ unsigned g_kvcnt[128 * 32];
__device__ unsigned g_pcnt[16 * 8 * 4 * 32];
#define TS(k) do {} while (0)

__device__ __forceinline__ uint32_t smem_u32(const void* p) { return (uint32_t)__cvta_generic_to_shared(p); }
__device__ __forceinline__ void mbar_init(uint32_t bar, uint32_t cnt) { asm volatile("mbarrier.init.shared::cta.b64 [%0], %1;" :: "r"(bar), "r"(cnt) : "memory"); }
__device__ __forceinline__ void mbar_expect_tx(uint32_t bar, uint32_t bytes) { asm volatile("mbarrier.arrive.expect_tx.shared::cta.b64 _, [%0], %1;" :: "r"(bar), "r"(bytes) : "memory"); }
__device__ __forceinline__ void mbar_arrive(uint32_t bar) { asm volatile("mbarrier.arrive.shared::cta.b64 _, [%0];" :: "r"(bar) : "memory"); }
__device__ __forceinline__ bool mbar_try(uint32_t bar, uint32_t parity) {
    uint32_t ok;
    asm volatile("{\n.reg .pred P1;\nmbarrier.try_wait.parity.shared::cta.b64 P1, [%1], %2;\nselp.u32 %0, 1, 0, P1;\n}" : "=r"(ok) : "r"(bar), "r"(parity) : "memory");
    return ok != 0;
}
__device__ __forceinline__ void mbar_wait(uint32_t bar, uint32_t parity) {
    uint32_t n = 0;
    while (!mbar_try(bar, parity)) { if (++n > (1u << 24)) __trap(); }
}
__device__ __forceinline__ void tma_2d(uint32_t dst, const void* map, uint32_t bar, int c0, int c1) {
    asm volatile("cp.async.bulk.tensor.2d.shared::cluster.global.mbarrier::complete_tx::bytes [%0], [%1, {%3, %4}], [%2];"
        :: "r"(dst), "l"(map), "r"(bar), "r"(c0), "r"(c1) : "memory");
}
__device__ __forceinline__ void tma_3d(uint32_t dst, const void* map, uint32_t bar, int c0, int c1, int c2) {
    asm volatile("cp.async.bulk.tensor.3d.shared::cluster.global.mbarrier::complete_tx::bytes [%0], [%1, {%3, %4, %5}], [%2];"
        :: "r"(dst), "l"(map), "r"(bar), "r"(c0), "r"(c1), "r"(c2) : "memory");
}
__device__ __forceinline__ void tma_4d(uint32_t dst, const void* map, uint32_t bar, int c0, int c1, int c2, int c3) {
    asm volatile("cp.async.bulk.tensor.4d.shared::cluster.global.mbarrier::complete_tx::bytes [%0], [%1, {%3, %4, %5, %6}], [%2];"
        :: "r"(dst), "l"(map), "r"(bar), "r"(c0), "r"(c1), "r"(c2), "r"(c3) : "memory");
}
__device__ __forceinline__ void bulk_g2s(uint32_t dst, const void* src, uint32_t bytes, uint32_t bar) {
    asm volatile("cp.async.bulk.shared::cluster.global.mbarrier::complete_tx::bytes [%0], [%1], %2, [%3];"
        :: "r"(dst), "l"(src), "r"(bytes), "r"(bar) : "memory");
}
__device__ __forceinline__ void prefetch_l2(const void* src, uint32_t bytes) {
    asm volatile("cp.async.bulk.prefetch.L2.global [%0], %1;" :: "l"(src), "r"(bytes) : "memory");
}
__device__ __forceinline__ void wgmma_fence() { asm volatile("wgmma.fence.sync.aligned;" ::: "memory"); }
__device__ __forceinline__ void wgmma_commit() { asm volatile("wgmma.commit_group.sync.aligned;" ::: "memory"); }
template <int N> __device__ __forceinline__ void wgmma_wait() { asm volatile("wgmma.wait_group.sync.aligned %0;" :: "n"(N) : "memory"); }
__device__ __forceinline__ void fence_async_smem() { asm volatile("fence.proxy.async.shared::cta;" ::: "memory"); }
__device__ __forceinline__ uint64_t desc_a(uint32_t addr) {
    return (uint64_t)((addr & 0x3FFFF) >> 4) | ((uint64_t)1 << 16) | ((uint64_t)(1024 >> 4) << 32) | ((uint64_t)1 << 62);
}
__device__ __forceinline__ uint64_t desc_b(uint32_t addr) {
    return (uint64_t)((addr & 0x3FFFF) >> 4) | ((uint64_t)(4096 >> 4) << 16) | ((uint64_t)(1024 >> 4) << 32) | ((uint64_t)1 << 62);
}
__device__ __forceinline__ uint32_t pack_bf16(float lo, float hi) {
    uint32_t r; asm("cvt.rn.bf16x2.f32 %0, %1, %2;" : "=r"(r) : "f"(hi), "f"(lo)); return r;
}
__device__ __forceinline__ uint32_t pack_bf16_relu(float lo, float hi) {
    uint32_t r; asm("cvt.rn.relu.bf16x2.f32 %0, %1, %2;" : "=r"(r) : "f"(hi), "f"(lo)); return r;
}
__device__ __forceinline__ uint32_t movmatrix(uint32_t a) {
    uint32_t d; asm volatile("movmatrix.sync.aligned.m8n8.trans.b16 %0, %1;" : "=r"(d) : "r"(a)); return d;
}
__device__ __forceinline__ void stmatrix_x4(uint32_t addr, uint32_t r0, uint32_t r1, uint32_t r2, uint32_t r3) {
    asm volatile("stmatrix.sync.aligned.m8n8.x4.shared.b16 [%0], {%1, %2, %3, %4};" :: "r"(addr), "r"(r0), "r"(r1), "r"(r2), "r"(r3) : "memory");
}
__device__ __forceinline__ uint4 lds128(uint32_t addr) {
    uint4 v; asm volatile("ld.shared.v4.b32 {%0, %1, %2, %3}, [%4];" : "=r"(v.x), "=r"(v.y), "=r"(v.z), "=r"(v.w) : "r"(addr) : "memory"); return v;
}
__device__ __forceinline__ void mma16816(float (&c)[4], uint32_t a0, uint32_t a1, uint32_t a2, uint32_t a3, uint32_t b0, uint32_t b1) {
    asm volatile("mma.sync.aligned.m16n8k16.row.col.f32.bf16.bf16.f32 {%0,%1,%2,%3}, {%4,%5,%6,%7}, {%8,%9}, {%0,%1,%2,%3};"
        : "+f"(c[0]), "+f"(c[1]), "+f"(c[2]), "+f"(c[3]) : "r"(a0), "r"(a1), "r"(a2), "r"(a3), "r"(b0), "r"(b1));
}
__device__ __forceinline__ void mma16816_z(float (&c)[4], uint32_t a0, uint32_t a1, uint32_t a2, uint32_t a3, uint32_t b0, uint32_t b1) {
    asm volatile("mma.sync.aligned.m16n8k16.row.col.f32.bf16.bf16.f32 {%0,%1,%2,%3}, {%4,%5,%6,%7}, {%8,%9}, {%10,%10,%10,%10};"
        : "=f"(c[0]), "=f"(c[1]), "=f"(c[2]), "=f"(c[3]) : "r"(a0), "r"(a1), "r"(a2), "r"(a3), "r"(b0), "r"(b1), "f"(0.f));
}
__device__ __forceinline__ float ex2(float x) { float y; asm("ex2.approx.ftz.f32 %0, %1;" : "=f"(y) : "f"(x)); return y; }
__device__ __forceinline__ unsigned ld_acquire(const unsigned* p) {
    unsigned v; asm volatile("ld.acquire.gpu.global.u32 %0, [%1];" : "=r"(v) : "l"(p) : "memory"); return v;
}
__device__ __forceinline__ void red_release(unsigned* p, unsigned v) {
    asm volatile("red.release.gpu.global.add.u32 [%0], %1;" :: "l"(p), "r"(v) : "memory");
}
__device__ __forceinline__ void wait_counter(const unsigned* p, unsigned target) {
    uint32_t n = 0;
    while ((int)(ld_acquire(p) - target) < 0) { if (++n > (1u << 22)) __trap(); }
}
__device__ __forceinline__ float bf_lo(uint32_t v) { return __uint_as_float(v << 16); }
__device__ __forceinline__ float bf_hi(uint32_t v) { return __uint_as_float(v & 0xFFFF0000u); }

__device__ __forceinline__ void wgmma_ss_n128(float (&d)[64], uint64_t da, uint64_t db, int scale_d) {
    asm volatile("{\n.reg .pred p;\nsetp.ne.b32 p, %66, 0;\n"
        "wgmma.mma_async.sync.aligned.m64n128k16.f32.bf16.bf16 {%0, %1, %2, %3, %4, %5, %6, %7, %8, %9, %10, %11, %12, %13, %14, %15, %16, %17, %18, %19, %20, %21, %22, %23, %24, %25, %26, %27, %28, %29, %30, %31, %32, %33, %34, %35, %36, %37, %38, %39, %40, %41, %42, %43, %44, %45, %46, %47, %48, %49, %50, %51, %52, %53, %54, %55, %56, %57, %58, %59, %60, %61, %62, %63}, %64, %65, p, 1, 1, 0, 1;\n}\n"
        : "+f"(d[0]), "+f"(d[1]), "+f"(d[2]), "+f"(d[3]), "+f"(d[4]), "+f"(d[5]), "+f"(d[6]), "+f"(d[7]), "+f"(d[8]), "+f"(d[9]), "+f"(d[10]), "+f"(d[11]), "+f"(d[12]), "+f"(d[13]), "+f"(d[14]), "+f"(d[15]), "+f"(d[16]), "+f"(d[17]), "+f"(d[18]), "+f"(d[19]), "+f"(d[20]), "+f"(d[21]), "+f"(d[22]), "+f"(d[23]), "+f"(d[24]), "+f"(d[25]), "+f"(d[26]), "+f"(d[27]), "+f"(d[28]), "+f"(d[29]), "+f"(d[30]), "+f"(d[31]), "+f"(d[32]), "+f"(d[33]), "+f"(d[34]), "+f"(d[35]), "+f"(d[36]), "+f"(d[37]), "+f"(d[38]), "+f"(d[39]), "+f"(d[40]), "+f"(d[41]), "+f"(d[42]), "+f"(d[43]), "+f"(d[44]), "+f"(d[45]), "+f"(d[46]), "+f"(d[47]), "+f"(d[48]), "+f"(d[49]), "+f"(d[50]), "+f"(d[51]), "+f"(d[52]), "+f"(d[53]), "+f"(d[54]), "+f"(d[55]), "+f"(d[56]), "+f"(d[57]), "+f"(d[58]), "+f"(d[59]), "+f"(d[60]), "+f"(d[61]), "+f"(d[62]), "+f"(d[63])
        : "l"(da), "l"(db), "r"(scale_d));
}
__device__ __forceinline__ void wgmma_ss_n192(float (&d)[96], uint64_t da, uint64_t db, int scale_d) {
    asm volatile("{\n.reg .pred p;\nsetp.ne.b32 p, %98, 0;\n"
        "wgmma.mma_async.sync.aligned.m64n192k16.f32.bf16.bf16 {%0, %1, %2, %3, %4, %5, %6, %7, %8, %9, %10, %11, %12, %13, %14, %15, %16, %17, %18, %19, %20, %21, %22, %23, %24, %25, %26, %27, %28, %29, %30, %31, %32, %33, %34, %35, %36, %37, %38, %39, %40, %41, %42, %43, %44, %45, %46, %47, %48, %49, %50, %51, %52, %53, %54, %55, %56, %57, %58, %59, %60, %61, %62, %63, %64, %65, %66, %67, %68, %69, %70, %71, %72, %73, %74, %75, %76, %77, %78, %79, %80, %81, %82, %83, %84, %85, %86, %87, %88, %89, %90, %91, %92, %93, %94, %95}, %96, %97, p, 1, 1, 0, 1;\n}\n"
        : "+f"(d[0]), "+f"(d[1]), "+f"(d[2]), "+f"(d[3]), "+f"(d[4]), "+f"(d[5]), "+f"(d[6]), "+f"(d[7]), "+f"(d[8]), "+f"(d[9]), "+f"(d[10]), "+f"(d[11]), "+f"(d[12]), "+f"(d[13]), "+f"(d[14]), "+f"(d[15]), "+f"(d[16]), "+f"(d[17]), "+f"(d[18]), "+f"(d[19]), "+f"(d[20]), "+f"(d[21]), "+f"(d[22]), "+f"(d[23]), "+f"(d[24]), "+f"(d[25]), "+f"(d[26]), "+f"(d[27]), "+f"(d[28]), "+f"(d[29]), "+f"(d[30]), "+f"(d[31]), "+f"(d[32]), "+f"(d[33]), "+f"(d[34]), "+f"(d[35]), "+f"(d[36]), "+f"(d[37]), "+f"(d[38]), "+f"(d[39]), "+f"(d[40]), "+f"(d[41]), "+f"(d[42]), "+f"(d[43]), "+f"(d[44]), "+f"(d[45]), "+f"(d[46]), "+f"(d[47]), "+f"(d[48]), "+f"(d[49]), "+f"(d[50]), "+f"(d[51]), "+f"(d[52]), "+f"(d[53]), "+f"(d[54]), "+f"(d[55]), "+f"(d[56]), "+f"(d[57]), "+f"(d[58]), "+f"(d[59]), "+f"(d[60]), "+f"(d[61]), "+f"(d[62]), "+f"(d[63]), "+f"(d[64]), "+f"(d[65]), "+f"(d[66]), "+f"(d[67]), "+f"(d[68]), "+f"(d[69]), "+f"(d[70]), "+f"(d[71]), "+f"(d[72]), "+f"(d[73]), "+f"(d[74]), "+f"(d[75]), "+f"(d[76]), "+f"(d[77]), "+f"(d[78]), "+f"(d[79]), "+f"(d[80]), "+f"(d[81]), "+f"(d[82]), "+f"(d[83]), "+f"(d[84]), "+f"(d[85]), "+f"(d[86]), "+f"(d[87]), "+f"(d[88]), "+f"(d[89]), "+f"(d[90]), "+f"(d[91]), "+f"(d[92]), "+f"(d[93]), "+f"(d[94]), "+f"(d[95])
        : "l"(da), "l"(db), "r"(scale_d));
}
__device__ __forceinline__ void wgmma_ss_n224(float (&d)[112], uint64_t da, uint64_t db, int scale_d) {
    asm volatile("{\n.reg .pred p;\nsetp.ne.b32 p, %114, 0;\n"
        "wgmma.mma_async.sync.aligned.m64n224k16.f32.bf16.bf16 {%0, %1, %2, %3, %4, %5, %6, %7, %8, %9, %10, %11, %12, %13, %14, %15, %16, %17, %18, %19, %20, %21, %22, %23, %24, %25, %26, %27, %28, %29, %30, %31, %32, %33, %34, %35, %36, %37, %38, %39, %40, %41, %42, %43, %44, %45, %46, %47, %48, %49, %50, %51, %52, %53, %54, %55, %56, %57, %58, %59, %60, %61, %62, %63, %64, %65, %66, %67, %68, %69, %70, %71, %72, %73, %74, %75, %76, %77, %78, %79, %80, %81, %82, %83, %84, %85, %86, %87, %88, %89, %90, %91, %92, %93, %94, %95, %96, %97, %98, %99, %100, %101, %102, %103, %104, %105, %106, %107, %108, %109, %110, %111}, %112, %113, p, 1, 1, 0, 1;\n}\n"
        : "+f"(d[0]), "+f"(d[1]), "+f"(d[2]), "+f"(d[3]), "+f"(d[4]), "+f"(d[5]), "+f"(d[6]), "+f"(d[7]), "+f"(d[8]), "+f"(d[9]), "+f"(d[10]), "+f"(d[11]), "+f"(d[12]), "+f"(d[13]), "+f"(d[14]), "+f"(d[15]), "+f"(d[16]), "+f"(d[17]), "+f"(d[18]), "+f"(d[19]), "+f"(d[20]), "+f"(d[21]), "+f"(d[22]), "+f"(d[23]), "+f"(d[24]), "+f"(d[25]), "+f"(d[26]), "+f"(d[27]), "+f"(d[28]), "+f"(d[29]), "+f"(d[30]), "+f"(d[31]), "+f"(d[32]), "+f"(d[33]), "+f"(d[34]), "+f"(d[35]), "+f"(d[36]), "+f"(d[37]), "+f"(d[38]), "+f"(d[39]), "+f"(d[40]), "+f"(d[41]), "+f"(d[42]), "+f"(d[43]), "+f"(d[44]), "+f"(d[45]), "+f"(d[46]), "+f"(d[47]), "+f"(d[48]), "+f"(d[49]), "+f"(d[50]), "+f"(d[51]), "+f"(d[52]), "+f"(d[53]), "+f"(d[54]), "+f"(d[55]), "+f"(d[56]), "+f"(d[57]), "+f"(d[58]), "+f"(d[59]), "+f"(d[60]), "+f"(d[61]), "+f"(d[62]), "+f"(d[63]), "+f"(d[64]), "+f"(d[65]), "+f"(d[66]), "+f"(d[67]), "+f"(d[68]), "+f"(d[69]), "+f"(d[70]), "+f"(d[71]), "+f"(d[72]), "+f"(d[73]), "+f"(d[74]), "+f"(d[75]), "+f"(d[76]), "+f"(d[77]), "+f"(d[78]), "+f"(d[79]), "+f"(d[80]), "+f"(d[81]), "+f"(d[82]), "+f"(d[83]), "+f"(d[84]), "+f"(d[85]), "+f"(d[86]), "+f"(d[87]), "+f"(d[88]), "+f"(d[89]), "+f"(d[90]), "+f"(d[91]), "+f"(d[92]), "+f"(d[93]), "+f"(d[94]), "+f"(d[95]), "+f"(d[96]), "+f"(d[97]), "+f"(d[98]), "+f"(d[99]), "+f"(d[100]), "+f"(d[101]), "+f"(d[102]), "+f"(d[103]), "+f"(d[104]), "+f"(d[105]), "+f"(d[106]), "+f"(d[107]), "+f"(d[108]), "+f"(d[109]), "+f"(d[110]), "+f"(d[111])
        : "l"(da), "l"(db), "r"(scale_d));
}
template <int N> __device__ __forceinline__ void fence_acc(float (&d)[N]) {
#pragma unroll
    for (int i = 0; i < N; i++) asm volatile("" : "+f"(d[i]) :: "memory");
}

struct Ring {
    int slot; uint32_t phase;
    __device__ __forceinline__ void next() { if (++slot == RING) { slot = 0; phase ^= 1; } }
};

__global__ void __launch_bounds__(384, 1)
fused_kernel(const __grid_constant__ CUtensorMap map_x, const __grid_constant__ CUtensorMap map_qkv,
             const __grid_constant__ CUtensorMap map_w1, const __grid_constant__ CUtensorMap map_w2,
             const __grid_constant__ CUtensorMap map_wo,
             const __nv_bfloat16* __restrict__ gate_w, __nv_bfloat16* __restrict__ out,
             const uint8_t* __restrict__ w1p, const uint8_t* __restrict__ w2p, const uint8_t* __restrict__ wop)
{
    extern __shared__ __align__(1024) uint8_t smem_raw[];
    const uint32_t sb = smem_u32(smem_raw);
    const int tid = threadIdx.x, warp = tid >> 5, lane = tid & 31;
    const int ti = blockIdx.x >> 3, tj = blockIdx.x & 7;

    if (tid == 256) {
        if (sb & 1023) __trap();
        for (int s = 0; s < RING; s++) { mbar_init(sb + B_FULL + 8 * s, 1); mbar_init(sb + B_EMPTY + 8 * s, 8); }
        for (int s = 0; s < 8; s++) mbar_init(sb + B_XFULL + 8 * s, 1);
        mbar_init(sb + B_GREADY, 2); mbar_init(sb + B_EREADY, 1); mbar_init(sb + B_KVDONE, 8);
        for (int s = 0; s < 4; s++) mbar_init(sb + B_PDONE + 8 * s, 8);
        asm volatile("fence.mbarrier_init.release.cluster;" ::: "memory");
        fence_async_smem();
        for (int kb = 0; kb < 8; kb++) {
            mbar_expect_tx(sb + B_XFULL + 8 * kb, 16384);
            tma_2d(sb + X_OFF + kb * 16384, &map_x, sb + B_XFULL + 8 * kb, kb * 64, ti * 128);
            if (kb < 3) {
                for (int s = 2 * kb; s < 2 * kb + 2; s++) {
                    mbar_expect_tx(sb + B_FULL + 8 * s, 12288);
                    tma_4d(sb + RING_OFF + s * SLOT, &map_qkv, sb + B_FULL + 8 * s, 0, 32 * s, tj, 0);
                }
            }
        }
    }
    __syncthreads();

    if (warp >= 8) {
        asm volatile("setmaxnreg.dec.sync.aligned.u32 88;");
        if (warp == 8) {
            if (lane == 0) {
                Ring r{0, 0};
                for (int n = RING; n < S_END; n++) {
                    const uint32_t full = sb + B_FULL + 8 * r.slot, dst = sb + RING_OFF + r.slot * SLOT;
                    if (n == S_KV) {
                        mbar_wait(sb + B_EREADY, 0);
                        unsigned epoch; asm volatile("ld.shared.u32 %0, [%1];" : "=r"(epoch) : "r"(sb + EPOCH_OFF) : "memory");
                        for (int d = 2; d >= 0; d--)
                            if (ti - d >= 0) wait_counter(&g_kvcnt[((ti - d) * 8 + tj) * 32], epoch + 1);
                        asm volatile("fence.proxy.async.global;" ::: "memory");
                    }
                    mbar_wait(sb + B_EMPTY + 8 * r.slot, r.phase);
                    if (n < S_FFN1) {
                        mbar_expect_tx(full, 12288);
                        tma_4d(dst, &map_qkv, full, 0, 32 * n, tj, 0);
                    } else if (n < S_KV) {
                        mbar_expect_tx(full, 16384);
                        for (int c = 0; c < 4; c++) tma_2d(dst + c * 4096, &map_w1, full, 224 * tj + 64 * c, 32 * (n - S_FFN1));
                    } else if (n < S_FFN2) {
                        const int m = n - S_KV, head = tj * 4 + (m >> 1);
                        const int bbase = 8 * ti - 16, b0 = bbase < 0 ? 0 : bbase;
                        const uint32_t bytes = (uint32_t)(8 * ti + 8 - b0) * 512;
                        const uint4* src = ((m & 1) ? g_vf : g_kf) + (head * 128 + b0) * 32;
                        mbar_expect_tx(full, bytes);
                        bulk_g2s(dst + (b0 - bbase) * 512, src, bytes, full);
                    } else {
                        mbar_expect_tx(full, 16384);
                        for (int h = 0; h < 2; h++) {
                            const int u = 2 * (n - S_FFN2) + h, q = u / 9, rr = u % 9;
                            if (rr < 7) tma_3d(dst + h * 8192, &map_w2, full, 0, 224 * tj + 32 * rr, 2 * q);
                            else        tma_3d(dst + h * 8192, &map_wo, full, 0, 64 * tj + 32 * (rr - 7), 2 * q);
                        }
                    }
                    r.next();
                }
            }
        } else if (warp == 9) {
            if (lane == 0) {
                unsigned t = atomicAdd(&g_ticket, 1u);
                asm volatile("st.shared.u32 [%0], %1;" :: "r"(sb + EPOCH_OFF), "r"(t >> 7) : "memory");
                mbar_arrive(sb + B_EREADY);
                mbar_wait(sb + B_XFULL + 8 * 7, 0);
                prefetch_l2(w1p + (size_t)blockIdx.x * 14336, 14336);
                prefetch_l2(w2p + (size_t)blockIdx.x * 14336, 14336);
                prefetch_l2(wop + (size_t)blockIdx.x * 4096, 4096);
                mbar_wait(sb + B_KVDONE, 0);
                red_release(&g_kvcnt[blockIdx.x * 32], 1u);
            }
            __syncwarp();
            for (int q = 0; q < 4; q++) {
                mbar_wait(sb + B_PDONE + 8 * q, 0);
                if (lane < 8) red_release(&g_pcnt[((ti * 8 + lane) * 4 + q) * 32], 1u);
                __syncwarp();
            }
        } else {
            const int hw = warp - 10, r = lane >> 2, c = lane & 3;
            float z[8];
#pragma unroll
            for (int gi = 0; gi < 8; gi++) z[gi] = 0.f;
            for (int kb = 0; kb < 8; kb++) {
                mbar_wait(sb + B_XFULL + 8 * kb, 0);
#pragma unroll
                for (int h = 0; h < 2; h++) {
                    const int chunk = c + 4 * (h ^ (r & 1));
                    const uint4 gw = __ldg(reinterpret_cast<const uint4*>(gate_w + kb * 64 + chunk * 8));
                    const float w0 = bf_lo(gw.x), w1 = bf_hi(gw.x), w2 = bf_lo(gw.y), w3 = bf_hi(gw.y);
                    const float w4 = bf_lo(gw.z), w5 = bf_hi(gw.z), w6 = bf_lo(gw.w), w7 = bf_hi(gw.w);
#pragma unroll
                    for (int gi = 0; gi < 8; gi++) {
                        const int row = (hw * 8 + gi) * 8 + r;
                        const uint4 xv = lds128(sb + X_OFF + kb * 16384 + row * 128 + ((chunk ^ r) << 4));
                        float a = z[gi];
                        a = fmaf(bf_lo(xv.x), w0, a); a = fmaf(bf_hi(xv.x), w1, a);
                        a = fmaf(bf_lo(xv.y), w2, a); a = fmaf(bf_hi(xv.y), w3, a);
                        a = fmaf(bf_lo(xv.z), w4, a); a = fmaf(bf_hi(xv.z), w5, a);
                        a = fmaf(bf_lo(xv.w), w6, a); a = fmaf(bf_hi(xv.w), w7, a);
                        z[gi] = a;
                    }
                }
            }
#pragma unroll
            for (int gi = 0; gi < 8; gi++) {
                float a = z[gi];
                a += __shfl_xor_sync(0xffffffffu, a, 1);
                a += __shfl_xor_sync(0xffffffffu, a, 2);
                const float gv = 1.f / (1.f + __expf(-a));
                if (c == 0) asm volatile("st.shared.f32 [%0], %1;" :: "r"(sb + G_OFF + ((hw * 8 + gi) * 8 + r) * 4), "f"(gv) : "memory");
            }
            __syncwarp();
            if (lane == 0) mbar_arrive(sb + B_GREADY);
            mbar_wait(sb + B_EREADY, 0);
            unsigned epoch; asm volatile("ld.shared.u32 %0, [%1];" : "=r"(epoch) : "r"(sb + EPOCH_OFF) : "memory");
            for (int q = 0; q < 4; q++) {
                if (lane == 0) wait_counter(&g_pcnt[((ti * 8 + tj) * 4 + q) * 32], 8 * (epoch + 1));
                __syncwarp();
                const uint4* pb = g_part + (size_t)(((ti * 8 + tj) * 4 + q) * 8) * 256 + lane;
                for (int t2 = hw; t2 < 8; t2 += 2) {
                    uint4 v[8];
#pragma unroll
                    for (int s = 0; s < 8; s++) v[s] = __ldcg(pb + s * 256 + t2 * 32);
                    float a[8];
#pragma unroll
                    for (int e = 0; e < 8; e++) a[e] = 0.f;
#pragma unroll
                    for (int s = 0; s < 8; s++) {
                        a[0] += bf_lo(v[s].x); a[1] += bf_hi(v[s].x); a[2] += bf_lo(v[s].y); a[3] += bf_hi(v[s].y);
                        a[4] += bf_lo(v[s].z); a[5] += bf_hi(v[s].z); a[6] += bf_lo(v[s].w); a[7] += bf_hi(v[s].w);
                    }
                    uint32_t* o0 = reinterpret_cast<uint32_t*>(out + (size_t)(ti * 128 + tj * 16 + r) * 512 + q * 128 + t2 * 16 + 2 * c);
                    o0[0] = pack_bf16(a[0], a[1]);
                    o0[4] = pack_bf16(a[4], a[5]);
                    o0[8 * 256] = pack_bf16(a[2], a[3]);
                    o0[8 * 256 + 4] = pack_bf16(a[6], a[7]);
                }
            }
        }
    } else {
        asm volatile("setmaxnreg.inc.sync.aligned.u32 208;");
        const int wg = warp >> 2, g = lane >> 2, c = lane & 3;
        const uint32_t xa = sb + X_OFF + wg * 8192;
        Ring r{0, 0};
        uint32_t qf[4][4];
        TS(0);
        {
            float acc[96];
            int prev = 0;
            for (int s = 0; s < N_QKV; s++) {
                if (!(s & 1)) mbar_wait(sb + B_XFULL + 8 * (s >> 1), 0);
                mbar_wait(sb + B_FULL + 8 * r.slot, r.phase);
                if (s == 0) TS(1);
                const uint32_t bs = sb + RING_OFF + r.slot * SLOT, as = xa + (s >> 1) * 16384 + (s & 1) * 64;
                wgmma_fence();
                wgmma_ss_n192(acc, desc_a(as), desc_b(bs), s);
                wgmma_ss_n192(acc, desc_a(as + 32), desc_b(bs + 2048), 1);
                wgmma_commit();
                if (s > 0) { wgmma_wait<1>(); if (lane == 0) mbar_arrive(sb + B_EMPTY + 8 * prev); }
                prev = r.slot; r.next();
            }
            wgmma_wait<0>();
            fence_acc(acc);
            if (lane == 0) mbar_arrive(sb + B_EMPTY + 8 * prev);
            TS(2);
            const int blk = ti * 8 + warp;
#pragma unroll
            for (int hh = 0; hh < 4; hh++) {
                const float* t0 = &acc[8 * hh]; const float* t1 = &acc[8 * hh + 4];
                qf[hh][0] = pack_bf16(t0[0], t0[1]); qf[hh][1] = pack_bf16(t0[2], t0[3]);
                qf[hh][2] = pack_bf16(t1[0], t1[1]); qf[hh][3] = pack_bf16(t1[2], t1[3]);
                const float* k0 = &acc[32 + 8 * hh]; const float* k1 = &acc[32 + 8 * hh + 4];
                uint4 kv;
                kv.x = pack_bf16(k0[0], k0[1]); kv.y = pack_bf16(k1[0], k1[1]);
                kv.z = pack_bf16(k0[2], k0[3]); kv.w = pack_bf16(k1[2], k1[3]);
                g_kf[((tj * 4 + hh) * 128 + blk) * 32 + lane] = kv;
                const float* v0 = &acc[64 + 8 * hh]; const float* v1 = &acc[64 + 8 * hh + 4];
                uint4 vv;
                vv.x = movmatrix(pack_bf16(v0[0], v0[1])); vv.y = movmatrix(pack_bf16(v0[2], v0[3]));
                vv.z = movmatrix(pack_bf16(v1[0], v1[1])); vv.w = movmatrix(pack_bf16(v1[2], v1[3]));
                g_vf[((tj * 4 + hh) * 128 + blk) * 32 + lane] = vv;
            }
            __syncwarp();
            if (lane == 0) mbar_arrive(sb + B_KVDONE);
        }
        TS(3);
        const int wrow = (warp & 3) * 16;
        float g0, g1;
        {
            float acc[112];
            int prev = 0;
            for (int s = 0; s < N_FFN1; s++) {
                mbar_wait(sb + B_FULL + 8 * r.slot, r.phase);
                const uint32_t bs = sb + RING_OFF + r.slot * SLOT, as = xa + (s >> 1) * 16384 + (s & 1) * 64;
                wgmma_fence();
                wgmma_ss_n224(acc, desc_a(as), desc_b(bs), s);
                wgmma_ss_n224(acc, desc_a(as + 32), desc_b(bs + 2048), 1);
                wgmma_commit();
                if (s > 0) { wgmma_wait<1>(); if (lane == 0) mbar_arrive(sb + B_EMPTY + 8 * prev); }
                prev = r.slot; r.next();
            }
            wgmma_wait<0>();
            fence_acc(acc);
            if (lane == 0) mbar_arrive(sb + B_EMPTY + 8 * prev);
            TS(4);
            mbar_wait(sb + B_GREADY, 0);
            asm volatile("ld.shared.f32 %0, [%1];" : "=f"(g0) : "r"(sb + G_OFF + (warp * 16 + g) * 4) : "memory");
            asm volatile("ld.shared.f32 %0, [%1];" : "=f"(g1) : "r"(sb + G_OFF + (warp * 16 + g + 8) * 4) : "memory");
            const float s0 = 1.f - g0, s1 = 1.f - g1;
            asm volatile("bar.sync %0, 128;" :: "r"(1 + wg) : "memory");
            const uint32_t strow = xa + (wrow + ((lane >> 3) & 1) * 8 + (lane & 7)) * 128;
#pragma unroll
            for (int p = 0; p < 14; p++) {
                const int nt = 2 * p + (lane >> 4);
                const float* a = &acc[8 * p];
                stmatrix_x4(strow + (p >> 2) * 16384 + (((nt & 7) ^ (lane & 7)) << 4),
                            pack_bf16_relu(a[0] * s0, a[1] * s0), pack_bf16_relu(a[2] * s1, a[3] * s1),
                            pack_bf16_relu(a[4] * s0, a[5] * s0), pack_bf16_relu(a[6] * s1, a[7] * s1));
            }
        }
        TS(5);
        {
            const float SC = 0.25f * 1.4426950408889634f;
            const int gb0 = 8 * ti - 16 + warp;
#pragma unroll 1
            for (int hh = 0; hh < 4; hh++) {
                const int slotK = r.slot; mbar_wait(sb + B_FULL + 8 * r.slot, r.phase); r.next();
                const int slotV = r.slot; const uint32_t phV = r.phase; r.next();
                const uint32_t kbase = sb + RING_OFF + slotK * SLOT + warp * 512 + lane * 16;
                const uint32_t vbase = sb + RING_OFF + slotV * SLOT + warp * 512 + lane * 16;
                uint32_t q0, q1, q2, q3;
                if (hh == 0) { q0 = qf[0][0]; q1 = qf[0][1]; q2 = qf[0][2]; q3 = qf[0][3]; }
                else if (hh == 1) { q0 = qf[1][0]; q1 = qf[1][1]; q2 = qf[1][2]; q3 = qf[1][3]; }
                else if (hh == 2) { q0 = qf[2][0]; q1 = qf[2][1]; q2 = qf[2][2]; q3 = qf[2][3]; }
                else { q0 = qf[3][0]; q1 = qf[3][1]; q2 = qf[3][2]; q3 = qf[3][3]; }
                float s[16][2][4];
                const float NEG = -INFINITY;
                {
                    const uint4 kd = lds128(kbase + 16 * 512);
                    mma16816_z(s[0][0], q0, q1, q2, q3, kd.x, kd.y);
                    mma16816_z(s[0][1], q0, q1, q2, q3, kd.z, kd.w);
                    float f[2][4];
                    if (gb0 >= 0) {
                        const uint4 kf = lds128(kbase);
                        mma16816_z(f[0], q0, q1, q2, q3, kf.x, kf.y);
                        mma16816_z(f[1], q0, q1, q2, q3, kf.z, kf.w);
                    } else {
#pragma unroll
                        for (int e = 0; e < 4; e++) { f[0][e] = NEG; f[1][e] = NEG; }
                    }
#pragma unroll
                    for (int u = 0; u < 2; u++)
#pragma unroll
                        for (int e = 0; e < 4; e++) {
                            const int row = g + 8 * (e >> 1), col = 8 * u + 2 * c + (e & 1);
                            s[0][u][e] = (col > row) ? f[u][e] : s[0][u][e];
                        }
                }
#pragma unroll
                for (int t = 1; t < 16; t++) {
                    if (gb0 + t >= 0) {
                        const uint4 kf = lds128(kbase + t * 512);
                        mma16816_z(s[t][0], q0, q1, q2, q3, kf.x, kf.y);
                        mma16816_z(s[t][1], q0, q1, q2, q3, kf.z, kf.w);
                    } else {
#pragma unroll
                        for (int e = 0; e < 4; e++) { s[t][0][e] = NEG; s[t][1][e] = NEG; }
                    }
                }
                __syncwarp();
                if (lane == 0) mbar_arrive(sb + B_EMPTY + 8 * slotK);
                float m0 = NEG, m1 = NEG;
#pragma unroll
                for (int t = 0; t < 16; t++)
#pragma unroll
                    for (int u = 0; u < 2; u++) {
                        m0 = fmaxf(m0, fmaxf(s[t][u][0], s[t][u][1]));
                        m1 = fmaxf(m1, fmaxf(s[t][u][2], s[t][u][3]));
                    }
                m0 = fmaxf(m0, __shfl_xor_sync(0xffffffffu, m0, 1)); m1 = fmaxf(m1, __shfl_xor_sync(0xffffffffu, m1, 1));
                m0 = fmaxf(m0, __shfl_xor_sync(0xffffffffu, m0, 2)); m1 = fmaxf(m1, __shfl_xor_sync(0xffffffffu, m1, 2));
                const float mc0 = m0 * SC, mc1 = m1 * SC;
                float l0 = 0.f, l1 = 0.f;
                float o[2][4];
#pragma unroll
                for (int e = 0; e < 4; e++) { o[0][e] = 0.f; o[1][e] = 0.f; }
                mbar_wait(sb + B_FULL + 8 * slotV, phV);
#pragma unroll
                for (int t = 0; t < 16; t++) {
                    float p[2][4];
#pragma unroll
                    for (int u = 0; u < 2; u++) {
                        p[u][0] = ex2(fmaf(s[t][u][0], SC, -mc0)); p[u][1] = ex2(fmaf(s[t][u][1], SC, -mc0));
                        p[u][2] = ex2(fmaf(s[t][u][2], SC, -mc1)); p[u][3] = ex2(fmaf(s[t][u][3], SC, -mc1));
                        l0 += p[u][0] + p[u][1]; l1 += p[u][2] + p[u][3];
                    }
                    if (t == 0) {
                        float pd[2][4], pf[2][4];
#pragma unroll
                        for (int u = 0; u < 2; u++)
#pragma unroll
                            for (int e = 0; e < 4; e++) {
                                const int row = g + 8 * (e >> 1), col = 8 * u + 2 * c + (e & 1);
                                pf[u][e] = (col > row) ? p[u][e] : 0.f;
                                pd[u][e] = (col > row) ? 0.f : p[u][e];
                            }
                        {
                            const uint4 vf = lds128(vbase + 16 * 512);
                            const uint32_t a0 = pack_bf16(pd[0][0], pd[0][1]), a1 = pack_bf16(pd[0][2], pd[0][3]);
                            const uint32_t a2 = pack_bf16(pd[1][0], pd[1][1]), a3 = pack_bf16(pd[1][2], pd[1][3]);
                            mma16816(o[0], a0, a1, a2, a3, vf.x, vf.y);
                            mma16816(o[1], a0, a1, a2, a3, vf.z, vf.w);
                        }
                        if (gb0 >= 0) {
                            const uint4 vf = lds128(vbase);
                            const uint32_t a0 = pack_bf16(pf[0][0], pf[0][1]), a1 = pack_bf16(pf[0][2], pf[0][3]);
                            const uint32_t a2 = pack_bf16(pf[1][0], pf[1][1]), a3 = pack_bf16(pf[1][2], pf[1][3]);
                            mma16816(o[0], a0, a1, a2, a3, vf.x, vf.y);
                            mma16816(o[1], a0, a1, a2, a3, vf.z, vf.w);
                        }
                    } else if (gb0 + t >= 0) {
                        const uint4 vf = lds128(vbase + t * 512);
                        const uint32_t a0 = pack_bf16(p[0][0], p[0][1]), a1 = pack_bf16(p[0][2], p[0][3]);
                        const uint32_t a2 = pack_bf16(p[1][0], p[1][1]), a3 = pack_bf16(p[1][2], p[1][3]);
                        mma16816(o[0], a0, a1, a2, a3, vf.x, vf.y);
                        mma16816(o[1], a0, a1, a2, a3, vf.z, vf.w);
                    }
                }
                __syncwarp();
                if (lane == 0) mbar_arrive(sb + B_EMPTY + 8 * slotV);
                l0 += __shfl_xor_sync(0xffffffffu, l0, 1); l1 += __shfl_xor_sync(0xffffffffu, l1, 1);
                l0 += __shfl_xor_sync(0xffffffffu, l0, 2); l1 += __shfl_xor_sync(0xffffffffu, l1, 2);
                const float f0 = g0 / l0, f1 = g1 / l1;
                const uint32_t strow = xa + 4 * 16384 + (wrow + ((lane >> 3) & 1) * 8 + (lane & 7)) * 128;
                stmatrix_x4(strow + (((2 * hh + (lane >> 4)) ^ (lane & 7)) << 4),
                            pack_bf16(o[0][0] * f0, o[0][1] * f0), pack_bf16(o[0][2] * f1, o[0][3] * f1),
                            pack_bf16(o[1][0] * f0, o[1][1] * f0), pack_bf16(o[1][2] * f1, o[1][3] * f1));
            }
        }
        fence_async_smem();
        asm volatile("bar.sync %0, 128;" :: "r"(1 + wg) : "memory");
        TS(6);
        {
            float accA[64], accB[64];
            uint4* pdst = g_part + (size_t)((ti * 8 + warp) * 4 * 8 + tj) * 256 + lane;
            auto epilogue = [&](float (&acc)[64], int q) {
                fence_acc(acc);
                uint4* p = pdst + (size_t)q * 8 * 256;
#pragma unroll
                for (int t2 = 0; t2 < 8; t2++) {
                    uint4 v;
                    v.x = pack_bf16(acc[8 * t2 + 0], acc[8 * t2 + 1]); v.y = pack_bf16(acc[8 * t2 + 2], acc[8 * t2 + 3]);
                    v.z = pack_bf16(acc[8 * t2 + 4], acc[8 * t2 + 5]); v.w = pack_bf16(acc[8 * t2 + 6], acc[8 * t2 + 7]);
                    p[t2 * 32] = v;
                }
                __syncwarp();
                if (lane == 0) mbar_arrive(sb + B_PDONE + 8 * q);
            };
            int rel = r.slot;
#pragma unroll 1
            for (int half = 0; half < 2; half++) {
#pragma unroll
                for (int u = 0; u < 18; u++) {
                    const int rr = u % 9;
                    if (!(u & 1)) mbar_wait(sb + B_FULL + 8 * r.slot, r.phase);
                    const uint32_t bs = sb + RING_OFF + r.slot * SLOT + (u & 1) * 8192;
                    const int vk = rr < 7 ? 32 * rr : 256 + 32 * (rr - 7);
                    const uint32_t as = xa + (vk >> 6) * 16384 + (vk & 63) * 2;
                    wgmma_fence();
                    if (u < 9) {
                        wgmma_ss_n128(accA, desc_a(as), desc_b(bs), rr);
                        wgmma_ss_n128(accA, desc_a(as + 32), desc_b(bs + 2048), 1);
                    } else {
                        wgmma_ss_n128(accB, desc_a(as), desc_b(bs), rr);
                        wgmma_ss_n128(accB, desc_a(as + 32), desc_b(bs + 2048), 1);
                    }
                    wgmma_commit();
                    if (u & 1) r.next();
                    wgmma_wait<1>();
                    if (!(u & 1) && (u > 0 || half > 0)) {
                        if (lane == 0) mbar_arrive(sb + B_EMPTY + 8 * rel);
                        if (++rel == RING) rel = 0;
                    }
                    if (u == 9) epilogue(accA, 2 * half);
                    if (u == 0 && half == 1) epilogue(accB, 1);
                }
            }
            wgmma_wait<0>();
            TS(7);
            epilogue(accB, 3);
        }
        TS(8);
    }
}

typedef CUresult (*PFN_encodeTiled)(CUtensorMap*, CUtensorMapDataType, cuuint32_t, void*, const cuuint64_t*, const cuuint64_t*,
                                    const cuuint32_t*, const cuuint32_t*, CUtensorMapInterleave, CUtensorMapSwizzle,
                                    CUtensorMapL2promotion, CUtensorMapFloatOOBfill);

void make_map(PFN_encodeTiled enc, CUtensorMap* m, const void* base, int rank, const cuuint64_t* dims, const cuuint64_t* strides, const cuuint32_t* box) {
    cuuint32_t es[5] = {1, 1, 1, 1, 1};
    enc(m, CU_TENSOR_MAP_DATA_TYPE_BFLOAT16, (cuuint32_t)rank, const_cast<void*>(base), dims, strides, box, es,
        CU_TENSOR_MAP_INTERLEAVE_NONE, CU_TENSOR_MAP_SWIZZLE_128B, CU_TENSOR_MAP_L2_PROMOTION_L2_256B, CU_TENSOR_MAP_FLOAT_OOB_FILL_NONE);
}

}

extern "C" void kernel_launch(void* const* d_in, const int* in_sizes, int n_in, void* d_out, int out_size) {
    (void)in_sizes; (void)n_in; (void)out_size;
    const void* x = d_in[0]; const void* wqkv = d_in[1]; const void* wo = d_in[2];
    const void* w1 = d_in[4]; const void* w2 = d_in[5]; const void* gate_w = d_in[6];
    static PFN_encodeTiled enc = nullptr;
    if (!enc) {
        void* fn = nullptr; cudaDriverEntryPointQueryResult st;
        cudaGetDriverEntryPoint("cuTensorMapEncodeTiled", &fn, cudaEnableDefault, &st);
        enc = (PFN_encodeTiled)fn;
        cudaFuncSetAttribute(fused_kernel, cudaFuncAttributeMaxDynamicSharedMemorySize, SMEM_BYTES);
    }
    CUtensorMap mx, mqkv, mw1, mw2, mwo;
    { cuuint64_t d[2] = {512, 2048}, s[1] = {1024}; cuuint32_t b[2] = {64, 128}; make_map(enc, &mx, x, 2, d, s, b); }
    { cuuint64_t d[4] = {64, 512, 8, 3}, s[3] = {3072, 128, 1024}; cuuint32_t b[4] = {64, 32, 1, 3}; make_map(enc, &mqkv, wqkv, 4, d, s, b); }
    { cuuint64_t d[2] = {1792, 512}, s[1] = {3584}; cuuint32_t b[2] = {64, 32}; make_map(enc, &mw1, w1, 2, d, s, b); }
    { cuuint64_t d[3] = {64, 1792, 8}, s[2] = {1024, 128}; cuuint32_t b[3] = {64, 32, 2}; make_map(enc, &mw2, w2, 3, d, s, b); }
    { cuuint64_t d[3] = {64, 512, 8}, s[2] = {1024, 128}; cuuint32_t b[3] = {64, 32, 2}; make_map(enc, &mwo, wo, 3, d, s, b); }
    fused_kernel<<<128, 384, SMEM_BYTES, cudaStreamPerThread>>>(mx, mqkv, mw1, mw2, mwo, (const __nv_bfloat16*)gate_w, (__nv_bfloat16*)d_out,
                                           (const uint8_t*)w1, (const uint8_t*)w2, (const uint8_t*)wo);
}
```

```cpp
#include <cuda_runtime.h>
#include <cuda_bf16.h>
#include <cuda.h>
#include <stdint.h>

namespace {

#define PF1_AT 1
#define PF2_AT 7
#define LEAD1 2
#define LEAD2 2
constexpr int RING = 6;
constexpr int SLOT = 16384;
constexpr uint32_t X_OFF = 0;
constexpr uint32_t RING_OFF = 131072;
constexpr uint32_t BAR_OFF = RING_OFF + RING * SLOT;
constexpr uint32_t B_FULL = BAR_OFF, B_EMPTY = BAR_OFF + 64, B_XFULL = BAR_OFF + 128, B_XDEAD = BAR_OFF + 192,
                   B_EREADY = BAR_OFF + 200, B_KVDONE = BAR_OFF + 208, B_PDONE = BAR_OFF + 216,
                   B_KVREADY = BAR_OFF + 248, B_EFULL = BAR_OFF + 264;
constexpr uint32_t EPOCH_OFF = BAR_OFF + 256;
constexpr uint32_t SMEM_BYTES = BAR_OFF + 1024;

constexpr int N_QKV = 16, N_FFN1 = 16, N_KV = 8, N_EXTRA = 3, N_FFN2 = 18 - N_EXTRA;
constexpr int S_FFN1 = N_QKV, S_KV = S_FFN1 + N_FFN1, S_FFN2 = S_KV + N_KV;

__device__ uint4 g_kf[32 * 128 * 32];
__device__ uint4 g_vf[32 * 128 * 32];
__device__ uint4 g_part[16 * 8 * 4 * 8 * 8 * 32];
__device__ unsigned g_ticket;
__device__ unsigned g_kvcnt[128 * 32];
__device__ unsigned g_pcnt[16 * 8 * 4 * 32];
#define TS(k) do {} while (0)
#define TS2(k) do {} while (0)
#define TS2X(k) do {} while (0)
#define TSX(k) do {} while (0)
#define TSG(k) do {} while (0)

__device__ __forceinline__ uint32_t smem_u32(const void* p) { return (uint32_t)__cvta_generic_to_shared(p); }
__device__ __forceinline__ void mbar_init(uint32_t bar, uint32_t cnt) { asm volatile("mbarrier.init.shared::cta.b64 [%0], %1;" :: "r"(bar), "r"(cnt) : "memory"); }
__device__ __forceinline__ void mbar_expect_tx(uint32_t bar, uint32_t bytes) { asm volatile("mbarrier.arrive.expect_tx.shared::cta.b64 _, [%0], %1;" :: "r"(bar), "r"(bytes) : "memory"); }
__device__ __forceinline__ void mbar_expect_only(uint32_t bar, uint32_t bytes) { asm volatile("mbarrier.expect_tx.relaxed.cta.shared::cta.b64 [%0], %1;" :: "r"(bar), "r"(bytes) : "memory"); }
__device__ __forceinline__ void mbar_arrive(uint32_t bar) { asm volatile("mbarrier.arrive.shared::cta.b64 _, [%0];" :: "r"(bar) : "memory"); }
__device__ __forceinline__ bool mbar_try(uint32_t bar, uint32_t parity) {
    uint32_t ok;
    asm volatile("{\n.reg .pred P1;\nmbarrier.try_wait.parity.shared::cta.b64 P1, [%1], %2;\nselp.u32 %0, 1, 0, P1;\n}" : "=r"(ok) : "r"(bar), "r"(parity) : "memory");
    return ok != 0;
}
__device__ __forceinline__ void mbar_wait(uint32_t bar, uint32_t parity) {
    asm volatile("{\n.reg .pred P1, P2;\n.reg .u32 n;\nmov.u32 n, 0;\n"
                 "WAIT_LOOP:\n"
                 "mbarrier.try_wait.parity.shared::cta.b64 P1, [%0], %1;\n"
                 "@P1 bra WAIT_DONE;\n"
                 "add.u32 n, n, 1;\n"
                 "setp.lt.u32 P2, n, 0x400000;\n"
                 "@P2 bra WAIT_LOOP;\n"
                 "WAIT_DONE:\n}" :: "r"(bar), "r"(parity) : "memory");
}
__device__ __forceinline__ void tma_2d(uint32_t dst, const void* map, uint32_t bar, int c0, int c1) {
    asm volatile("cp.async.bulk.tensor.2d.shared::cluster.global.mbarrier::complete_tx::bytes [%0], [%1, {%3, %4}], [%2];"
        :: "r"(dst), "l"(map), "r"(bar), "r"(c0), "r"(c1) : "memory");
}
__device__ __forceinline__ void tma_3d(uint32_t dst, const void* map, uint32_t bar, int c0, int c1, int c2) {
    asm volatile("cp.async.bulk.tensor.3d.shared::cluster.global.mbarrier::complete_tx::bytes [%0], [%1, {%3, %4, %5}], [%2];"
        :: "r"(dst), "l"(map), "r"(bar), "r"(c0), "r"(c1), "r"(c2) : "memory");
}
__device__ __forceinline__ void tma_4d(uint32_t dst, const void* map, uint32_t bar, int c0, int c1, int c2, int c3) {
    asm volatile("cp.async.bulk.tensor.4d.shared::cluster.global.mbarrier::complete_tx::bytes [%0], [%1, {%3, %4, %5, %6}], [%2];"
        :: "r"(dst), "l"(map), "r"(bar), "r"(c0), "r"(c1), "r"(c2), "r"(c3) : "memory");
}
__device__ __forceinline__ void bulk_g2s(uint32_t dst, const void* src, uint32_t bytes, uint32_t bar) {
    asm volatile("cp.async.bulk.shared::cluster.global.mbarrier::complete_tx::bytes [%0], [%1], %2, [%3];"
        :: "r"(dst), "l"(src), "r"(bytes), "r"(bar) : "memory");
}
__device__ __forceinline__ void prefetch_l2(const void* src, uint32_t bytes) {
    asm volatile("cp.async.bulk.prefetch.L2.global [%0], %1;" :: "l"(src), "r"(bytes) : "memory");
}
__device__ __forceinline__ bool elect_one() {
    uint32_t p;
    asm volatile("{\n.reg .pred P;\nelect.sync _|P, 0xffffffff;\nselp.u32 %0, 1, 0, P;\n}" : "=r"(p));
    return p != 0;
}
__device__ __forceinline__ void wgmma_fence() { asm volatile("wgmma.fence.sync.aligned;" ::: "memory"); }
__device__ __forceinline__ void wgmma_commit() { asm volatile("wgmma.commit_group.sync.aligned;" ::: "memory"); }
template <int N> __device__ __forceinline__ void wgmma_wait() { asm volatile("wgmma.wait_group.sync.aligned %0;" :: "n"(N) : "memory"); }
__device__ __forceinline__ void fence_async_smem() { asm volatile("fence.proxy.async.shared::cta;" ::: "memory"); }
__device__ __forceinline__ uint64_t desc_a(uint32_t addr) {
    return (uint64_t)((addr & 0x3FFFF) >> 4) | ((uint64_t)1 << 16) | ((uint64_t)(1024 >> 4) << 32) | ((uint64_t)1 << 62);
}
__device__ __forceinline__ uint64_t desc_b(uint32_t addr) {
    return (uint64_t)((addr & 0x3FFFF) >> 4) | ((uint64_t)(4096 >> 4) << 16) | ((uint64_t)(1024 >> 4) << 32) | ((uint64_t)1 << 62);
}
__device__ __forceinline__ uint32_t pack_bf16(float lo, float hi) {
    uint32_t r; asm("cvt.rn.bf16x2.f32 %0, %1, %2;" : "=r"(r) : "f"(hi), "f"(lo)); return r;
}
__device__ __forceinline__ uint32_t pack_bf16_relu(float lo, float hi) {
    uint32_t r; asm("cvt.rn.relu.bf16x2.f32 %0, %1, %2;" : "=r"(r) : "f"(hi), "f"(lo)); return r;
}
__device__ __forceinline__ uint32_t movmatrix(uint32_t a) {
    uint32_t d; asm volatile("movmatrix.sync.aligned.m8n8.trans.b16 %0, %1;" : "=r"(d) : "r"(a)); return d;
}
__device__ __forceinline__ void stmatrix_x4(uint32_t addr, uint32_t r0, uint32_t r1, uint32_t r2, uint32_t r3) {
    asm volatile("stmatrix.sync.aligned.m8n8.x4.shared.b16 [%0], {%1, %2, %3, %4};" :: "r"(addr), "r"(r0), "r"(r1), "r"(r2), "r"(r3) : "memory");
}
__device__ __forceinline__ uint4 lds128(uint32_t addr) {
    uint4 v; asm volatile("ld.shared.v4.b32 {%0, %1, %2, %3}, [%4];" : "=r"(v.x), "=r"(v.y), "=r"(v.z), "=r"(v.w) : "r"(addr) : "memory"); return v;
}
__device__ __forceinline__ void mma16816(float (&c)[4], uint32_t a0, uint32_t a1, uint32_t a2, uint32_t a3, uint32_t b0, uint32_t b1) {
    asm volatile("mma.sync.aligned.m16n8k16.row.col.f32.bf16.bf16.f32 {%0,%1,%2,%3}, {%4,%5,%6,%7}, {%8,%9}, {%0,%1,%2,%3};"
        : "+f"(c[0]), "+f"(c[1]), "+f"(c[2]), "+f"(c[3]) : "r"(a0), "r"(a1), "r"(a2), "r"(a3), "r"(b0), "r"(b1));
}
__device__ __forceinline__ void mma16816_c(float (&c)[4], uint32_t a0, uint32_t a1, uint32_t a2, uint32_t a3, uint32_t b0, uint32_t b1, float ci) {
    asm volatile("mma.sync.aligned.m16n8k16.row.col.f32.bf16.bf16.f32 {%0,%1,%2,%3}, {%4,%5,%6,%7}, {%8,%9}, {%10,%10,%10,%10};"
        : "=f"(c[0]), "=f"(c[1]), "=f"(c[2]), "=f"(c[3]) : "r"(a0), "r"(a1), "r"(a2), "r"(a3), "r"(b0), "r"(b1), "f"(ci));
}
__device__ __forceinline__ int opaque(int v) { asm volatile("" : "+r"(v)); return v; }
__device__ __forceinline__ float ex2(float x) { float y; asm("ex2.approx.ftz.f32 %0, %1;" : "=f"(y) : "f"(x)); return y; }
__device__ __forceinline__ unsigned ld_acquire(const unsigned* p) {
    unsigned v; asm volatile("ld.acquire.gpu.global.u32 %0, [%1];" : "=r"(v) : "l"(p) : "memory"); return v;
}
__device__ __forceinline__ void red_release(unsigned* p, unsigned v) {
    asm volatile("red.release.gpu.global.add.u32 [%0], %1;" :: "l"(p), "r"(v) : "memory");
}
__device__ __forceinline__ void wait_counter(const unsigned* p, unsigned target) {
    uint32_t n = 0;
    while ((int)(ld_acquire(p) - target) < 0) { if (++n > (1u << 20)) break; }
}
__device__ __forceinline__ uint4 ldg_weak(const uint4* p) {
    uint4 v; asm volatile("ld.global.L1::no_allocate.v4.b32 {%0, %1, %2, %3}, [%4];" : "=r"(v.x), "=r"(v.y), "=r"(v.z), "=r"(v.w) : "l"(p) : "memory"); return v;
}
__device__ __forceinline__ float bf_lo(uint32_t v) { return __uint_as_float(v << 16); }
__device__ __forceinline__ float bf_hi(uint32_t v) { return __uint_as_float(v & 0xFFFF0000u); }

__device__ __forceinline__ void wgmma_ss_n128(float (&d)[64], uint64_t da, uint64_t db, int scale_d) {
    asm volatile("{\n.reg .pred p;\nsetp.ne.b32 p, %66, 0;\n"
        "wgmma.mma_async.sync.aligned.m64n128k16.f32.bf16.bf16 {%0, %1, %2, %3, %4, %5, %6, %7, %8, %9, %10, %11, %12, %13, %14, %15, %16, %17, %18, %19, %20, %21, %22, %23, %24, %25, %26, %27, %28, %29, %30, %31, %32, %33, %34, %35, %36, %37, %38, %39, %40, %41, %42, %43, %44, %45, %46, %47, %48, %49, %50, %51, %52, %53, %54, %55, %56, %57, %58, %59, %60, %61, %62, %63}, %64, %65, p, 1, 1, 0, 1;\n}\n"
        : "+f"(d[0]), "+f"(d[1]), "+f"(d[2]), "+f"(d[3]), "+f"(d[4]), "+f"(d[5]), "+f"(d[6]), "+f"(d[7]), "+f"(d[8]), "+f"(d[9]), "+f"(d[10]), "+f"(d[11]), "+f"(d[12]), "+f"(d[13]), "+f"(d[14]), "+f"(d[15]), "+f"(d[16]), "+f"(d[17]), "+f"(d[18]), "+f"(d[19]), "+f"(d[20]), "+f"(d[21]), "+f"(d[22]), "+f"(d[23]), "+f"(d[24]), "+f"(d[25]), "+f"(d[26]), "+f"(d[27]), "+f"(d[28]), "+f"(d[29]), "+f"(d[30]), "+f"(d[31]), "+f"(d[32]), "+f"(d[33]), "+f"(d[34]), "+f"(d[35]), "+f"(d[36]), "+f"(d[37]), "+f"(d[38]), "+f"(d[39]), "+f"(d[40]), "+f"(d[41]), "+f"(d[42]), "+f"(d[43]), "+f"(d[44]), "+f"(d[45]), "+f"(d[46]), "+f"(d[47]), "+f"(d[48]), "+f"(d[49]), "+f"(d[50]), "+f"(d[51]), "+f"(d[52]), "+f"(d[53]), "+f"(d[54]), "+f"(d[55]), "+f"(d[56]), "+f"(d[57]), "+f"(d[58]), "+f"(d[59]), "+f"(d[60]), "+f"(d[61]), "+f"(d[62]), "+f"(d[63])
        : "l"(da), "l"(db), "r"(scale_d));
}
__device__ __forceinline__ void wgmma_ss_n200(float (&d)[100], uint64_t da, uint64_t db, int scale_d) {
    asm volatile("{\n.reg .pred p;\nsetp.ne.b32 p, %102, 0;\n"
        "wgmma.mma_async.sync.aligned.m64n200k16.f32.bf16.bf16 {%0, %1, %2, %3, %4, %5, %6, %7, %8, %9, %10, %11, %12, %13, %14, %15, %16, %17, %18, %19, %20, %21, %22, %23, %24, %25, %26, %27, %28, %29, %30, %31, %32, %33, %34, %35, %36, %37, %38, %39, %40, %41, %42, %43, %44, %45, %46, %47, %48, %49, %50, %51, %52, %53, %54, %55, %56, %57, %58, %59, %60, %61, %62, %63, %64, %65, %66, %67, %68, %69, %70, %71, %72, %73, %74, %75, %76, %77, %78, %79, %80, %81, %82, %83, %84, %85, %86, %87, %88, %89, %90, %91, %92, %93, %94, %95, %96, %97, %98, %99}, %100, %101, p, 1, 1, 0, 1;\n}\n"
        : "+f"(d[0]), "+f"(d[1]), "+f"(d[2]), "+f"(d[3]), "+f"(d[4]), "+f"(d[5]), "+f"(d[6]), "+f"(d[7]), "+f"(d[8]), "+f"(d[9]), "+f"(d[10]), "+f"(d[11]), "+f"(d[12]), "+f"(d[13]), "+f"(d[14]), "+f"(d[15]), "+f"(d[16]), "+f"(d[17]), "+f"(d[18]), "+f"(d[19]), "+f"(d[20]), "+f"(d[21]), "+f"(d[22]), "+f"(d[23]), "+f"(d[24]), "+f"(d[25]), "+f"(d[26]), "+f"(d[27]), "+f"(d[28]), "+f"(d[29]), "+f"(d[30]), "+f"(d[31]), "+f"(d[32]), "+f"(d[33]), "+f"(d[34]), "+f"(d[35]), "+f"(d[36]), "+f"(d[37]), "+f"(d[38]), "+f"(d[39]), "+f"(d[40]), "+f"(d[41]), "+f"(d[42]), "+f"(d[43]), "+f"(d[44]), "+f"(d[45]), "+f"(d[46]), "+f"(d[47]), "+f"(d[48]), "+f"(d[49]), "+f"(d[50]), "+f"(d[51]), "+f"(d[52]), "+f"(d[53]), "+f"(d[54]), "+f"(d[55]), "+f"(d[56]), "+f"(d[57]), "+f"(d[58]), "+f"(d[59]), "+f"(d[60]), "+f"(d[61]), "+f"(d[62]), "+f"(d[63]), "+f"(d[64]), "+f"(d[65]), "+f"(d[66]), "+f"(d[67]), "+f"(d[68]), "+f"(d[69]), "+f"(d[70]), "+f"(d[71]), "+f"(d[72]), "+f"(d[73]), "+f"(d[74]), "+f"(d[75]), "+f"(d[76]), "+f"(d[77]), "+f"(d[78]), "+f"(d[79]), "+f"(d[80]), "+f"(d[81]), "+f"(d[82]), "+f"(d[83]), "+f"(d[84]), "+f"(d[85]), "+f"(d[86]), "+f"(d[87]), "+f"(d[88]), "+f"(d[89]), "+f"(d[90]), "+f"(d[91]), "+f"(d[92]), "+f"(d[93]), "+f"(d[94]), "+f"(d[95]), "+f"(d[96]), "+f"(d[97]), "+f"(d[98]), "+f"(d[99])
        : "l"(da), "l"(db), "r"(scale_d));
}
__device__ __forceinline__ void wgmma_ss_n224(float (&d)[112], uint64_t da, uint64_t db, int scale_d) {
    asm volatile("{\n.reg .pred p;\nsetp.ne.b32 p, %114, 0;\n"
        "wgmma.mma_async.sync.aligned.m64n224k16.f32.bf16.bf16 {%0, %1, %2, %3, %4, %5, %6, %7, %8, %9, %10, %11, %12, %13, %14, %15, %16, %17, %18, %19, %20, %21, %22, %23, %24, %25, %26, %27, %28, %29, %30, %31, %32, %33, %34, %35, %36, %37, %38, %39, %40, %41, %42, %43, %44, %45, %46, %47, %48, %49, %50, %51, %52, %53, %54, %55, %56, %57, %58, %59, %60, %61, %62, %63, %64, %65, %66, %67, %68, %69, %70, %71, %72, %73, %74, %75, %76, %77, %78, %79, %80, %81, %82, %83, %84, %85, %86, %87, %88, %89, %90, %91, %92, %93, %94, %95, %96, %97, %98, %99, %100, %101, %102, %103, %104, %105, %106, %107, %108, %109, %110, %111}, %112, %113, p, 1, 1, 0, 1;\n}\n"
        : "+f"(d[0]), "+f"(d[1]), "+f"(d[2]), "+f"(d[3]), "+f"(d[4]), "+f"(d[5]), "+f"(d[6]), "+f"(d[7]), "+f"(d[8]), "+f"(d[9]), "+f"(d[10]), "+f"(d[11]), "+f"(d[12]), "+f"(d[13]), "+f"(d[14]), "+f"(d[15]), "+f"(d[16]), "+f"(d[17]), "+f"(d[18]), "+f"(d[19]), "+f"(d[20]), "+f"(d[21]), "+f"(d[22]), "+f"(d[23]), "+f"(d[24]), "+f"(d[25]), "+f"(d[26]), "+f"(d[27]), "+f"(d[28]), "+f"(d[29]), "+f"(d[30]), "+f"(d[31]), "+f"(d[32]), "+f"(d[33]), "+f"(d[34]), "+f"(d[35]), "+f"(d[36]), "+f"(d[37]), "+f"(d[38]), "+f"(d[39]), "+f"(d[40]), "+f"(d[41]), "+f"(d[42]), "+f"(d[43]), "+f"(d[44]), "+f"(d[45]), "+f"(d[46]), "+f"(d[47]), "+f"(d[48]), "+f"(d[49]), "+f"(d[50]), "+f"(d[51]), "+f"(d[52]), "+f"(d[53]), "+f"(d[54]), "+f"(d[55]), "+f"(d[56]), "+f"(d[57]), "+f"(d[58]), "+f"(d[59]), "+f"(d[60]), "+f"(d[61]), "+f"(d[62]), "+f"(d[63]), "+f"(d[64]), "+f"(d[65]), "+f"(d[66]), "+f"(d[67]), "+f"(d[68]), "+f"(d[69]), "+f"(d[70]), "+f"(d[71]), "+f"(d[72]), "+f"(d[73]), "+f"(d[74]), "+f"(d[75]), "+f"(d[76]), "+f"(d[77]), "+f"(d[78]), "+f"(d[79]), "+f"(d[80]), "+f"(d[81]), "+f"(d[82]), "+f"(d[83]), "+f"(d[84]), "+f"(d[85]), "+f"(d[86]), "+f"(d[87]), "+f"(d[88]), "+f"(d[89]), "+f"(d[90]), "+f"(d[91]), "+f"(d[92]), "+f"(d[93]), "+f"(d[94]), "+f"(d[95]), "+f"(d[96]), "+f"(d[97]), "+f"(d[98]), "+f"(d[99]), "+f"(d[100]), "+f"(d[101]), "+f"(d[102]), "+f"(d[103]), "+f"(d[104]), "+f"(d[105]), "+f"(d[106]), "+f"(d[107]), "+f"(d[108]), "+f"(d[109]), "+f"(d[110]), "+f"(d[111])
        : "l"(da), "l"(db), "r"(scale_d));
}
template <int N> __device__ __forceinline__ void fence_acc(float (&d)[N]) {
#pragma unroll
    for (int i = 0; i < N; i++) asm volatile("" : "+f"(d[i]) :: "memory");
}

__device__ __forceinline__ void reduce_store(const uint4 (&v)[8], __nv_bfloat16* __restrict__ out, int ti, int tj, int q, int t2, int lane) {
    float a[8];
#pragma unroll
    for (int e = 0; e < 8; e++) a[e] = 0.f;
#pragma unroll
    for (int s = 0; s < 8; s++) {
        a[0] += bf_lo(v[s].x); a[1] += bf_hi(v[s].x); a[2] += bf_lo(v[s].y); a[3] += bf_hi(v[s].y);
        a[4] += bf_lo(v[s].z); a[5] += bf_hi(v[s].z); a[6] += bf_lo(v[s].w); a[7] += bf_hi(v[s].w);
    }
    const uint32_t lo0 = pack_bf16(a[0], a[1]), lo1 = pack_bf16(a[4], a[5]);
    const uint32_t hi0 = pack_bf16(a[2], a[3]), hi1 = pack_bf16(a[6], a[7]);
    const bool odd = lane & 1;
    const uint32_t sl = __shfl_xor_sync(0xffffffffu, odd ? lo0 : lo1, 1);
    const uint32_t sh = __shfl_xor_sync(0xffffffffu, odd ? hi0 : hi1, 1);
    const uint2 wl = odd ? make_uint2(sl, lo1) : make_uint2(lo0, sl);
    const uint2 wh = odd ? make_uint2(sh, hi1) : make_uint2(hi0, sh);
    __nv_bfloat16* o = out + (size_t)(ti * 128 + tj * 16 + (lane >> 2)) * 512 + q * 128 + t2 * 16 + (odd ? 8 : 0) + (lane & 2) * 2;
    *reinterpret_cast<uint2*>(o) = wl;
    *reinterpret_cast<uint2*>(o + 8 * 512) = wh;
}
__device__ __forceinline__ uint4* part_ptr(int ti, int owner, int q, int t2, int lane) {
    return g_part + (size_t)(((ti * 8 + owner) * 4 + q) * 8) * 256 + t2 * 32 + lane;
}
__device__ __forceinline__ void reduce_unit(__nv_bfloat16* __restrict__ out, int ti, int tj, int q, int t2, int lane) {
    const uint4* pb = part_ptr(ti, tj, q, t2, lane);
    uint4 v[8];
#pragma unroll
    for (int s = 0; s < 8; s++) v[s] = ldg_weak(pb + s * 256);
    reduce_store(v, out, ti, tj, q, t2, lane);
}
__device__ __forceinline__ uint4 ldg_relaxed(const uint4* p) {
    uint4 v; asm volatile("ld.relaxed.gpu.global.v4.b32 {%0, %1, %2, %3}, [%4];" : "=r"(v.x), "=r"(v.y), "=r"(v.z), "=r"(v.w) : "l"(p) : "memory"); return v;
}
__device__ __forceinline__ void stg_relaxed(uint4* p, uint4 v) {
    asm volatile("st.relaxed.gpu.global.v4.b32 [%0], {%1, %2, %3, %4};" :: "l"(p), "r"(v.x), "r"(v.y), "r"(v.z), "r"(v.w) : "memory");
}
__device__ __forceinline__ uint32_t nz(uint32_t w) { return w ? w : 0x80000000u; }

#define PWAIT() mbar_wait(sb + B_EMPTY + 8 * r.slot, r.phase)
#define CWAIT() mbar_wait(sb + B_FULL + 8 * r.slot, r.phase)
template <bool B> struct BoolTag { static constexpr bool value = B; };
struct Ring {
    int slot; uint32_t phase;
    __device__ __forceinline__ void next() { if (++slot == RING) { slot = 0; phase ^= 1; } }
};

__global__ void __launch_bounds__(384, 1)
fused_kernel(const __grid_constant__ CUtensorMap map_x, const __grid_constant__ CUtensorMap map_qkv,
             const __grid_constant__ CUtensorMap map_w1, const __grid_constant__ CUtensorMap map_w2,
             const __grid_constant__ CUtensorMap map_wo, const __grid_constant__ CUtensorMap map_w1a,
             const __nv_bfloat16* __restrict__ gate_w, __nv_bfloat16* __restrict__ out,
             const uint8_t* __restrict__ w1p, const uint8_t* __restrict__ w2p, const uint8_t* __restrict__ wop,
             const uint8_t* __restrict__ xp, const uint8_t* __restrict__ wqkvp)
{
    extern __shared__ __align__(1024) uint8_t smem_raw[];
    const uint32_t sb = smem_u32(smem_raw);
    const int tid = threadIdx.x, warp = tid >> 5, lane = tid & 31;
    const int ti = blockIdx.x >> 3, tj = blockIdx.x & 7;

    if (tid == 0) { TSG(31); TSX(0); }
    if (tid == 320) {
        asm volatile("prefetch.tensormap [%0];" :: "l"(&map_x) : "memory");
        asm volatile("prefetch.tensormap [%0];" :: "l"(&map_qkv) : "memory");
        asm volatile("prefetch.tensormap [%0];" :: "l"(&map_w1) : "memory");
        asm volatile("prefetch.tensormap [%0];" :: "l"(&map_w2) : "memory");
        asm volatile("prefetch.tensormap [%0];" :: "l"(&map_wo) : "memory");
        asm volatile("prefetch.tensormap [%0];" :: "l"(&map_w1a) : "memory");
    }
    uint32_t gwv[N_QKV / 2];
    if (warp == 8) {
        const unsigned short* gws = reinterpret_cast<const unsigned short*>(gate_w);
#pragma unroll
        for (int n = 0; n < N_QKV / 2; n++) gwv[n] = (uint32_t)__ldg(gws + 64 * n + lane) | ((uint32_t)__ldg(gws + 64 * n + 32 + lane) << 16);
    }
    if (tid == 256) {
        for (int s = 0; s < RING; s++) { mbar_init(sb + B_FULL + 8 * s, 1); mbar_init(sb + B_EMPTY + 8 * s, 8); }
        for (int s = 0; s < 8; s++) mbar_init(sb + B_XFULL + 8 * s, 1);
        mbar_init(sb + B_XDEAD, 8); mbar_init(sb + B_EREADY, 1); mbar_init(sb + B_KVDONE, 8); mbar_init(sb + B_KVREADY, 1);
        for (int s = 0; s < 3; s++) { mbar_init(sb + B_PDONE + 8 * s, 8); mbar_init(sb + B_EFULL + 8 * s, 1); }
        asm volatile("fence.mbarrier_init.release.cluster;" ::: "memory");
        fence_async_smem();
        mbar_expect_tx(sb + B_XFULL, 16384);
        tma_2d(sb + X_OFF, &map_x, sb + B_XFULL, 0, ti * 128);
        mbar_expect_only(sb + B_FULL, 12288);
        tma_4d(sb + RING_OFF, &map_qkv, sb + B_FULL, 0, 0, tj, 0);
    }
    __syncthreads();

    if (warp >= 8) {
        asm volatile("setmaxnreg.dec.sync.aligned.u32 56;");
        if (warp == 8) {
            Ring r{0, 1};
            const bool leader = elect_one();
#pragma unroll
            for (int n = 0; n < N_QKV; n++) {
                const uint32_t full = sb + B_FULL + 8 * r.slot, dst = sb + RING_OFF + r.slot * SLOT;
                if (n > 0) {
                    if (!(n & 1) && leader) {
                        mbar_expect_tx(sb + B_XFULL + 8 * (n >> 1), 16384);
                        tma_2d(sb + X_OFF + (n >> 1) * 16384, &map_x, sb + B_XFULL + 8 * (n >> 1), (n >> 1) * 64, ti * 128);
                    }
                    if (n >= RING) PWAIT();
                    if (leader) {
                        mbar_expect_only(full, 12288);
                        tma_4d(dst, &map_qkv, full, 0, 32 * n, tj, 0);
                    }
                }
                const uint32_t gv = (n & 1) ? (gwv[n >> 1] >> 16) : (gwv[n >> 1] & 0xFFFFu);
                asm volatile("st.shared.v4.b32 [%0], {%1, %2, %2, %2};" :: "r"(dst + 12288 + lane * 128 + ((lane & 7) << 4)), "r"(gv), "r"(0) : "memory");
                fence_async_smem();
                __syncwarp();
                if (leader) mbar_arrive(full);
                r.next();
            }
#pragma unroll 1
            for (int n = 0; n < N_FFN1; n++) {
                const uint32_t full = sb + B_FULL + 8 * r.slot, dst = sb + RING_OFF + r.slot * SLOT;
                PWAIT();
                if (leader) {
                    mbar_expect_tx(full, 16384);
                    tma_4d(dst, &map_w1a, full, 0, 32 * n, 0, tj);
                    tma_2d(dst + 3 * 4096, &map_w1, full, 224 * tj + 192, 32 * n);
                }
                r.next();
            }
            if (lane == 0) TSX(10);
            mbar_wait(sb + B_KVREADY, 0);
            asm volatile("fence.proxy.async.global;" ::: "memory");
            if (lane == 0) TSX(11);
            {
                const int bbase = 8 * ti - 16, b0 = bbase < 0 ? 0 : bbase;
                const uint32_t bytes = (uint32_t)(8 * ti + 8 - b0) * 512;
#pragma unroll 1
                for (int m = 0; m < N_KV; m++) {
                    const uint32_t full = sb + B_FULL + 8 * r.slot, dst = sb + RING_OFF + r.slot * SLOT;
                    if (m == RING) {
                        mbar_wait(sb + B_XDEAD, 0);
                        if (leader) {
#pragma unroll
                            for (int e = 0; e < N_EXTRA; e++) {
                                mbar_expect_tx(sb + B_EFULL + 8 * e, 16384);
                                tma_3d(sb + X_OFF + (5 + e) * 16384, &map_w2, sb + B_EFULL + 8 * e, 0, 224 * tj + 64 * e, 0);
                                tma_3d(sb + X_OFF + (5 + e) * 16384 + 8192, &map_w2, sb + B_EFULL + 8 * e, 0, 224 * tj + 64 * e + 32, 0);
                            }
                        }
                    }
                    PWAIT();
                    if (leader) {
                        const uint4* src = ((m & 1) ? g_vf : g_kf) + ((tj * 4 + (m >> 1)) * 128 + b0) * 32;
                        mbar_expect_tx(full, bytes);
                        bulk_g2s(dst + (b0 - bbase) * 512, src, bytes, full);
                    }
                    r.next();
                }
            }
            {
                int q = 0, rr = 2 * N_EXTRA;
#pragma unroll 1
                for (int n = 0; n < N_FFN2; n++) {
                    const uint32_t full = sb + B_FULL + 8 * r.slot, dst = sb + RING_OFF + r.slot * SLOT;
                    PWAIT();
                    if (leader) mbar_expect_tx(full, 16384);
#pragma unroll
                    for (int h = 0; h < 2; h++) {
                        const bool isw2 = rr < 7;
                        const int row = isw2 ? 224 * tj + 32 * rr : 64 * tj + 32 * (rr - 7);
                        if (leader) tma_3d(dst + h * 8192, isw2 ? &map_w2 : &map_wo, full, 0, row, 2 * q);
                        if (++rr == 9) { rr = 0; q++; }
                    }
                    r.next();
                }
            }
        } else if (warp == 9) {
            unsigned epoch = 0;
            if (lane == 0) {
                epoch = atomicAdd(&g_ticket, 1u) >> 7;
                asm volatile("st.shared.u32 [%0], %1;" :: "r"(sb + EPOCH_OFF), "r"(epoch) : "memory");
                mbar_arrive(sb + B_EREADY);
                mbar_wait(sb + B_XFULL + 8 * PF1_AT, 0);
                prefetch_l2(w1p + (size_t)blockIdx.x * 14336, 14336);
                mbar_wait(sb + B_XFULL + 8 * PF2_AT, 0);
                prefetch_l2(w2p + (size_t)blockIdx.x * 14336, 14336);
                prefetch_l2(wop + (size_t)blockIdx.x * 4096, 4096);
                mbar_wait(sb + B_KVDONE, 0);
                red_release(&g_kvcnt[blockIdx.x * 32], 1u);
            }
            epoch = __shfl_sync(0xffffffffu, epoch, 0);
            if (lane < 3 && ti - lane >= 0) wait_counter(&g_kvcnt[((ti - lane) * 8 + tj) * 32], epoch + 1);
            __syncwarp();
            if (lane == 0) mbar_arrive(sb + B_KVREADY);
            for (int q = 0; q < 3; q++) {
                mbar_wait(sb + B_PDONE + 8 * q, 0);
                if (lane < 8) red_release(&g_pcnt[((ti * 8 + lane) * 4 + q) * 32], 1u);
                __syncwarp();
            }
        } else {
            const int hw = warp - 10;
            mbar_wait(sb + B_EREADY, 0);
            unsigned epoch; asm volatile("ld.shared.u32 %0, [%1];" : "=r"(epoch) : "r"(sb + EPOCH_OFF) : "memory");
#pragma unroll 1
            for (int q = 0; q < 2; q++) {
                mbar_wait(sb + B_PDONE + 8 * q, 0);
                if (lane == 0) wait_counter(&g_pcnt[((ti * 8 + tj) * 4 + q) * 32], 8 * (epoch + 1));
                __syncwarp();
                if (tid == 320) TSX(13 + 2 * q);
#pragma unroll 1
                for (int t2 = hw; t2 < 8; t2 += 2) reduce_unit(out, ti, tj, q, t2, lane);
                if (tid == 320) TSX(14 + 2 * q);
            }
        }
    } else {
        asm volatile("setmaxnreg.inc.sync.aligned.u32 224;");
        const int wg = warp >> 2, g = lane >> 2, c = lane & 3;
        const uint32_t xa = sb + X_OFF + wg * 8192;
        Ring r{0, 0};
        uint32_t qf[4][4];
        float g0, g1;
        TS(9);
        {
            float acc[100];
            int prev = 0;
            if (wg == 1) asm volatile("bar.sync 3, 256;" ::: "memory");
            for (int s = 0; s < N_QKV; s++) {
                if (!(s & 1)) mbar_wait(sb + B_XFULL + 8 * (s >> 1), 0);
                CWAIT();
                if (s == 0) TS(1);
                if (s == 2) TS(28);
                if (s == 6) TS(29);
                if (s == 10) TS(20);
                const uint32_t bs = sb + RING_OFF + r.slot * SLOT, as = xa + (s >> 1) * 16384 + (s & 1) * 64;
                wgmma_fence();
                wgmma_ss_n200(acc, desc_a(as), desc_b(bs), s);
                wgmma_ss_n200(acc, desc_a(as + 32), desc_b(bs + 2048), 1);
                wgmma_commit();
                if (wg == 0 && s == LEAD1) asm volatile("bar.arrive 3, 256;" ::: "memory");
                if (s > 0) { wgmma_wait<1>(); if (lane == 0) mbar_arrive(sb + B_EMPTY + 8 * prev); }
                prev = r.slot; r.next();
            }
            wgmma_wait<0>();
            fence_acc(acc);
            if (lane == 0) mbar_arrive(sb + B_EMPTY + 8 * prev);
            TS(2);
            const int blk = ti * 8 + warp;
#pragma unroll
            for (int hh = 0; hh < 4; hh++) {
                const float* t0 = &acc[8 * hh]; const float* t1 = &acc[8 * hh + 4];
                qf[hh][0] = pack_bf16(t0[0], t0[1]); qf[hh][1] = pack_bf16(t0[2], t0[3]);
                qf[hh][2] = pack_bf16(t1[0], t1[1]); qf[hh][3] = pack_bf16(t1[2], t1[3]);
                const float* k0 = &acc[32 + 8 * hh]; const float* k1 = &acc[32 + 8 * hh + 4];
                uint4 kv;
                kv.x = pack_bf16(k0[0], k0[1]); kv.y = pack_bf16(k1[0], k1[1]);
                kv.z = pack_bf16(k0[2], k0[3]); kv.w = pack_bf16(k1[2], k1[3]);
                g_kf[((tj * 4 + hh) * 128 + blk) * 32 + lane] = kv;
                const float* v0 = &acc[64 + 8 * hh]; const float* v1 = &acc[64 + 8 * hh + 4];
                uint4 vv;
                vv.x = movmatrix(pack_bf16(v0[0], v0[1])); vv.y = movmatrix(pack_bf16(v0[2], v0[3]));
                vv.z = movmatrix(pack_bf16(v1[0], v1[1])); vv.w = movmatrix(pack_bf16(v1[2], v1[3]));
                g_vf[((tj * 4 + hh) * 128 + blk) * 32 + lane] = vv;
            }
            __syncwarp();
            if (lane == 0) mbar_arrive(sb + B_KVDONE);
            const float z0 = __shfl_sync(0xffffffffu, acc[96], lane & ~3), z1 = __shfl_sync(0xffffffffu, acc[98], lane & ~3);
            g0 = 1.f / (1.f + __expf(-z0)); g1 = 1.f / (1.f + __expf(-z1));
        }
        TS(3);
        const int wrow = (warp & 3) * 16;
        {
            float acc[112];
            int prev = 0;
            for (int s = 0; s < N_FFN1; s++) {
                CWAIT();
                const uint32_t bs = sb + RING_OFF + r.slot * SLOT, as = xa + (s >> 1) * 16384 + (s & 1) * 64;
                wgmma_fence();
                wgmma_ss_n224(acc, desc_a(as), desc_b(bs), s);
                wgmma_ss_n224(acc, desc_a(as + 32), desc_b(bs + 2048), 1);
                wgmma_commit();
                if (s > 0) { wgmma_wait<1>(); if (lane == 0) mbar_arrive(sb + B_EMPTY + 8 * prev); }
                prev = r.slot; r.next();
            }
            wgmma_wait<0>();
            fence_acc(acc);
            if (lane == 0) mbar_arrive(sb + B_EMPTY + 8 * prev);
            TS(4);
            if (lane == 0) mbar_arrive(sb + B_XDEAD);
            const float s0 = 1.f - g0, s1 = 1.f - g1;
            asm volatile("bar.sync %0, 128;" :: "r"(1 + wg) : "memory");
            const uint32_t strow = xa + (wrow + ((lane >> 3) & 1) * 8 + (lane & 7)) * 128;
#pragma unroll
            for (int p = 0; p < 14; p++) {
                const int nt = 2 * p + (lane >> 4);
                const float* a = &acc[8 * p];
                stmatrix_x4(strow + (p >> 2) * 16384 + (((nt & 7) ^ (lane & 7)) << 4),
                            pack_bf16_relu(a[0] * s0, a[1] * s0), pack_bf16_relu(a[2] * s1, a[3] * s1),
                            pack_bf16_relu(a[4] * s0, a[5] * s0), pack_bf16_relu(a[6] * s1, a[7] * s1));
            }
        }
        TS(5);
        {
            const float SC = 0.25f * 1.4426950408889634f;
            const int gb0 = 8 * ti - 16 + warp;
            int slotK = 0, slotV = 0;
            const uint32_t ostore = xa + 4 * 16384 + (wrow + ((lane >> 3) & 1) * 8 + (lane & 7)) * 128;
#define NHEADS 4
#define ATT_KWAIT(kb) do { slotK = r.slot; CWAIT(); kb = sb + RING_OFF + slotK * SLOT + warp * 512 + lane * 16; r.next(); } while (0)
#define ATT_VWAIT(vb) do { slotV = r.slot; CWAIT(); vb = sb + RING_OFF + slotV * SLOT + warp * 512 + lane * 16; r.next(); TS(21 + hh); } while (0)
#define ATT_KREL() do { __syncwarp(); if (lane == 0) mbar_arrive(sb + B_EMPTY + 8 * slotK); } while (0)
#define ATT_VREL() do { __syncwarp(); if (lane == 0) mbar_arrive(sb + B_EMPTY + 8 * slotV); } while (0)
#define ATT_NEXTQ(h) do { \
                if ((h) == 1) { q0 = qf[1][0]; q1 = qf[1][1]; q2 = qf[1][2]; q3 = qf[1][3]; } \
                else if ((h) == 2) { q0 = qf[2][0]; q1 = qf[2][1]; q2 = qf[2][2]; q3 = qf[2][3]; } \
                else { q0 = qf[3][0]; q1 = qf[3][1]; q2 = qf[3][2]; q3 = qf[3][3]; } } while (0)
#define ATT_STORE(h, r0, r1, r2, r3) stmatrix_x4(ostore + (((2 * (h) + (lane >> 4)) ^ (lane & 7)) << 4), r0, r1, r2, r3)
            auto attention = [&](auto masked_tag) {
            constexpr bool MASKED = decltype(masked_tag)::value;
            const float NEG = -INFINITY;
            const uint32_t ONES = 0x3F803F80u;
            float sa[8][2][4], sb2[8][2][4];
            float o[2][4], ls[4];
            float m0, m1;
            uint32_t q0 = qf[0][0], q1 = qf[0][1], q2 = qf[0][2], q3 = qf[0][3];
            auto qk = [&](float (&s)[8][2][4], int ps, int t, uint32_t kbase) {
                if (ps == 0 && t == 0) {
                    const uint4 kd = lds128(kbase + 16 * 512);
                    const uint4 kf = lds128(kbase);
                    float f[2][4];
                    const float ci = (!MASKED || opaque(gb0) >= 0) ? 0.f : NEG;
                    mma16816_c(s[0][0], q0, q1, q2, q3, kd.x, kd.y, 0.f);
                    mma16816_c(s[0][1], q0, q1, q2, q3, kd.z, kd.w, 0.f);
                    mma16816_c(f[0], q0, q1, q2, q3, kf.x, kf.y, ci);
                    mma16816_c(f[1], q0, q1, q2, q3, kf.z, kf.w, ci);
#pragma unroll
                    for (int u = 0; u < 2; u++)
#pragma unroll
                        for (int e = 0; e < 4; e++) {
                            const int row = g + 8 * (e >> 1), col = 8 * u + 2 * c + (e & 1);
                            s[0][u][e] = (col > row) ? f[u][e] : s[0][u][e];
                        }
                } else {
                    const uint4 kf = lds128(kbase + (8 * ps + t) * 512);
                    const float ci = (!MASKED || opaque(gb0) + 8 * ps + t >= 0) ? 0.f : NEG;
                    mma16816_c(s[t][0], q0, q1, q2, q3, kf.x, kf.y, ci);
                    mma16816_c(s[t][1], q0, q1, q2, q3, kf.z, kf.w, ci);
                }
            };
            auto rowmax = [&](float (&s)[8][2][4], float b0, float b1, float& n0, float& n1) {
                int i0 = __float_as_int(b0), i1 = __float_as_int(b1);
#pragma unroll
                for (int t = 0; t < 8; t++)
#pragma unroll
                    for (int u = 0; u < 2; u++) {
                        i0 = __vimax3_s32(i0, __float_as_int(s[t][u][0]), __float_as_int(s[t][u][1]));
                        i1 = __vimax3_s32(i1, __float_as_int(s[t][u][2]), __float_as_int(s[t][u][3]));
                    }
                i0 = max(i0, __shfl_xor_sync(0xffffffffu, i0, 1)); i1 = max(i1, __shfl_xor_sync(0xffffffffu, i1, 1));
                i0 = max(i0, __shfl_xor_sync(0xffffffffu, i0, 2)); i1 = max(i1, __shfl_xor_sync(0xffffffffu, i1, 2));
                n0 = __int_as_float(i0); n1 = __int_as_float(i1);
                if (__any_sync(0xffffffffu, (i0 | i1) < 0)) {
                    asm volatile("" ::: "memory");
                    n0 = b0; n1 = b1;
#pragma unroll
                    for (int t = 0; t < 8; t++)
#pragma unroll
                        for (int u = 0; u < 2; u++) {
                            n0 = fmaxf(n0, fmaxf(s[t][u][0], s[t][u][1]));
                            n1 = fmaxf(n1, fmaxf(s[t][u][2], s[t][u][3]));
                        }
                    n0 = fmaxf(n0, __shfl_xor_sync(0xffffffffu, n0, 1)); n1 = fmaxf(n1, __shfl_xor_sync(0xffffffffu, n1, 1));
                    n0 = fmaxf(n0, __shfl_xor_sync(0xffffffffu, n0, 2)); n1 = fmaxf(n1, __shfl_xor_sync(0xffffffffu, n1, 2));
                }
            };
            auto pv = [&](const float (&p)[2][4], uint32_t vaddr) {
                const uint4 vf = lds128(vaddr);
                const uint32_t a0 = pack_bf16(p[0][0], p[0][1]), a1 = pack_bf16(p[0][2], p[0][3]);
                const uint32_t a2 = pack_bf16(p[1][0], p[1][1]), a3 = pack_bf16(p[1][2], p[1][3]);
                mma16816(o[0], a0, a1, a2, a3, vf.x, vf.y);
                mma16816(o[1], a0, a1, a2, a3, vf.z, vf.w);
                mma16816(ls, a0, a1, a2, a3, ONES, ONES);
            };
            auto expv = [&](float (&s)[8][2][4], int ps, int t, float mc0, float mc1, uint32_t vbase) {
                float p[2][4];
#pragma unroll
                for (int u = 0; u < 2; u++) {
                    p[u][0] = ex2(fmaf(s[t][u][0], SC, -mc0)); p[u][1] = ex2(fmaf(s[t][u][1], SC, -mc0));
                    p[u][2] = ex2(fmaf(s[t][u][2], SC, -mc1)); p[u][3] = ex2(fmaf(s[t][u][3], SC, -mc1));
                }
                if (ps == 0 && t == 0) {
                    float pd[2][4], pf[2][4];
#pragma unroll
                    for (int u = 0; u < 2; u++)
#pragma unroll
                        for (int e = 0; e < 4; e++) {
                            const int row = g + 8 * (e >> 1), col = 8 * u + 2 * c + (e & 1);
                            pf[u][e] = (col > row) ? p[u][e] : 0.f;
                            pd[u][e] = (col > row) ? 0.f : p[u][e];
                        }
                    pv(pd, vbase + 16 * 512);
                    pv(pf, vbase);
                } else {
                    pv(p, vbase + (8 * ps + t) * 512);
                }
            };
            uint32_t kbase, vbase;
            ATT_KWAIT(kbase);
#pragma unroll
            for (int t = 0; t < 8; t++) qk(sa, 0, t, kbase);
            rowmax(sa, NEG, NEG, m0, m1);
#pragma unroll 1
            for (int hh = 0; hh < NHEADS; hh++) {
                ATT_VWAIT(vbase);
#pragma unroll
                for (int e = 0; e < 4; e++) { o[0][e] = 0.f; o[1][e] = 0.f; ls[e] = 0.f; }
                {
                    const float mc0 = m0 * SC, mc1 = m1 * SC;
#pragma unroll
                    for (int t = 0; t < 8; t++) { qk(sb2, 1, t, kbase); expv(sa, 0, t, mc0, mc1, vbase); }
                    ATT_KREL();
                    float n0, n1;
                    rowmax(sb2, m0, m1, n0, n1);
                    const float a0 = ex2((m0 - n0) * SC), a1 = ex2((m1 - n1) * SC);
                    ls[0] *= a0; ls[2] *= a1;
                    o[0][0] *= a0; o[0][1] *= a0; o[1][0] *= a0; o[1][1] *= a0;
                    o[0][2] *= a1; o[0][3] *= a1; o[1][2] *= a1; o[1][3] *= a1;
                    m0 = n0; m1 = n1;
                }
                {
                    const float mc0 = m0 * SC, mc1 = m1 * SC;
                    const bool more = hh + 1 < NHEADS;
                    if (more) {
                        ATT_KWAIT(kbase);
                        ATT_NEXTQ(hh + 1);
#pragma unroll
                        for (int t = 0; t < 8; t++) { qk(sa, 0, t, kbase); expv(sb2, 1, t, mc0, mc1, vbase); }
                        rowmax(sa, NEG, NEG, m0, m1);
                    } else {
#pragma unroll
                        for (int t = 0; t < 8; t++) expv(sb2, 1, t, mc0, mc1, vbase);
                    }
                    ATT_VREL();
                }
                const float f0 = __fdividef(g0, ls[0]), f1 = __fdividef(g1, ls[2]);
                ATT_STORE(hh, pack_bf16(o[0][0] * f0, o[0][1] * f0), pack_bf16(o[0][2] * f1, o[0][3] * f1),
                              pack_bf16(o[1][0] * f0, o[1][1] * f0), pack_bf16(o[1][2] * f1, o[1][3] * f1));
            }
            };
            if (ti >= 2) attention(BoolTag<false>{}); else attention(BoolTag<true>{});
        }
        fence_async_smem();
        asm volatile("bar.sync 4, 256;" ::: "memory");
        TS(6);
        {
            float accA[64], accB[64];
            uint4* pdst = g_part + (size_t)((ti * 8 + warp) * 4 * 8 + tj) * 256 + lane;
            auto epilogue = [&](float (&acc)[64], int q) {
                fence_acc(acc);
                uint4* p = pdst + (size_t)q * 8 * 256;
#pragma unroll
                for (int t2 = 0; t2 < 8; t2++) {
                    uint4 v;
                    v.x = pack_bf16(acc[8 * t2 + 0], acc[8 * t2 + 1]); v.y = pack_bf16(acc[8 * t2 + 2], acc[8 * t2 + 3]);
                    v.z = pack_bf16(acc[8 * t2 + 4], acc[8 * t2 + 5]); v.w = pack_bf16(acc[8 * t2 + 6], acc[8 * t2 + 7]);
                    if (q < 3) p[t2 * 32] = v;
                    else stg_relaxed(p + t2 * 32, make_uint4(nz(v.x), nz(v.y), nz(v.z), nz(v.w)));
                }
                if (q < 3) {
                    __syncwarp();
                    if (lane == 0) mbar_arrive(sb + B_PDONE + 8 * q);
                }
            };
            int rel = r.slot;
            if (wg == 1) asm volatile("bar.sync 3, 256;" ::: "memory");
#pragma unroll
            for (int half = 0; half < 2; half++) {
#pragma unroll
                for (int m = 0; m < 9; m++) {
                    const bool ext = (m < N_EXTRA) && (half == 0);
                    const uint32_t bslot = ext ? sb + X_OFF + (5 + m) * 16384 : sb + RING_OFF + r.slot * SLOT;
                    if (ext) mbar_wait(sb + B_EFULL + 8 * m, 0); else CWAIT();
                    wgmma_fence();
#pragma unroll
                    for (int h = 0; h < 2; h++) {
                        const int u = 2 * m + h, rr = u % 9;
                        const uint32_t bs = bslot + h * 8192;
                        const int vk = rr < 7 ? 32 * rr : 256 + 32 * (rr - 7);
                        const uint32_t as = xa + (vk >> 6) * 16384 + (vk & 63) * 2;
                        if (u < 9) {
                            wgmma_ss_n128(accA, desc_a(as), desc_b(bs), rr);
                            wgmma_ss_n128(accA, desc_a(as + 32), desc_b(bs + 2048), 1);
                        } else {
                            wgmma_ss_n128(accB, desc_a(as), desc_b(bs), rr);
                            wgmma_ss_n128(accB, desc_a(as + 32), desc_b(bs + 2048), 1);
                        }
                    }
                    wgmma_commit();
                    if (m == LEAD2 && half == 0 && wg == 0) asm volatile("bar.arrive 3, 256;" ::: "memory");
                    if (!ext) r.next();
                    wgmma_wait<1>();
                    if (m > N_EXTRA || half > 0) {
                        if (lane == 0) mbar_arrive(sb + B_EMPTY + 8 * rel);
                        if (++rel == RING) rel = 0;
                    }
                    if (m == 5) { TS(25 + 2 * half); epilogue(accA, 2 * half); }
                    if (m == 0 && half == 1) { TS(26); epilogue(accB, 1); }
                }
            }
            wgmma_wait<0>();
            TS(7);
            epilogue(accB, 3);
            mbar_wait(sb + B_EREADY, 0);
            unsigned epoch; asm volatile("ld.shared.u32 %0, [%1];" : "=r"(epoch) : "r"(sb + EPOCH_OFF) : "memory");
            uint4* p3 = part_ptr(ti, tj, 3, warp, lane);
            uint4 v3[8];
#pragma unroll
            for (int s = 0; s < 8; s++) v3[s] = ldg_relaxed(p3 + s * 256);
            if (lane == 0) wait_counter(&g_pcnt[((ti * 8 + tj) * 4 + 2) * 32], 8 * (epoch + 1));
            __syncwarp();
            TS(17);
            reduce_unit(out, ti, tj, 2, warp, lane);
            TS(18);
            for (int it = 0; it < (1 << 16); it++) {
                bool ok = true;
#pragma unroll
                for (int s = 0; s < 8; s++) {
                    if (!(v3[s].x && v3[s].y && v3[s].z && v3[s].w)) { v3[s] = ldg_relaxed(p3 + s * 256); ok = false; }
                }
                if (__all_sync(0xffffffffu, ok)) break;
            }
            TS(19);
            reduce_store(v3, out, ti, tj, 3, warp, lane);
#pragma unroll
            for (int s = 0; s < 8; s++) p3[s * 256] = make_uint4(0u, 0u, 0u, 0u);
            if (tid == 0) TSG(30);
        }
        TS(8);
    }
}

typedef CUresult (*PFN_encodeTiled)(CUtensorMap*, CUtensorMapDataType, cuuint32_t, void*, const cuuint64_t*, const cuuint64_t*,
                                    const cuuint32_t*, const cuuint32_t*, CUtensorMapInterleave, CUtensorMapSwizzle,
                                    CUtensorMapL2promotion, CUtensorMapFloatOOBfill);

void make_map(PFN_encodeTiled enc, CUtensorMap* m, const void* base, int rank, const cuuint64_t* dims, const cuuint64_t* strides, const cuuint32_t* box) {
    cuuint32_t es[5] = {1, 1, 1, 1, 1};
    enc(m, CU_TENSOR_MAP_DATA_TYPE_BFLOAT16, (cuuint32_t)rank, const_cast<void*>(base), dims, strides, box, es,
        CU_TENSOR_MAP_INTERLEAVE_NONE, CU_TENSOR_MAP_SWIZZLE_128B, CU_TENSOR_MAP_L2_PROMOTION_L2_256B, CU_TENSOR_MAP_FLOAT_OOB_FILL_NONE);
}

}

extern "C" void kernel_launch(void* const* d_in, const int* in_sizes, int n_in, void* d_out, int out_size) {
    (void)in_sizes; (void)n_in; (void)out_size;
    const void* x = d_in[0]; const void* wqkv = d_in[1]; const void* wo = d_in[2];
    const void* w1 = d_in[4]; const void* w2 = d_in[5]; const void* gate_w = d_in[6];
    static PFN_encodeTiled enc = nullptr;
    if (!enc) {
        void* fn = nullptr; cudaDriverEntryPointQueryResult st;
        cudaGetDriverEntryPoint("cuTensorMapEncodeTiled", &fn, cudaEnableDefault, &st);
        enc = (PFN_encodeTiled)fn;
        cudaFuncSetAttribute(fused_kernel, cudaFuncAttributeMaxDynamicSharedMemorySize, SMEM_BYTES);
    }
    CUtensorMap mx, mqkv, mw1, mw2, mwo, mw1a;
    { cuuint64_t d[4] = {64, 512, 3, 8}, s[3] = {3584, 128, 448}; cuuint32_t b[4] = {64, 32, 3, 1}; make_map(enc, &mw1a, w1, 4, d, s, b); }
    { cuuint64_t d[2] = {512, 2048}, s[1] = {1024}; cuuint32_t b[2] = {64, 128}; make_map(enc, &mx, x, 2, d, s, b); }
    { cuuint64_t d[4] = {64, 512, 8, 3}, s[3] = {3072, 128, 1024}; cuuint32_t b[4] = {64, 32, 1, 3}; make_map(enc, &mqkv, wqkv, 4, d, s, b); }
    { cuuint64_t d[2] = {1792, 512}, s[1] = {3584}; cuuint32_t b[2] = {64, 32}; make_map(enc, &mw1, w1, 2, d, s, b); }
    { cuuint64_t d[3] = {64, 1792, 8}, s[2] = {1024, 128}; cuuint32_t b[3] = {64, 32, 2}; make_map(enc, &mw2, w2, 3, d, s, b); }
    { cuuint64_t d[3] = {64, 512, 8}, s[2] = {1024, 128}; cuuint32_t b[3] = {64, 32, 2}; make_map(enc, &mwo, wo, 3, d, s, b); }
    fused_kernel<<<128, 384, SMEM_BYTES, cudaStreamPerThread>>>(mx, mqkv, mw1, mw2, mwo, mw1a, (const __nv_bfloat16*)gate_w, (__nv_bfloat16*)d_out,
                                           (const uint8_t*)w1, (const uint8_t*)w2, (const uint8_t*)wo,
                                           (const uint8_t*)x, (const uint8_t*)wqkv);
}
```

```cpp
#include <cuda_runtime.h>
#include <cuda_bf16.h>
#include <cuda.h>
#include <stdint.h>

namespace {

#define PF1_AT 1
#define PF2_AT 7
#define LEAD1 2
#define LEAD2 2
constexpr int RING = 6;
constexpr int SLOT = 16384;
constexpr uint32_t X_OFF = 0;
constexpr uint32_t RING_OFF = 131072;
constexpr uint32_t BAR_OFF = RING_OFF + RING * SLOT;
constexpr uint32_t B_FULL = BAR_OFF, B_EMPTY = BAR_OFF + 64, B_XFULL = BAR_OFF + 128, B_XDEAD = BAR_OFF + 192,
                   B_EREADY = BAR_OFF + 200, B_KVDONE = BAR_OFF + 208, B_PDONE = BAR_OFF + 216,
                   B_KVREADY = BAR_OFF + 248, B_EFULL = BAR_OFF + 264;
constexpr uint32_t EPOCH_OFF = BAR_OFF + 256, ITEM_OFF = BAR_OFF + 260;
constexpr uint32_t SMEM_BYTES = BAR_OFF + 1024;

constexpr int N_QKV = 16, N_FFN1 = 16, N_KV = 8, N_EXTRA = 3, N_FFN2 = 18 - N_EXTRA;
constexpr int S_FFN1 = N_QKV, S_KV = S_FFN1 + N_FFN1, S_FFN2 = S_KV + N_KV;

__device__ uint4 g_kf[32 * 128 * 32];
__device__ uint4 g_vf[32 * 128 * 32];
__device__ uint4 g_part[16 * 8 * 4 * 8 * 8 * 32];
__device__ unsigned g_ticket;
__device__ unsigned g_kvcnt[128 * 32];
#define TS(k) do {} while (0)
#define TS2(k) do {} while (0)
#define TS2X(k) do {} while (0)
#define TSX(k) do {} while (0)
#define TSG(k) do {} while (0)

__device__ __forceinline__ uint32_t smem_u32(const void* p) { return (uint32_t)__cvta_generic_to_shared(p); }
__device__ __forceinline__ void mbar_init(uint32_t bar, uint32_t cnt) { asm volatile("mbarrier.init.shared::cta.b64 [%0], %1;" :: "r"(bar), "r"(cnt) : "memory"); }
__device__ __forceinline__ void mbar_expect_tx(uint32_t bar, uint32_t bytes) { asm volatile("mbarrier.arrive.expect_tx.shared::cta.b64 _, [%0], %1;" :: "r"(bar), "r"(bytes) : "memory"); }
__device__ __forceinline__ void mbar_expect_only(uint32_t bar, uint32_t bytes) { asm volatile("mbarrier.expect_tx.relaxed.cta.shared::cta.b64 [%0], %1;" :: "r"(bar), "r"(bytes) : "memory"); }
__device__ __forceinline__ void mbar_arrive(uint32_t bar) { asm volatile("mbarrier.arrive.shared::cta.b64 _, [%0];" :: "r"(bar) : "memory"); }
__device__ __forceinline__ bool mbar_try(uint32_t bar, uint32_t parity) {
    uint32_t ok;
    asm volatile("{\n.reg .pred P1;\nmbarrier.try_wait.parity.shared::cta.b64 P1, [%1], %2;\nselp.u32 %0, 1, 0, P1;\n}" : "=r"(ok) : "r"(bar), "r"(parity) : "memory");
    return ok != 0;
}
__device__ __forceinline__ void mbar_wait(uint32_t bar, uint32_t parity) {
    asm volatile("{\n.reg .pred P1, P2;\n.reg .u32 n;\nmov.u32 n, 0;\n"
                 "WAIT_LOOP:\n"
                 "mbarrier.try_wait.parity.shared::cta.b64 P1, [%0], %1;\n"
                 "@P1 bra WAIT_DONE;\n"
                 "add.u32 n, n, 1;\n"
                 "setp.lt.u32 P2, n, 0x400000;\n"
                 "@P2 bra WAIT_LOOP;\n"
                 "WAIT_DONE:\n}" :: "r"(bar), "r"(parity) : "memory");
}
__device__ __forceinline__ void tma_2d(uint32_t dst, const void* map, uint32_t bar, int c0, int c1) {
    asm volatile("cp.async.bulk.tensor.2d.shared::cluster.global.mbarrier::complete_tx::bytes [%0], [%1, {%3, %4}], [%2];"
        :: "r"(dst), "l"(map), "r"(bar), "r"(c0), "r"(c1) : "memory");
}
__device__ __forceinline__ void tma_3d(uint32_t dst, const void* map, uint32_t bar, int c0, int c1, int c2) {
    asm volatile("cp.async.bulk.tensor.3d.shared::cluster.global.mbarrier::complete_tx::bytes [%0], [%1, {%3, %4, %5}], [%2];"
        :: "r"(dst), "l"(map), "r"(bar), "r"(c0), "r"(c1), "r"(c2) : "memory");
}
__device__ __forceinline__ void tma_4d(uint32_t dst, const void* map, uint32_t bar, int c0, int c1, int c2, int c3) {
    asm volatile("cp.async.bulk.tensor.4d.shared::cluster.global.mbarrier::complete_tx::bytes [%0], [%1, {%3, %4, %5, %6}], [%2];"
        :: "r"(dst), "l"(map), "r"(bar), "r"(c0), "r"(c1), "r"(c2), "r"(c3) : "memory");
}
__device__ __forceinline__ void bulk_g2s(uint32_t dst, const void* src, uint32_t bytes, uint32_t bar) {
    asm volatile("cp.async.bulk.shared::cluster.global.mbarrier::complete_tx::bytes [%0], [%1], %2, [%3];"
        :: "r"(dst), "l"(src), "r"(bytes), "r"(bar) : "memory");
}
__device__ __forceinline__ void prefetch_l2(const void* src, uint32_t bytes) {
    asm volatile("cp.async.bulk.prefetch.L2.global [%0], %1;" :: "l"(src), "r"(bytes) : "memory");
}
__device__ __forceinline__ bool elect_one() {
    uint32_t p;
    asm volatile("{\n.reg .pred P;\nelect.sync _|P, 0xffffffff;\nselp.u32 %0, 1, 0, P;\n}" : "=r"(p));
    return p != 0;
}
__device__ __forceinline__ void wgmma_fence() { asm volatile("wgmma.fence.sync.aligned;" ::: "memory"); }
__device__ __forceinline__ void wgmma_commit() { asm volatile("wgmma.commit_group.sync.aligned;" ::: "memory"); }
template <int N> __device__ __forceinline__ void wgmma_wait() { asm volatile("wgmma.wait_group.sync.aligned %0;" :: "n"(N) : "memory"); }
__device__ __forceinline__ void fence_async_smem() { asm volatile("fence.proxy.async.shared::cta;" ::: "memory"); }
__device__ __forceinline__ uint64_t desc_a(uint32_t addr) {
    return (uint64_t)((addr & 0x3FFFF) >> 4) | ((uint64_t)1 << 16) | ((uint64_t)(1024 >> 4) << 32) | ((uint64_t)1 << 62);
}
__device__ __forceinline__ uint64_t desc_b(uint32_t addr) {
    return (uint64_t)((addr & 0x3FFFF) >> 4) | ((uint64_t)(4096 >> 4) << 16) | ((uint64_t)(1024 >> 4) << 32) | ((uint64_t)1 << 62);
}
__device__ __forceinline__ uint32_t pack_bf16(float lo, float hi) {
    uint32_t r; asm("cvt.rn.bf16x2.f32 %0, %1, %2;" : "=r"(r) : "f"(hi), "f"(lo)); return r;
}
__device__ __forceinline__ uint32_t pack_bf16_relu(float lo, float hi) {
    uint32_t r; asm("cvt.rn.relu.bf16x2.f32 %0, %1, %2;" : "=r"(r) : "f"(hi), "f"(lo)); return r;
}
__device__ __forceinline__ uint32_t movmatrix(uint32_t a) {
    uint32_t d; asm volatile("movmatrix.sync.aligned.m8n8.trans.b16 %0, %1;" : "=r"(d) : "r"(a)); return d;
}
__device__ __forceinline__ void stmatrix_x4(uint32_t addr, uint32_t r0, uint32_t r1, uint32_t r2, uint32_t r3) {
    asm volatile("stmatrix.sync.aligned.m8n8.x4.shared.b16 [%0], {%1, %2, %3, %4};" :: "r"(addr), "r"(r0), "r"(r1), "r"(r2), "r"(r3) : "memory");
}
__device__ __forceinline__ uint4 lds128(uint32_t addr) {
    uint4 v; asm volatile("ld.shared.v4.b32 {%0, %1, %2, %3}, [%4];" : "=r"(v.x), "=r"(v.y), "=r"(v.z), "=r"(v.w) : "r"(addr) : "memory"); return v;
}
__device__ __forceinline__ void mma16816(float (&c)[4], uint32_t a0, uint32_t a1, uint32_t a2, uint32_t a3, uint32_t b0, uint32_t b1) {
    asm volatile("mma.sync.aligned.m16n8k16.row.col.f32.bf16.bf16.f32 {%0,%1,%2,%3}, {%4,%5,%6,%7}, {%8,%9}, {%0,%1,%2,%3};"
        : "+f"(c[0]), "+f"(c[1]), "+f"(c[2]), "+f"(c[3]) : "r"(a0), "r"(a1), "r"(a2), "r"(a3), "r"(b0), "r"(b1));
}
__device__ __forceinline__ void mma16816_c(float (&c)[4], uint32_t a0, uint32_t a1, uint32_t a2, uint32_t a3, uint32_t b0, uint32_t b1, float ci) {
    asm volatile("mma.sync.aligned.m16n8k16.row.col.f32.bf16.bf16.f32 {%0,%1,%2,%3}, {%4,%5,%6,%7}, {%8,%9}, {%10,%10,%10,%10};"
        : "=f"(c[0]), "=f"(c[1]), "=f"(c[2]), "=f"(c[3]) : "r"(a0), "r"(a1), "r"(a2), "r"(a3), "r"(b0), "r"(b1), "f"(ci));
}
__device__ __forceinline__ int opaque(int v) { asm volatile("" : "+r"(v)); return v; }
__device__ __forceinline__ float ex2(float x) { float y; asm("ex2.approx.ftz.f32 %0, %1;" : "=f"(y) : "f"(x)); return y; }
__device__ __forceinline__ unsigned ld_acquire(const unsigned* p) {
    unsigned v; asm volatile("ld.acquire.gpu.global.u32 %0, [%1];" : "=r"(v) : "l"(p) : "memory"); return v;
}
__device__ __forceinline__ void red_release(unsigned* p, unsigned v) {
    asm volatile("red.release.gpu.global.add.u32 [%0], %1;" :: "l"(p), "r"(v) : "memory");
}
__device__ __forceinline__ void wait_counter(const unsigned* p, unsigned target) {
    uint32_t n = 0;
    while ((int)(ld_acquire(p) - target) < 0) { if (++n > (1u << 20)) break; }
}
__device__ __forceinline__ uint4 ldg_weak(const uint4* p) {
    uint4 v; asm volatile("ld.global.L1::no_allocate.v4.b32 {%0, %1, %2, %3}, [%4];" : "=r"(v.x), "=r"(v.y), "=r"(v.z), "=r"(v.w) : "l"(p) : "memory"); return v;
}
__device__ __forceinline__ float bf_lo(uint32_t v) { return __uint_as_float(v << 16); }
__device__ __forceinline__ float bf_hi(uint32_t v) { return __uint_as_float(v & 0xFFFF0000u); }

__device__ __forceinline__ void wgmma_ss_n128(float (&d)[64], uint64_t da, uint64_t db, int scale_d) {
    asm volatile("{\n.reg .pred p;\nsetp.ne.b32 p, %66, 0;\n"
        "wgmma.mma_async.sync.aligned.m64n128k16.f32.bf16.bf16 {%0, %1, %2, %3, %4, %5, %6, %7, %8, %9, %10, %11, %12, %13, %14, %15, %16, %17, %18, %19, %20, %21, %22, %23, %24, %25, %26, %27, %28, %29, %30, %31, %32, %33, %34, %35, %36, %37, %38, %39, %40, %41, %42, %43, %44, %45, %46, %47, %48, %49, %50, %51, %52, %53, %54, %55, %56, %57, %58, %59, %60, %61, %62, %63}, %64, %65, p, 1, 1, 0, 1;\n}\n"
        : "+f"(d[0]), "+f"(d[1]), "+f"(d[2]), "+f"(d[3]), "+f"(d[4]), "+f"(d[5]), "+f"(d[6]), "+f"(d[7]), "+f"(d[8]), "+f"(d[9]), "+f"(d[10]), "+f"(d[11]), "+f"(d[12]), "+f"(d[13]), "+f"(d[14]), "+f"(d[15]), "+f"(d[16]), "+f"(d[17]), "+f"(d[18]), "+f"(d[19]), "+f"(d[20]), "+f"(d[21]), "+f"(d[22]), "+f"(d[23]), "+f"(d[24]), "+f"(d[25]), "+f"(d[26]), "+f"(d[27]), "+f"(d[28]), "+f"(d[29]), "+f"(d[30]), "+f"(d[31]), "+f"(d[32]), "+f"(d[33]), "+f"(d[34]), "+f"(d[35]), "+f"(d[36]), "+f"(d[37]), "+f"(d[38]), "+f"(d[39]), "+f"(d[40]), "+f"(d[41]), "+f"(d[42]), "+f"(d[43]), "+f"(d[44]), "+f"(d[45]), "+f"(d[46]), "+f"(d[47]), "+f"(d[48]), "+f"(d[49]), "+f"(d[50]), "+f"(d[51]), "+f"(d[52]), "+f"(d[53]), "+f"(d[54]), "+f"(d[55]), "+f"(d[56]), "+f"(d[57]), "+f"(d[58]), "+f"(d[59]), "+f"(d[60]), "+f"(d[61]), "+f"(d[62]), "+f"(d[63])
        : "l"(da), "l"(db), "r"(scale_d));
}
__device__ __forceinline__ void wgmma_ss_n200(float (&d)[100], uint64_t da, uint64_t db, int scale_d) {
    asm volatile("{\n.reg .pred p;\nsetp.ne.b32 p, %102, 0;\n"
        "wgmma.mma_async.sync.aligned.m64n200k16.f32.bf16.bf16 {%0, %1, %2, %3, %4, %5, %6, %7, %8, %9, %10, %11, %12, %13, %14, %15, %16, %17, %18, %19, %20, %21, %22, %23, %24, %25, %26, %27, %28, %29, %30, %31, %32, %33, %34, %35, %36, %37, %38, %39, %40, %41, %42, %43, %44, %45, %46, %47, %48, %49, %50, %51, %52, %53, %54, %55, %56, %57, %58, %59, %60, %61, %62, %63, %64, %65, %66, %67, %68, %69, %70, %71, %72, %73, %74, %75, %76, %77, %78, %79, %80, %81, %82, %83, %84, %85, %86, %87, %88, %89, %90, %91, %92, %93, %94, %95, %96, %97, %98, %99}, %100, %101, p, 1, 1, 0, 1;\n}\n"
        : "+f"(d[0]), "+f"(d[1]), "+f"(d[2]), "+f"(d[3]), "+f"(d[4]), "+f"(d[5]), "+f"(d[6]), "+f"(d[7]), "+f"(d[8]), "+f"(d[9]), "+f"(d[10]), "+f"(d[11]), "+f"(d[12]), "+f"(d[13]), "+f"(d[14]), "+f"(d[15]), "+f"(d[16]), "+f"(d[17]), "+f"(d[18]), "+f"(d[19]), "+f"(d[20]), "+f"(d[21]), "+f"(d[22]), "+f"(d[23]), "+f"(d[24]), "+f"(d[25]), "+f"(d[26]), "+f"(d[27]), "+f"(d[28]), "+f"(d[29]), "+f"(d[30]), "+f"(d[31]), "+f"(d[32]), "+f"(d[33]), "+f"(d[34]), "+f"(d[35]), "+f"(d[36]), "+f"(d[37]), "+f"(d[38]), "+f"(d[39]), "+f"(d[40]), "+f"(d[41]), "+f"(d[42]), "+f"(d[43]), "+f"(d[44]), "+f"(d[45]), "+f"(d[46]), "+f"(d[47]), "+f"(d[48]), "+f"(d[49]), "+f"(d[50]), "+f"(d[51]), "+f"(d[52]), "+f"(d[53]), "+f"(d[54]), "+f"(d[55]), "+f"(d[56]), "+f"(d[57]), "+f"(d[58]), "+f"(d[59]), "+f"(d[60]), "+f"(d[61]), "+f"(d[62]), "+f"(d[63]), "+f"(d[64]), "+f"(d[65]), "+f"(d[66]), "+f"(d[67]), "+f"(d[68]), "+f"(d[69]), "+f"(d[70]), "+f"(d[71]), "+f"(d[72]), "+f"(d[73]), "+f"(d[74]), "+f"(d[75]), "+f"(d[76]), "+f"(d[77]), "+f"(d[78]), "+f"(d[79]), "+f"(d[80]), "+f"(d[81]), "+f"(d[82]), "+f"(d[83]), "+f"(d[84]), "+f"(d[85]), "+f"(d[86]), "+f"(d[87]), "+f"(d[88]), "+f"(d[89]), "+f"(d[90]), "+f"(d[91]), "+f"(d[92]), "+f"(d[93]), "+f"(d[94]), "+f"(d[95]), "+f"(d[96]), "+f"(d[97]), "+f"(d[98]), "+f"(d[99])
        : "l"(da), "l"(db), "r"(scale_d));
}
__device__ __forceinline__ void wgmma_ss_n224(float (&d)[112], uint64_t da, uint64_t db, int scale_d) {
    asm volatile("{\n.reg .pred p;\nsetp.ne.b32 p, %114, 0;\n"
        "wgmma.mma_async.sync.aligned.m64n224k16.f32.bf16.bf16 {%0, %1, %2, %3, %4, %5, %6, %7, %8, %9, %10, %11, %12, %13, %14, %15, %16, %17, %18, %19, %20, %21, %22, %23, %24, %25, %26, %27, %28, %29, %30, %31, %32, %33, %34, %35, %36, %37, %38, %39, %40, %41, %42, %43, %44, %45, %46, %47, %48, %49, %50, %51, %52, %53, %54, %55, %56, %57, %58, %59, %60, %61, %62, %63, %64, %65, %66, %67, %68, %69, %70, %71, %72, %73, %74, %75, %76, %77, %78, %79, %80, %81, %82, %83, %84, %85, %86, %87, %88, %89, %90, %91, %92, %93, %94, %95, %96, %97, %98, %99, %100, %101, %102, %103, %104, %105, %106, %107, %108, %109, %110, %111}, %112, %113, p, 1, 1, 0, 1;\n}\n"
        : "+f"(d[0]), "+f"(d[1]), "+f"(d[2]), "+f"(d[3]), "+f"(d[4]), "+f"(d[5]), "+f"(d[6]), "+f"(d[7]), "+f"(d[8]), "+f"(d[9]), "+f"(d[10]), "+f"(d[11]), "+f"(d[12]), "+f"(d[13]), "+f"(d[14]), "+f"(d[15]), "+f"(d[16]), "+f"(d[17]), "+f"(d[18]), "+f"(d[19]), "+f"(d[20]), "+f"(d[21]), "+f"(d[22]), "+f"(d[23]), "+f"(d[24]), "+f"(d[25]), "+f"(d[26]), "+f"(d[27]), "+f"(d[28]), "+f"(d[29]), "+f"(d[30]), "+f"(d[31]), "+f"(d[32]), "+f"(d[33]), "+f"(d[34]), "+f"(d[35]), "+f"(d[36]), "+f"(d[37]), "+f"(d[38]), "+f"(d[39]), "+f"(d[40]), "+f"(d[41]), "+f"(d[42]), "+f"(d[43]), "+f"(d[44]), "+f"(d[45]), "+f"(d[46]), "+f"(d[47]), "+f"(d[48]), "+f"(d[49]), "+f"(d[50]), "+f"(d[51]), "+f"(d[52]), "+f"(d[53]), "+f"(d[54]), "+f"(d[55]), "+f"(d[56]), "+f"(d[57]), "+f"(d[58]), "+f"(d[59]), "+f"(d[60]), "+f"(d[61]), "+f"(d[62]), "+f"(d[63]), "+f"(d[64]), "+f"(d[65]), "+f"(d[66]), "+f"(d[67]), "+f"(d[68]), "+f"(d[69]), "+f"(d[70]), "+f"(d[71]), "+f"(d[72]), "+f"(d[73]), "+f"(d[74]), "+f"(d[75]), "+f"(d[76]), "+f"(d[77]), "+f"(d[78]), "+f"(d[79]), "+f"(d[80]), "+f"(d[81]), "+f"(d[82]), "+f"(d[83]), "+f"(d[84]), "+f"(d[85]), "+f"(d[86]), "+f"(d[87]), "+f"(d[88]), "+f"(d[89]), "+f"(d[90]), "+f"(d[91]), "+f"(d[92]), "+f"(d[93]), "+f"(d[94]), "+f"(d[95]), "+f"(d[96]), "+f"(d[97]), "+f"(d[98]), "+f"(d[99]), "+f"(d[100]), "+f"(d[101]), "+f"(d[102]), "+f"(d[103]), "+f"(d[104]), "+f"(d[105]), "+f"(d[106]), "+f"(d[107]), "+f"(d[108]), "+f"(d[109]), "+f"(d[110]), "+f"(d[111])
        : "l"(da), "l"(db), "r"(scale_d));
}
template <int N> __device__ __forceinline__ void fence_acc(float (&d)[N]) {
#pragma unroll
    for (int i = 0; i < N; i++) asm volatile("" : "+f"(d[i]) :: "memory");
}

__device__ __forceinline__ void reduce_store(const uint4 (&v)[8], __nv_bfloat16* __restrict__ out, int ti, int tj, int q, int t2, int lane) {
    float a[8];
#pragma unroll
    for (int e = 0; e < 8; e++) a[e] = 0.f;
#pragma unroll
    for (int s = 0; s < 8; s++) {
        a[0] += bf_lo(v[s].x); a[1] += bf_hi(v[s].x); a[2] += bf_lo(v[s].y); a[3] += bf_hi(v[s].y);
        a[4] += bf_lo(v[s].z); a[5] += bf_hi(v[s].z); a[6] += bf_lo(v[s].w); a[7] += bf_hi(v[s].w);
    }
    const uint32_t lo0 = pack_bf16(a[0], a[1]), lo1 = pack_bf16(a[4], a[5]);
    const uint32_t hi0 = pack_bf16(a[2], a[3]), hi1 = pack_bf16(a[6], a[7]);
    const bool odd = lane & 1;
    const uint32_t sl = __shfl_xor_sync(0xffffffffu, odd ? lo0 : lo1, 1);
    const uint32_t sh = __shfl_xor_sync(0xffffffffu, odd ? hi0 : hi1, 1);
    const uint2 wl = odd ? make_uint2(sl, lo1) : make_uint2(lo0, sl);
    const uint2 wh = odd ? make_uint2(sh, hi1) : make_uint2(hi0, sh);
    __nv_bfloat16* o = out + (size_t)(ti * 128 + tj * 16 + (lane >> 2)) * 512 + q * 128 + t2 * 16 + (odd ? 8 : 0) + (lane & 2) * 2;
    *reinterpret_cast<uint2*>(o) = wl;
    *reinterpret_cast<uint2*>(o + 8 * 512) = wh;
}
__device__ __forceinline__ uint4* part_ptr(int ti, int owner, int q, int t2, int lane) {
    return g_part + (size_t)(((ti * 8 + owner) * 4 + q) * 8) * 256 + t2 * 32 + lane;
}
__device__ __forceinline__ uint4 ldg_relaxed(const uint4* p) {
    uint4 v; asm volatile("ld.relaxed.gpu.global.v4.b32 {%0, %1, %2, %3}, [%4];" : "=r"(v.x), "=r"(v.y), "=r"(v.z), "=r"(v.w) : "l"(p) : "memory"); return v;
}
__device__ __forceinline__ void stg_relaxed(uint4* p, uint4 v) {
    asm volatile("st.relaxed.gpu.global.v4.b32 [%0], {%1, %2, %3, %4};" :: "l"(p), "r"(v.x), "r"(v.y), "r"(v.z), "r"(v.w) : "memory");
}
__device__ __forceinline__ void reduce_items(uint32_t sb, __nv_bfloat16* __restrict__ out, int ti, int tj, uint32_t tag, int lane) {
    for (;;) {
        uint32_t item = 0;
        if (lane == 0) asm volatile("atom.shared.add.u32 %0, [%1], 1;" : "=r"(item) : "r"(sb + ITEM_OFF) : "memory");
        item = __shfl_sync(0xffffffffu, item, 0);
        if (item >= 32) break;
        const int q = item >> 3, t2 = item & 7;
        mbar_wait(sb + B_PDONE + 8 * q, 0);
        const uint4* p = part_ptr(ti, tj, q, t2, lane);
        uint4 v[8];
#pragma unroll
        for (int s = 0; s < 8; s++) v[s] = ldg_relaxed(p + s * 256);
        for (int it = 0; it < (1 << 16); it++) {
            bool ok = true;
#pragma unroll
            for (int s = 0; s < 8; s++) {
                const uint32_t bad = ((v[s].x ^ tag) | (v[s].y ^ tag) | (v[s].z ^ tag) | (v[s].w ^ tag)) & 1u;
                if (bad) { v[s] = ldg_relaxed(p + s * 256); ok = false; }
            }
            if (__all_sync(0xffffffffu, ok)) break;
        }
        reduce_store(v, out, ti, tj, q, t2, lane);
    }
}

#define PWAIT() mbar_wait(sb + B_EMPTY + 8 * r.slot, r.phase)
#define CWAIT() mbar_wait(sb + B_FULL + 8 * r.slot, r.phase)
template <bool B> struct BoolTag { static constexpr bool value = B; };
struct Ring {
    int slot; uint32_t phase;
    __device__ __forceinline__ void next() { if (++slot == RING) { slot = 0; phase ^= 1; } }
};

__global__ void __launch_bounds__(384, 1)
fused_kernel(const __grid_constant__ CUtensorMap map_x, const __grid_constant__ CUtensorMap map_qkv,
             const __grid_constant__ CUtensorMap map_w1, const __grid_constant__ CUtensorMap map_w2,
             const __grid_constant__ CUtensorMap map_wo, const __grid_constant__ CUtensorMap map_w1a,
             const __nv_bfloat16* __restrict__ gate_w, __nv_bfloat16* __restrict__ out,
             const uint8_t* __restrict__ w1p, const uint8_t* __restrict__ w2p, const uint8_t* __restrict__ wop,
             const uint8_t* __restrict__ xp, const uint8_t* __restrict__ wqkvp)
{
    extern __shared__ __align__(1024) uint8_t smem_raw[];
    const uint32_t sb = smem_u32(smem_raw);
    const int tid = threadIdx.x, warp = tid >> 5, lane = tid & 31;
    const int ti = blockIdx.x >> 3, tj = blockIdx.x & 7;

    if (tid == 0) { TSG(31); TSX(0); }
    if (tid == 320) {
        asm volatile("prefetch.tensormap [%0];" :: "l"(&map_x) : "memory");
        asm volatile("prefetch.tensormap [%0];" :: "l"(&map_qkv) : "memory");
        asm volatile("prefetch.tensormap [%0];" :: "l"(&map_w1) : "memory");
        asm volatile("prefetch.tensormap [%0];" :: "l"(&map_w2) : "memory");
        asm volatile("prefetch.tensormap [%0];" :: "l"(&map_wo) : "memory");
        asm volatile("prefetch.tensormap [%0];" :: "l"(&map_w1a) : "memory");
    }
    uint32_t gwv[N_QKV / 2];
    if (warp == 8) {
        const unsigned short* gws = reinterpret_cast<const unsigned short*>(gate_w);
#pragma unroll
        for (int n = 0; n < N_QKV / 2; n++) gwv[n] = (uint32_t)__ldg(gws + 64 * n + lane) | ((uint32_t)__ldg(gws + 64 * n + 32 + lane) << 16);
    }
    if (tid == 256) {
        for (int s = 0; s < RING; s++) { mbar_init(sb + B_FULL + 8 * s, 1); mbar_init(sb + B_EMPTY + 8 * s, 8); }
        for (int s = 0; s < 8; s++) mbar_init(sb + B_XFULL + 8 * s, 1);
        mbar_init(sb + B_XDEAD, 8); mbar_init(sb + B_EREADY, 1); mbar_init(sb + B_KVDONE, 8); mbar_init(sb + B_KVREADY, 1);
        for (int s = 0; s < 4; s++) mbar_init(sb + B_PDONE + 8 * s, 8);
        for (int s = 0; s < 3; s++) mbar_init(sb + B_EFULL + 8 * s, 1);
        asm volatile("st.shared.u32 [%0], %1;" :: "r"(sb + ITEM_OFF), "r"(0) : "memory");
        asm volatile("fence.mbarrier_init.release.cluster;" ::: "memory");
        fence_async_smem();
        mbar_expect_tx(sb + B_XFULL, 16384);
        tma_2d(sb + X_OFF, &map_x, sb + B_XFULL, 0, ti * 128);
        mbar_expect_only(sb + B_FULL, 12288);
        tma_4d(sb + RING_OFF, &map_qkv, sb + B_FULL, 0, 0, tj, 0);
    }
    __syncthreads();

    if (warp >= 8) {
        asm volatile("setmaxnreg.dec.sync.aligned.u32 56;");
        if (warp == 8) {
            Ring r{0, 1};
            const bool leader = elect_one();
#pragma unroll
            for (int n = 0; n < N_QKV; n++) {
                const uint32_t full = sb + B_FULL + 8 * r.slot, dst = sb + RING_OFF + r.slot * SLOT;
                if (n > 0) {
                    if (!(n & 1) && leader) {
                        mbar_expect_tx(sb + B_XFULL + 8 * (n >> 1), 16384);
                        tma_2d(sb + X_OFF + (n >> 1) * 16384, &map_x, sb + B_XFULL + 8 * (n >> 1), (n >> 1) * 64, ti * 128);
                    }
                    if (n >= RING) PWAIT();
                    if (leader) {
                        mbar_expect_only(full, 12288);
                        tma_4d(dst, &map_qkv, full, 0, 32 * n, tj, 0);
                    }
                }
                const uint32_t gv = (n & 1) ? (gwv[n >> 1] >> 16) : (gwv[n >> 1] & 0xFFFFu);
                asm volatile("st.shared.v4.b32 [%0], {%1, %2, %2, %2};" :: "r"(dst + 12288 + lane * 128 + ((lane & 7) << 4)), "r"(gv), "r"(0) : "memory");
                fence_async_smem();
                __syncwarp();
                if (leader) mbar_arrive(full);
                r.next();
            }
#pragma unroll 1
            for (int n = 0; n < N_FFN1; n++) {
                const uint32_t full = sb + B_FULL + 8 * r.slot, dst = sb + RING_OFF + r.slot * SLOT;
                PWAIT();
                if (leader) {
                    mbar_expect_tx(full, 16384);
                    tma_4d(dst, &map_w1a, full, 0, 32 * n, 0, tj);
                    tma_2d(dst + 3 * 4096, &map_w1, full, 224 * tj + 192, 32 * n);
                }
                r.next();
            }
            if (lane == 0) TSX(10);
            mbar_wait(sb + B_KVREADY, 0);
            asm volatile("fence.proxy.async.global;" ::: "memory");
            if (lane == 0) TSX(11);
            {
                const int bbase = 8 * ti - 16, b0 = bbase < 0 ? 0 : bbase;
                const uint32_t bytes = (uint32_t)(8 * ti + 8 - b0) * 512;
#pragma unroll 1
                for (int m = 0; m < N_KV; m++) {
                    const uint32_t full = sb + B_FULL + 8 * r.slot, dst = sb + RING_OFF + r.slot * SLOT;
                    if (m == RING) {
                        mbar_wait(sb + B_XDEAD, 0);
                        if (leader) {
#pragma unroll
                            for (int e = 0; e < N_EXTRA; e++) {
                                mbar_expect_tx(sb + B_EFULL + 8 * e, 16384);
                                tma_3d(sb + X_OFF + (5 + e) * 16384, &map_w2, sb + B_EFULL + 8 * e, 0, 224 * tj + 64 * e, 0);
                                tma_3d(sb + X_OFF + (5 + e) * 16384 + 8192, &map_w2, sb + B_EFULL + 8 * e, 0, 224 * tj + 64 * e + 32, 0);
                            }
                        }
                    }
                    PWAIT();
                    if (leader) {
                        const uint4* src = ((m & 1) ? g_vf : g_kf) + ((tj * 4 + (m >> 1)) * 128 + b0) * 32;
                        mbar_expect_tx(full, bytes);
                        bulk_g2s(dst + (b0 - bbase) * 512, src, bytes, full);
                    }
                    r.next();
                }
            }
            {
                int q = 0, rr = 2 * N_EXTRA;
#pragma unroll 1
                for (int n = 0; n < N_FFN2; n++) {
                    const uint32_t full = sb + B_FULL + 8 * r.slot, dst = sb + RING_OFF + r.slot * SLOT;
                    PWAIT();
                    if (leader) mbar_expect_tx(full, 16384);
#pragma unroll
                    for (int h = 0; h < 2; h++) {
                        const bool isw2 = rr < 7;
                        const int row = isw2 ? 224 * tj + 32 * rr : 64 * tj + 32 * (rr - 7);
                        if (leader) tma_3d(dst + h * 8192, isw2 ? &map_w2 : &map_wo, full, 0, row, 2 * q);
                        if (++rr == 9) { rr = 0; q++; }
                    }
                    r.next();
                }
            }
        } else if (warp == 9) {
            unsigned epoch = 0;
            if (lane == 0) {
                epoch = atomicAdd(&g_ticket, 1u) >> 7;
                asm volatile("st.shared.u32 [%0], %1;" :: "r"(sb + EPOCH_OFF), "r"(epoch) : "memory");
                mbar_arrive(sb + B_EREADY);
                mbar_wait(sb + B_XFULL + 8 * PF1_AT, 0);
                prefetch_l2(w1p + (size_t)blockIdx.x * 14336, 14336);
                mbar_wait(sb + B_XFULL + 8 * PF2_AT, 0);
                prefetch_l2(w2p + (size_t)blockIdx.x * 14336, 14336);
                prefetch_l2(wop + (size_t)blockIdx.x * 4096, 4096);
                mbar_wait(sb + B_KVDONE, 0);
                red_release(&g_kvcnt[blockIdx.x * 32], 1u);
            }
            epoch = __shfl_sync(0xffffffffu, epoch, 0);
            if (lane < 3 && ti - lane >= 0) wait_counter(&g_kvcnt[((ti - lane) * 8 + tj) * 32], epoch + 1);
            __syncwarp();
            if (lane == 0) mbar_arrive(sb + B_KVREADY);
            reduce_items(sb, out, ti, tj, (epoch + 1) & 1u, lane);
        } else {
            mbar_wait(sb + B_EREADY, 0);
            unsigned epoch; asm volatile("ld.shared.u32 %0, [%1];" : "=r"(epoch) : "r"(sb + EPOCH_OFF) : "memory");
            reduce_items(sb, out, ti, tj, (epoch + 1) & 1u, lane);
            if (tid == 320) TSX(13);
        }
    } else {
        asm volatile("setmaxnreg.inc.sync.aligned.u32 224;");
        const int wg = warp >> 2, g = lane >> 2, c = lane & 3;
        const uint32_t xa = sb + X_OFF + wg * 8192;
        Ring r{0, 0};
        uint32_t qf[4][4];
        float g0, g1;
        TS(9);
        {
            float acc[100];
            int prev = 0;
            if (wg == 1) asm volatile("bar.sync 3, 256;" ::: "memory");
            for (int s = 0; s < N_QKV; s++) {
                if (!(s & 1)) mbar_wait(sb + B_XFULL + 8 * (s >> 1), 0);
                CWAIT();
                if (s == 0) TS(1);
                if (s == 2) TS(28);
                if (s == 6) TS(29);
                if (s == 10) TS(20);
                const uint32_t bs = sb + RING_OFF + r.slot * SLOT, as = xa + (s >> 1) * 16384 + (s & 1) * 64;
                wgmma_fence();
                wgmma_ss_n200(acc, desc_a(as), desc_b(bs), s);
                wgmma_ss_n200(acc, desc_a(as + 32), desc_b(bs + 2048), 1);
                wgmma_commit();
                if (wg == 0 && s == LEAD1) asm volatile("bar.arrive 3, 256;" ::: "memory");
                if (s > 0) { wgmma_wait<1>(); if (lane == 0) mbar_arrive(sb + B_EMPTY + 8 * prev); }
                prev = r.slot; r.next();
            }
            wgmma_wait<0>();
            fence_acc(acc);
            if (lane == 0) mbar_arrive(sb + B_EMPTY + 8 * prev);
            TS(2);
            const int blk = ti * 8 + warp;
#pragma unroll
            for (int hh = 0; hh < 4; hh++) {
                const float* t0 = &acc[8 * hh]; const float* t1 = &acc[8 * hh + 4];
                qf[hh][0] = pack_bf16(t0[0], t0[1]); qf[hh][1] = pack_bf16(t0[2], t0[3]);
                qf[hh][2] = pack_bf16(t1[0], t1[1]); qf[hh][3] = pack_bf16(t1[2], t1[3]);
                const float* k0 = &acc[32 + 8 * hh]; const float* k1 = &acc[32 + 8 * hh + 4];
                uint4 kv;
                kv.x = pack_bf16(k0[0], k0[1]); kv.y = pack_bf16(k1[0], k1[1]);
                kv.z = pack_bf16(k0[2], k0[3]); kv.w = pack_bf16(k1[2], k1[3]);
                g_kf[((tj * 4 + hh) * 128 + blk) * 32 + lane] = kv;
                const float* v0 = &acc[64 + 8 * hh]; const float* v1 = &acc[64 + 8 * hh + 4];
                uint4 vv;
                vv.x = movmatrix(pack_bf16(v0[0], v0[1])); vv.y = movmatrix(pack_bf16(v0[2], v0[3]));
                vv.z = movmatrix(pack_bf16(v1[0], v1[1])); vv.w = movmatrix(pack_bf16(v1[2], v1[3]));
                g_vf[((tj * 4 + hh) * 128 + blk) * 32 + lane] = vv;
            }
            __syncwarp();
            if (lane == 0) mbar_arrive(sb + B_KVDONE);
            const float z0 = __shfl_sync(0xffffffffu, acc[96], lane & ~3), z1 = __shfl_sync(0xffffffffu, acc[98], lane & ~3);
            g0 = 1.f / (1.f + __expf(-z0)); g1 = 1.f / (1.f + __expf(-z1));
        }
        TS(3);
        const int wrow = (warp & 3) * 16;
        {
            float acc[112];
            int prev = 0;
            for (int s = 0; s < N_FFN1; s++) {
                CWAIT();
                const uint32_t bs = sb + RING_OFF + r.slot * SLOT, as = xa + (s >> 1) * 16384 + (s & 1) * 64;
                wgmma_fence();
                wgmma_ss_n224(acc, desc_a(as), desc_b(bs), s);
                wgmma_ss_n224(acc, desc_a(as + 32), desc_b(bs + 2048), 1);
                wgmma_commit();
                if (s > 0) { wgmma_wait<1>(); if (lane == 0) mbar_arrive(sb + B_EMPTY + 8 * prev); }
                prev = r.slot; r.next();
            }
            wgmma_wait<0>();
            fence_acc(acc);
            if (lane == 0) mbar_arrive(sb + B_EMPTY + 8 * prev);
            TS(4);
            if (lane == 0) mbar_arrive(sb + B_XDEAD);
            const float s0 = 1.f - g0, s1 = 1.f - g1;
            asm volatile("bar.sync %0, 128;" :: "r"(1 + wg) : "memory");
            const uint32_t strow = xa + (wrow + ((lane >> 3) & 1) * 8 + (lane & 7)) * 128;
#pragma unroll
            for (int p = 0; p < 14; p++) {
                const int nt = 2 * p + (lane >> 4);
                const float* a = &acc[8 * p];
                stmatrix_x4(strow + (p >> 2) * 16384 + (((nt & 7) ^ (lane & 7)) << 4),
                            pack_bf16_relu(a[0] * s0, a[1] * s0), pack_bf16_relu(a[2] * s1, a[3] * s1),
                            pack_bf16_relu(a[4] * s0, a[5] * s0), pack_bf16_relu(a[6] * s1, a[7] * s1));
            }
        }
        TS(5);
        {
            const float SC = 0.25f * 1.4426950408889634f;
            const int gb0 = 8 * ti - 16 + warp;
            int slotK = 0, slotV = 0;
            const uint32_t ostore = xa + 4 * 16384 + (wrow + ((lane >> 3) & 1) * 8 + (lane & 7)) * 128;
#define NHEADS 4
#define ATT_KWAIT(kb) do { slotK = r.slot; CWAIT(); kb = sb + RING_OFF + slotK * SLOT + warp * 512 + lane * 16; r.next(); } while (0)
#define ATT_VWAIT(vb) do { slotV = r.slot; CWAIT(); vb = sb + RING_OFF + slotV * SLOT + warp * 512 + lane * 16; r.next(); TS(21 + hh); } while (0)
#define ATT_KREL() do { __syncwarp(); if (lane == 0) mbar_arrive(sb + B_EMPTY + 8 * slotK); } while (0)
#define ATT_VREL() do { __syncwarp(); if (lane == 0) mbar_arrive(sb + B_EMPTY + 8 * slotV); } while (0)
#define ATT_NEXTQ(h) do { \
                if ((h) == 1) { q0 = qf[1][0]; q1 = qf[1][1]; q2 = qf[1][2]; q3 = qf[1][3]; } \
                else if ((h) == 2) { q0 = qf[2][0]; q1 = qf[2][1]; q2 = qf[2][2]; q3 = qf[2][3]; } \
                else { q0 = qf[3][0]; q1 = qf[3][1]; q2 = qf[3][2]; q3 = qf[3][3]; } } while (0)
#define ATT_STORE(h, r0, r1, r2, r3) stmatrix_x4(ostore + (((2 * (h) + (lane >> 4)) ^ (lane & 7)) << 4), r0, r1, r2, r3)
            auto attention = [&](auto masked_tag) {
            constexpr bool MASKED = decltype(masked_tag)::value;
            const float NEG = -INFINITY;
            const uint32_t ONES = 0x3F803F80u;
            float sa[8][2][4], sb2[8][2][4];
            float o[2][4], ls[4];
            float m0, m1;
            uint32_t q0 = qf[0][0], q1 = qf[0][1], q2 = qf[0][2], q3 = qf[0][3];
            auto qk = [&](float (&s)[8][2][4], int ps, int t, uint32_t kbase) {
                if (ps == 0 && t == 0) {
                    const uint4 kd = lds128(kbase + 16 * 512);
                    const uint4 kf = lds128(kbase);
                    float f[2][4];
                    const float ci = (!MASKED || opaque(gb0) >= 0) ? 0.f : NEG;
                    mma16816_c(s[0][0], q0, q1, q2, q3, kd.x, kd.y, 0.f);
                    mma16816_c(s[0][1], q0, q1, q2, q3, kd.z, kd.w, 0.f);
                    mma16816_c(f[0], q0, q1, q2, q3, kf.x, kf.y, ci);
                    mma16816_c(f[1], q0, q1, q2, q3, kf.z, kf.w, ci);
#pragma unroll
                    for (int u = 0; u < 2; u++)
#pragma unroll
                        for (int e = 0; e < 4; e++) {
                            const int row = g + 8 * (e >> 1), col = 8 * u + 2 * c + (e & 1);
                            s[0][u][e] = (col > row) ? f[u][e] : s[0][u][e];
                        }
                } else {
                    const uint4 kf = lds128(kbase + (8 * ps + t) * 512);
                    const float ci = (!MASKED || opaque(gb0) + 8 * ps + t >= 0) ? 0.f : NEG;
                    mma16816_c(s[t][0], q0, q1, q2, q3, kf.x, kf.y, ci);
                    mma16816_c(s[t][1], q0, q1, q2, q3, kf.z, kf.w, ci);
                }
            };
            auto rowmax = [&](float (&s)[8][2][4], float b0, float b1, float& n0, float& n1) {
                int i0 = __float_as_int(b0), i1 = __float_as_int(b1);
#pragma unroll
                for (int t = 0; t < 8; t++)
#pragma unroll
                    for (int u = 0; u < 2; u++) {
                        i0 = __vimax3_s32(i0, __float_as_int(s[t][u][0]), __float_as_int(s[t][u][1]));
                        i1 = __vimax3_s32(i1, __float_as_int(s[t][u][2]), __float_as_int(s[t][u][3]));
                    }
                i0 = max(i0, __shfl_xor_sync(0xffffffffu, i0, 1)); i1 = max(i1, __shfl_xor_sync(0xffffffffu, i1, 1));
                i0 = max(i0, __shfl_xor_sync(0xffffffffu, i0, 2)); i1 = max(i1, __shfl_xor_sync(0xffffffffu, i1, 2));
                n0 = __int_as_float(i0); n1 = __int_as_float(i1);
                if (__any_sync(0xffffffffu, (i0 | i1) < 0)) {
                    asm volatile("" ::: "memory");
                    n0 = b0; n1 = b1;
#pragma unroll
                    for (int t = 0; t < 8; t++)
#pragma unroll
                        for (int u = 0; u < 2; u++) {
                            n0 = fmaxf(n0, fmaxf(s[t][u][0], s[t][u][1]));
                            n1 = fmaxf(n1, fmaxf(s[t][u][2], s[t][u][3]));
                        }
                    n0 = fmaxf(n0, __shfl_xor_sync(0xffffffffu, n0, 1)); n1 = fmaxf(n1, __shfl_xor_sync(0xffffffffu, n1, 1));
                    n0 = fmaxf(n0, __shfl_xor_sync(0xffffffffu, n0, 2)); n1 = fmaxf(n1, __shfl_xor_sync(0xffffffffu, n1, 2));
                }
            };
            auto pv = [&](const float (&p)[2][4], uint32_t vaddr) {
                const uint4 vf = lds128(vaddr);
                const uint32_t a0 = pack_bf16(p[0][0], p[0][1]), a1 = pack_bf16(p[0][2], p[0][3]);
                const uint32_t a2 = pack_bf16(p[1][0], p[1][1]), a3 = pack_bf16(p[1][2], p[1][3]);
                mma16816(o[0], a0, a1, a2, a3, vf.x, vf.y);
                mma16816(o[1], a0, a1, a2, a3, vf.z, vf.w);
                mma16816(ls, a0, a1, a2, a3, ONES, ONES);
            };
            auto expv = [&](float (&s)[8][2][4], int ps, int t, float mc0, float mc1, uint32_t vbase) {
                float p[2][4];
#pragma unroll
                for (int u = 0; u < 2; u++) {
                    p[u][0] = ex2(fmaf(s[t][u][0], SC, -mc0)); p[u][1] = ex2(fmaf(s[t][u][1], SC, -mc0));
                    p[u][2] = ex2(fmaf(s[t][u][2], SC, -mc1)); p[u][3] = ex2(fmaf(s[t][u][3], SC, -mc1));
                }
                if (ps == 0 && t == 0) {
                    float pd[2][4], pf[2][4];
#pragma unroll
                    for (int u = 0; u < 2; u++)
#pragma unroll
                        for (int e = 0; e < 4; e++) {
                            const int row = g + 8 * (e >> 1), col = 8 * u + 2 * c + (e & 1);
                            pf[u][e] = (col > row) ? p[u][e] : 0.f;
                            pd[u][e] = (col > row) ? 0.f : p[u][e];
                        }
                    pv(pd, vbase + 16 * 512);
                    pv(pf, vbase);
                } else {
                    pv(p, vbase + (8 * ps + t) * 512);
                }
            };
            uint32_t kbase, vbase;
            ATT_KWAIT(kbase);
#pragma unroll
            for (int t = 0; t < 8; t++) qk(sa, 0, t, kbase);
            rowmax(sa, NEG, NEG, m0, m1);
#pragma unroll 1
            for (int hh = 0; hh < NHEADS; hh++) {
                ATT_VWAIT(vbase);
#pragma unroll
                for (int e = 0; e < 4; e++) { o[0][e] = 0.f; o[1][e] = 0.f; ls[e] = 0.f; }
                {
                    const float mc0 = m0 * SC, mc1 = m1 * SC;
#pragma unroll
                    for (int t = 0; t < 8; t++) { qk(sb2, 1, t, kbase); expv(sa, 0, t, mc0, mc1, vbase); }
                    ATT_KREL();
                    float n0, n1;
                    rowmax(sb2, m0, m1, n0, n1);
                    const float a0 = ex2((m0 - n0) * SC), a1 = ex2((m1 - n1) * SC);
                    ls[0] *= a0; ls[2] *= a1;
                    o[0][0] *= a0; o[0][1] *= a0; o[1][0] *= a0; o[1][1] *= a0;
                    o[0][2] *= a1; o[0][3] *= a1; o[1][2] *= a1; o[1][3] *= a1;
                    m0 = n0; m1 = n1;
                }
                {
                    const float mc0 = m0 * SC, mc1 = m1 * SC;
                    const bool more = hh + 1 < NHEADS;
                    if (more) {
                        ATT_KWAIT(kbase);
                        ATT_NEXTQ(hh + 1);
#pragma unroll
                        for (int t = 0; t < 8; t++) { qk(sa, 0, t, kbase); expv(sb2, 1, t, mc0, mc1, vbase); }
                        rowmax(sa, NEG, NEG, m0, m1);
                    } else {
#pragma unroll
                        for (int t = 0; t < 8; t++) expv(sb2, 1, t, mc0, mc1, vbase);
                    }
                    ATT_VREL();
                }
                const float f0 = __fdividef(g0, ls[0]), f1 = __fdividef(g1, ls[2]);
                ATT_STORE(hh, pack_bf16(o[0][0] * f0, o[0][1] * f0), pack_bf16(o[0][2] * f1, o[0][3] * f1),
                              pack_bf16(o[1][0] * f0, o[1][1] * f0), pack_bf16(o[1][2] * f1, o[1][3] * f1));
            }
            };
            if (ti >= 2) attention(BoolTag<false>{}); else attention(BoolTag<true>{});
        }
        fence_async_smem();
        asm volatile("bar.sync 4, 256;" ::: "memory");
        TS(6);
        {
            float accA[64], accB[64];
            mbar_wait(sb + B_EREADY, 0);
            uint32_t tag; asm volatile("ld.shared.u32 %0, [%1];" : "=r"(tag) : "r"(sb + EPOCH_OFF) : "memory");
            tag = (tag + 1) & 1u;
            uint4* pdst = g_part + (size_t)((ti * 8 + warp) * 4 * 8 + tj) * 256 + lane;
            auto epilogue = [&](float (&acc)[64], int q) {
                fence_acc(acc);
                uint4* p = pdst + (size_t)q * 8 * 256;
#pragma unroll
                for (int t2 = 0; t2 < 8; t2++) {
                    uint4 v;
                    v.x = pack_bf16(acc[8 * t2 + 0], acc[8 * t2 + 1]); v.y = pack_bf16(acc[8 * t2 + 2], acc[8 * t2 + 3]);
                    v.z = pack_bf16(acc[8 * t2 + 4], acc[8 * t2 + 5]); v.w = pack_bf16(acc[8 * t2 + 6], acc[8 * t2 + 7]);
                    stg_relaxed(p + t2 * 32, make_uint4((v.x & ~1u) | tag, (v.y & ~1u) | tag, (v.z & ~1u) | tag, (v.w & ~1u) | tag));
                }
                __syncwarp();
                if (lane == 0) mbar_arrive(sb + B_PDONE + 8 * q);
            };
            int rel = r.slot;
            if (wg == 1) asm volatile("bar.sync 3, 256;" ::: "memory");
#pragma unroll
            for (int half = 0; half < 2; half++) {
#pragma unroll
                for (int m = 0; m < 9; m++) {
                    const bool ext = (m < N_EXTRA) && (half == 0);
                    const uint32_t bslot = ext ? sb + X_OFF + (5 + m) * 16384 : sb + RING_OFF + r.slot * SLOT;
                    if (ext) mbar_wait(sb + B_EFULL + 8 * m, 0); else CWAIT();
                    wgmma_fence();
#pragma unroll
                    for (int h = 0; h < 2; h++) {
                        const int u = 2 * m + h, rr = u % 9;
                        const uint32_t bs = bslot + h * 8192;
                        const int vk = rr < 7 ? 32 * rr : 256 + 32 * (rr - 7);
                        const uint32_t as = xa + (vk >> 6) * 16384 + (vk & 63) * 2;
                        if (u < 9) {
                            wgmma_ss_n128(accA, desc_a(as), desc_b(bs), rr);
                            wgmma_ss_n128(accA, desc_a(as + 32), desc_b(bs + 2048), 1);
                        } else {
                            wgmma_ss_n128(accB, desc_a(as), desc_b(bs), rr);
                            wgmma_ss_n128(accB, desc_a(as + 32), desc_b(bs + 2048), 1);
                        }
                    }
                    wgmma_commit();
                    if (m == LEAD2 && half == 0 && wg == 0) asm volatile("bar.arrive 3, 256;" ::: "memory");
                    if (!ext) r.next();
                    wgmma_wait<1>();
                    if (m > N_EXTRA || half > 0) {
                        if (lane == 0) mbar_arrive(sb + B_EMPTY + 8 * rel);
                        if (++rel == RING) rel = 0;
                    }
                    if (m == 5) { TS(25 + 2 * half); epilogue(accA, 2 * half); }
                    if (m == 0 && half == 1) { TS(26); epilogue(accB, 1); }
                }
            }
            wgmma_wait<0>();
            TS(7);
            epilogue(accB, 3);
            TS(19);
            reduce_items(sb, out, ti, tj, tag, lane);
            if (tid == 0) TSG(30);
        }
        TS(8);
    }
}

typedef CUresult (*PFN_encodeTiled)(CUtensorMap*, CUtensorMapDataType, cuuint32_t, void*, const cuuint64_t*, const cuuint64_t*,
                                    const cuuint32_t*, const cuuint32_t*, CUtensorMapInterleave, CUtensorMapSwizzle,
                                    CUtensorMapL2promotion, CUtensorMapFloatOOBfill);

void make_map(PFN_encodeTiled enc, CUtensorMap* m, const void* base, int rank, const cuuint64_t* dims, const cuuint64_t* strides, const cuuint32_t* box) {
    cuuint32_t es[5] = {1, 1, 1, 1, 1};
    enc(m, CU_TENSOR_MAP_DATA_TYPE_BFLOAT16, (cuuint32_t)rank, const_cast<void*>(base), dims, strides, box, es,
        CU_TENSOR_MAP_INTERLEAVE_NONE, CU_TENSOR_MAP_SWIZZLE_128B, CU_TENSOR_MAP_L2_PROMOTION_L2_256B, CU_TENSOR_MAP_FLOAT_OOB_FILL_NONE);
}

}

extern "C" void kernel_launch(void* const* d_in, const int* in_sizes, int n_in, void* d_out, int out_size) {
    (void)in_sizes; (void)n_in; (void)out_size;
    const void* x = d_in[0]; const void* wqkv = d_in[1]; const void* wo = d_in[2];
    const void* w1 = d_in[4]; const void* w2 = d_in[5]; const void* gate_w = d_in[6];
    static PFN_encodeTiled enc = nullptr;
    if (!enc) {
        void* fn = nullptr; cudaDriverEntryPointQueryResult st;
        cudaGetDriverEntryPoint("cuTensorMapEncodeTiled", &fn, cudaEnableDefault, &st);
        enc = (PFN_encodeTiled)fn;
        cudaFuncSetAttribute(fused_kernel, cudaFuncAttributeMaxDynamicSharedMemorySize, SMEM_BYTES);
    }
    CUtensorMap mx, mqkv, mw1, mw2, mwo, mw1a;
    { cuuint64_t d[4] = {64, 512, 3, 8}, s[3] = {3584, 128, 448}; cuuint32_t b[4] = {64, 32, 3, 1}; make_map(enc, &mw1a, w1, 4, d, s, b); }
    { cuuint64_t d[2] = {512, 2048}, s[1] = {1024}; cuuint32_t b[2] = {64, 128}; make_map(enc, &mx, x, 2, d, s, b); }
    { cuuint64_t d[4] = {64, 512, 8, 3}, s[3] = {3072, 128, 1024}; cuuint32_t b[4] = {64, 32, 1, 3}; make_map(enc, &mqkv, wqkv, 4, d, s, b); }
    { cuuint64_t d[2] = {1792, 512}, s[1] = {3584}; cuuint32_t b[2] = {64, 32}; make_map(enc, &mw1, w1, 2, d, s, b); }
    { cuuint64_t d[3] = {64, 1792, 8}, s[2] = {1024, 128}; cuuint32_t b[3] = {64, 32, 2}; make_map(enc, &mw2, w2, 3, d, s, b); }
    { cuuint64_t d[3] = {64, 512, 8}, s[2] = {1024, 128}; cuuint32_t b[3] = {64, 32, 2}; make_map(enc, &mwo, wo, 3, d, s, b); }
    fused_kernel<<<128, 384, SMEM_BYTES, cudaStreamPerThread>>>(mx, mqkv, mw1, mw2, mwo, mw1a, (const __nv_bfloat16*)gate_w, (__nv_bfloat16*)d_out,
                                           (const uint8_t*)w1, (const uint8_t*)w2, (const uint8_t*)wo,
                                           (const uint8_t*)x, (const uint8_t*)wqkv);
}
```

```cpp
#include <cuda_runtime.h>
#include <cuda_bf16.h>
#include <cuda.h>
#include <stdint.h>

namespace {

#define PF1_AT 1
#define PF2_AT 7
#define LEAD1 2
#define LEAD2 2
constexpr int RING = 6;
constexpr int SLOT = 16384;
constexpr uint32_t X_OFF = 0;
constexpr uint32_t RING_OFF = 131072;
constexpr uint32_t BAR_OFF = RING_OFF + RING * SLOT;
constexpr uint32_t B_FULL = BAR_OFF, B_EMPTY = BAR_OFF + 64, B_XFULL = BAR_OFF + 128, B_XDEAD = BAR_OFF + 192,
                   B_EREADY = BAR_OFF + 200, B_KVDONE = BAR_OFF + 208, B_PDONE = BAR_OFF + 216,
                   B_KVREADY = BAR_OFF + 248, B_EFULL = BAR_OFF + 264,
                   B_ECONS = BAR_OFF + 288, B_SFREE = BAR_OFF + 296,
                   B_SFULL = BAR_OFF + 320;
constexpr uint32_t STG_OFF = X_OFF + 5 * 16384;
constexpr uint32_t EPOCH_OFF = BAR_OFF + 256, ITEM_OFF = BAR_OFF + 260;
constexpr uint32_t SMEM_BYTES = BAR_OFF + 1024;

constexpr int N_QKV = 16, N_FFN1 = 16, N_KV = 8, N_EXTRA = 3, N_FFN2 = 18 - N_EXTRA;
constexpr int S_FFN1 = N_QKV, S_KV = S_FFN1 + N_FFN1, S_FFN2 = S_KV + N_KV;

__device__ uint4 g_kf[32 * 128 * 32];
__device__ uint4 g_vf[32 * 128 * 32];
__device__ uint4 g_part[16 * 8 * 4 * 4 * 8 * 32];
__device__ unsigned g_ticket;
__device__ unsigned g_kvcnt[128 * 32];
#define TS(k) do {} while (0)
#define TS2(k) do {} while (0)
#define TS2X(k) do {} while (0)
#define TSX(k) do {} while (0)
#define TSG(k) do {} while (0)

__device__ __forceinline__ uint32_t smem_u32(const void* p) { return (uint32_t)__cvta_generic_to_shared(p); }
__device__ __forceinline__ void mbar_init(uint32_t bar, uint32_t cnt) { asm volatile("mbarrier.init.shared::cta.b64 [%0], %1;" :: "r"(bar), "r"(cnt) : "memory"); }
__device__ __forceinline__ void mbar_expect_tx(uint32_t bar, uint32_t bytes) { asm volatile("mbarrier.arrive.expect_tx.shared::cta.b64 _, [%0], %1;" :: "r"(bar), "r"(bytes) : "memory"); }
__device__ __forceinline__ void mbar_expect_only(uint32_t bar, uint32_t bytes) { asm volatile("mbarrier.expect_tx.relaxed.cta.shared::cta.b64 [%0], %1;" :: "r"(bar), "r"(bytes) : "memory"); }
__device__ __forceinline__ void mbar_arrive(uint32_t bar) { asm volatile("mbarrier.arrive.shared::cta.b64 _, [%0];" :: "r"(bar) : "memory"); }
__device__ __forceinline__ bool mbar_try(uint32_t bar, uint32_t parity) {
    uint32_t ok;
    asm volatile("{\n.reg .pred P1;\nmbarrier.try_wait.parity.shared::cta.b64 P1, [%1], %2;\nselp.u32 %0, 1, 0, P1;\n}" : "=r"(ok) : "r"(bar), "r"(parity) : "memory");
    return ok != 0;
}
__device__ __forceinline__ void mbar_wait(uint32_t bar, uint32_t parity) {
    asm volatile("{\n.reg .pred P1, P2;\n.reg .u32 n;\nmov.u32 n, 0;\n"
                 "WAIT_LOOP:\n"
                 "mbarrier.try_wait.parity.shared::cta.b64 P1, [%0], %1;\n"
                 "@P1 bra WAIT_DONE;\n"
                 "add.u32 n, n, 1;\n"
                 "setp.lt.u32 P2, n, 0x400000;\n"
                 "@P2 bra WAIT_LOOP;\n"
                 "WAIT_DONE:\n}" :: "r"(bar), "r"(parity) : "memory");
}
__device__ __forceinline__ void mbar_wait_cluster(uint32_t bar, uint32_t parity) {
    asm volatile("{\n.reg .pred P1, P2;\n.reg .u32 n;\nmov.u32 n, 0;\n"
                 "WAIT_LOOP:\n"
                 "mbarrier.try_wait.parity.acquire.cluster.shared::cta.b64 P1, [%0], %1;\n"
                 "@P1 bra WAIT_DONE;\n"
                 "add.u32 n, n, 1;\n"
                 "setp.lt.u32 P2, n, 0x400000;\n"
                 "@P2 bra WAIT_LOOP;\n"
                 "WAIT_DONE:\n}" :: "r"(bar), "r"(parity) : "memory");
}
__device__ __forceinline__ uint32_t mapa(uint32_t addr, uint32_t cta) {
    uint32_t r; asm volatile("mapa.shared::cluster.u32 %0, %1, %2;" : "=r"(r) : "r"(addr), "r"(cta)); return r;
}
__device__ __forceinline__ void mbar_arrive_remote(uint32_t rbar) {
    asm volatile("mbarrier.arrive.relaxed.cluster.shared::cluster.b64 _, [%0];" :: "r"(rbar) : "memory");
}
__device__ __forceinline__ void st_async_v4(uint32_t raddr, uint4 v, uint32_t rbar) {
    asm volatile("st.async.weak.shared::cluster.mbarrier::complete_tx::bytes.v4.b32 [%0], {%1, %2, %3, %4}, [%5];"
        :: "r"(raddr), "r"(v.x), "r"(v.y), "r"(v.z), "r"(v.w), "r"(rbar) : "memory");
}
__device__ __forceinline__ void tma_2d(uint32_t dst, const void* map, uint32_t bar, int c0, int c1) {
    asm volatile("cp.async.bulk.tensor.2d.shared::cluster.global.mbarrier::complete_tx::bytes [%0], [%1, {%3, %4}], [%2];"
        :: "r"(dst), "l"(map), "r"(bar), "r"(c0), "r"(c1) : "memory");
}
__device__ __forceinline__ void tma_3d(uint32_t dst, const void* map, uint32_t bar, int c0, int c1, int c2) {
    asm volatile("cp.async.bulk.tensor.3d.shared::cluster.global.mbarrier::complete_tx::bytes [%0], [%1, {%3, %4, %5}], [%2];"
        :: "r"(dst), "l"(map), "r"(bar), "r"(c0), "r"(c1), "r"(c2) : "memory");
}
__device__ __forceinline__ void tma_4d(uint32_t dst, const void* map, uint32_t bar, int c0, int c1, int c2, int c3) {
    asm volatile("cp.async.bulk.tensor.4d.shared::cluster.global.mbarrier::complete_tx::bytes [%0], [%1, {%3, %4, %5, %6}], [%2];"
        :: "r"(dst), "l"(map), "r"(bar), "r"(c0), "r"(c1), "r"(c2), "r"(c3) : "memory");
}
__device__ __forceinline__ void bulk_g2s(uint32_t dst, const void* src, uint32_t bytes, uint32_t bar) {
    asm volatile("cp.async.bulk.shared::cluster.global.mbarrier::complete_tx::bytes [%0], [%1], %2, [%3];"
        :: "r"(dst), "l"(src), "r"(bytes), "r"(bar) : "memory");
}
__device__ __forceinline__ void prefetch_l2(const void* src, uint32_t bytes) {
    asm volatile("cp.async.bulk.prefetch.L2.global [%0], %1;" :: "l"(src), "r"(bytes) : "memory");
}
__device__ __forceinline__ bool elect_one() {
    uint32_t p;
    asm volatile("{\n.reg .pred P;\nelect.sync _|P, 0xffffffff;\nselp.u32 %0, 1, 0, P;\n}" : "=r"(p));
    return p != 0;
}
__device__ __forceinline__ void wgmma_fence() { asm volatile("wgmma.fence.sync.aligned;" ::: "memory"); }
__device__ __forceinline__ void wgmma_commit() { asm volatile("wgmma.commit_group.sync.aligned;" ::: "memory"); }
template <int N> __device__ __forceinline__ void wgmma_wait() { asm volatile("wgmma.wait_group.sync.aligned %0;" :: "n"(N) : "memory"); }
__device__ __forceinline__ void fence_async_smem() { asm volatile("fence.proxy.async.shared::cta;" ::: "memory"); }
__device__ __forceinline__ uint64_t desc_a(uint32_t addr) {
    return (uint64_t)((addr & 0x3FFFF) >> 4) | ((uint64_t)1 << 16) | ((uint64_t)(1024 >> 4) << 32) | ((uint64_t)1 << 62);
}
__device__ __forceinline__ uint64_t desc_b(uint32_t addr) {
    return (uint64_t)((addr & 0x3FFFF) >> 4) | ((uint64_t)(4096 >> 4) << 16) | ((uint64_t)(1024 >> 4) << 32) | ((uint64_t)1 << 62);
}
__device__ __forceinline__ uint32_t pack_bf16(float lo, float hi) {
    uint32_t r; asm("cvt.rn.bf16x2.f32 %0, %1, %2;" : "=r"(r) : "f"(hi), "f"(lo)); return r;
}
__device__ __forceinline__ uint32_t pack_bf16_relu(float lo, float hi) {
    uint32_t r; asm("cvt.rn.relu.bf16x2.f32 %0, %1, %2;" : "=r"(r) : "f"(hi), "f"(lo)); return r;
}
__device__ __forceinline__ uint32_t movmatrix(uint32_t a) {
    uint32_t d; asm volatile("movmatrix.sync.aligned.m8n8.trans.b16 %0, %1;" : "=r"(d) : "r"(a)); return d;
}
__device__ __forceinline__ void stmatrix_x4(uint32_t addr, uint32_t r0, uint32_t r1, uint32_t r2, uint32_t r3) {
    asm volatile("stmatrix.sync.aligned.m8n8.x4.shared.b16 [%0], {%1, %2, %3, %4};" :: "r"(addr), "r"(r0), "r"(r1), "r"(r2), "r"(r3) : "memory");
}
__device__ __forceinline__ uint4 lds128(uint32_t addr) {
    uint4 v; asm volatile("ld.shared.v4.b32 {%0, %1, %2, %3}, [%4];" : "=r"(v.x), "=r"(v.y), "=r"(v.z), "=r"(v.w) : "r"(addr) : "memory"); return v;
}
__device__ __forceinline__ void mma16816(float (&c)[4], uint32_t a0, uint32_t a1, uint32_t a2, uint32_t a3, uint32_t b0, uint32_t b1) {
    asm volatile("mma.sync.aligned.m16n8k16.row.col.f32.bf16.bf16.f32 {%0,%1,%2,%3}, {%4,%5,%6,%7}, {%8,%9}, {%0,%1,%2,%3};"
        : "+f"(c[0]), "+f"(c[1]), "+f"(c[2]), "+f"(c[3]) : "r"(a0), "r"(a1), "r"(a2), "r"(a3), "r"(b0), "r"(b1));
}
__device__ __forceinline__ void mma16816_c(float (&c)[4], uint32_t a0, uint32_t a1, uint32_t a2, uint32_t a3, uint32_t b0, uint32_t b1, float ci) {
    asm volatile("mma.sync.aligned.m16n8k16.row.col.f32.bf16.bf16.f32 {%0,%1,%2,%3}, {%4,%5,%6,%7}, {%8,%9}, {%10,%10,%10,%10};"
        : "=f"(c[0]), "=f"(c[1]), "=f"(c[2]), "=f"(c[3]) : "r"(a0), "r"(a1), "r"(a2), "r"(a3), "r"(b0), "r"(b1), "f"(ci));
}
__device__ __forceinline__ int opaque(int v) { asm volatile("" : "+r"(v)); return v; }
__device__ __forceinline__ float ex2(float x) { float y; asm("ex2.approx.ftz.f32 %0, %1;" : "=f"(y) : "f"(x)); return y; }
__device__ __forceinline__ unsigned ld_acquire(const unsigned* p) {
    unsigned v; asm volatile("ld.acquire.gpu.global.u32 %0, [%1];" : "=r"(v) : "l"(p) : "memory"); return v;
}
__device__ __forceinline__ void red_release(unsigned* p, unsigned v) {
    asm volatile("red.release.gpu.global.add.u32 [%0], %1;" :: "l"(p), "r"(v) : "memory");
}
__device__ __forceinline__ void wait_counter(const unsigned* p, unsigned target) {
    uint32_t n = 0;
    while ((int)(ld_acquire(p) - target) < 0) { if (++n > (1u << 20)) break; }
}
__device__ __forceinline__ uint4 ldg_weak(const uint4* p) {
    uint4 v; asm volatile("ld.global.L1::no_allocate.v4.b32 {%0, %1, %2, %3}, [%4];" : "=r"(v.x), "=r"(v.y), "=r"(v.z), "=r"(v.w) : "l"(p) : "memory"); return v;
}
__device__ __forceinline__ float bf_lo(uint32_t v) { return __uint_as_float(v << 16); }
__device__ __forceinline__ float bf_hi(uint32_t v) { return __uint_as_float(v & 0xFFFF0000u); }

__device__ __forceinline__ void wgmma_ss_n128(float (&d)[64], uint64_t da, uint64_t db, int scale_d) {
    asm volatile("{\n.reg .pred p;\nsetp.ne.b32 p, %66, 0;\n"
        "wgmma.mma_async.sync.aligned.m64n128k16.f32.bf16.bf16 {%0, %1, %2, %3, %4, %5, %6, %7, %8, %9, %10, %11, %12, %13, %14, %15, %16, %17, %18, %19, %20, %21, %22, %23, %24, %25, %26, %27, %28, %29, %30, %31, %32, %33, %34, %35, %36, %37, %38, %39, %40, %41, %42, %43, %44, %45, %46, %47, %48, %49, %50, %51, %52, %53, %54, %55, %56, %57, %58, %59, %60, %61, %62, %63}, %64, %65, p, 1, 1, 0, 1;\n}\n"
        : "+f"(d[0]), "+f"(d[1]), "+f"(d[2]), "+f"(d[3]), "+f"(d[4]), "+f"(d[5]), "+f"(d[6]), "+f"(d[7]), "+f"(d[8]), "+f"(d[9]), "+f"(d[10]), "+f"(d[11]), "+f"(d[12]), "+f"(d[13]), "+f"(d[14]), "+f"(d[15]), "+f"(d[16]), "+f"(d[17]), "+f"(d[18]), "+f"(d[19]), "+f"(d[20]), "+f"(d[21]), "+f"(d[22]), "+f"(d[23]), "+f"(d[24]), "+f"(d[25]), "+f"(d[26]), "+f"(d[27]), "+f"(d[28]), "+f"(d[29]), "+f"(d[30]), "+f"(d[31]), "+f"(d[32]), "+f"(d[33]), "+f"(d[34]), "+f"(d[35]), "+f"(d[36]), "+f"(d[37]), "+f"(d[38]), "+f"(d[39]), "+f"(d[40]), "+f"(d[41]), "+f"(d[42]), "+f"(d[43]), "+f"(d[44]), "+f"(d[45]), "+f"(d[46]), "+f"(d[47]), "+f"(d[48]), "+f"(d[49]), "+f"(d[50]), "+f"(d[51]), "+f"(d[52]), "+f"(d[53]), "+f"(d[54]), "+f"(d[55]), "+f"(d[56]), "+f"(d[57]), "+f"(d[58]), "+f"(d[59]), "+f"(d[60]), "+f"(d[61]), "+f"(d[62]), "+f"(d[63])
        : "l"(da), "l"(db), "r"(scale_d));
}
__device__ __forceinline__ void wgmma_ss_n200(float (&d)[100], uint64_t da, uint64_t db, int scale_d) {
    asm volatile("{\n.reg .pred p;\nsetp.ne.b32 p, %102, 0;\n"
        "wgmma.mma_async.sync.aligned.m64n200k16.f32.bf16.bf16 {%0, %1, %2, %3, %4, %5, %6, %7, %8, %9, %10, %11, %12, %13, %14, %15, %16, %17, %18, %19, %20, %21, %22, %23, %24, %25, %26, %27, %28, %29, %30, %31, %32, %33, %34, %35, %36, %37, %38, %39, %40, %41, %42, %43, %44, %45, %46, %47, %48, %49, %50, %51, %52, %53, %54, %55, %56, %57, %58, %59, %60, %61, %62, %63, %64, %65, %66, %67, %68, %69, %70, %71, %72, %73, %74, %75, %76, %77, %78, %79, %80, %81, %82, %83, %84, %85, %86, %87, %88, %89, %90, %91, %92, %93, %94, %95, %96, %97, %98, %99}, %100, %101, p, 1, 1, 0, 1;\n}\n"
        : "+f"(d[0]), "+f"(d[1]), "+f"(d[2]), "+f"(d[3]), "+f"(d[4]), "+f"(d[5]), "+f"(d[6]), "+f"(d[7]), "+f"(d[8]), "+f"(d[9]), "+f"(d[10]), "+f"(d[11]), "+f"(d[12]), "+f"(d[13]), "+f"(d[14]), "+f"(d[15]), "+f"(d[16]), "+f"(d[17]), "+f"(d[18]), "+f"(d[19]), "+f"(d[20]), "+f"(d[21]), "+f"(d[22]), "+f"(d[23]), "+f"(d[24]), "+f"(d[25]), "+f"(d[26]), "+f"(d[27]), "+f"(d[28]), "+f"(d[29]), "+f"(d[30]), "+f"(d[31]), "+f"(d[32]), "+f"(d[33]), "+f"(d[34]), "+f"(d[35]), "+f"(d[36]), "+f"(d[37]), "+f"(d[38]), "+f"(d[39]), "+f"(d[40]), "+f"(d[41]), "+f"(d[42]), "+f"(d[43]), "+f"(d[44]), "+f"(d[45]), "+f"(d[46]), "+f"(d[47]), "+f"(d[48]), "+f"(d[49]), "+f"(d[50]), "+f"(d[51]), "+f"(d[52]), "+f"(d[53]), "+f"(d[54]), "+f"(d[55]), "+f"(d[56]), "+f"(d[57]), "+f"(d[58]), "+f"(d[59]), "+f"(d[60]), "+f"(d[61]), "+f"(d[62]), "+f"(d[63]), "+f"(d[64]), "+f"(d[65]), "+f"(d[66]), "+f"(d[67]), "+f"(d[68]), "+f"(d[69]), "+f"(d[70]), "+f"(d[71]), "+f"(d[72]), "+f"(d[73]), "+f"(d[74]), "+f"(d[75]), "+f"(d[76]), "+f"(d[77]), "+f"(d[78]), "+f"(d[79]), "+f"(d[80]), "+f"(d[81]), "+f"(d[82]), "+f"(d[83]), "+f"(d[84]), "+f"(d[85]), "+f"(d[86]), "+f"(d[87]), "+f"(d[88]), "+f"(d[89]), "+f"(d[90]), "+f"(d[91]), "+f"(d[92]), "+f"(d[93]), "+f"(d[94]), "+f"(d[95]), "+f"(d[96]), "+f"(d[97]), "+f"(d[98]), "+f"(d[99])
        : "l"(da), "l"(db), "r"(scale_d));
}
__device__ __forceinline__ void wgmma_ss_n224(float (&d)[112], uint64_t da, uint64_t db, int scale_d) {
    asm volatile("{\n.reg .pred p;\nsetp.ne.b32 p, %114, 0;\n"
        "wgmma.mma_async.sync.aligned.m64n224k16.f32.bf16.bf16 {%0, %1, %2, %3, %4, %5, %6, %7, %8, %9, %10, %11, %12, %13, %14, %15, %16, %17, %18, %19, %20, %21, %22, %23, %24, %25, %26, %27, %28, %29, %30, %31, %32, %33, %34, %35, %36, %37, %38, %39, %40, %41, %42, %43, %44, %45, %46, %47, %48, %49, %50, %51, %52, %53, %54, %55, %56, %57, %58, %59, %60, %61, %62, %63, %64, %65, %66, %67, %68, %69, %70, %71, %72, %73, %74, %75, %76, %77, %78, %79, %80, %81, %82, %83, %84, %85, %86, %87, %88, %89, %90, %91, %92, %93, %94, %95, %96, %97, %98, %99, %100, %101, %102, %103, %104, %105, %106, %107, %108, %109, %110, %111}, %112, %113, p, 1, 1, 0, 1;\n}\n"
        : "+f"(d[0]), "+f"(d[1]), "+f"(d[2]), "+f"(d[3]), "+f"(d[4]), "+f"(d[5]), "+f"(d[6]), "+f"(d[7]), "+f"(d[8]), "+f"(d[9]), "+f"(d[10]), "+f"(d[11]), "+f"(d[12]), "+f"(d[13]), "+f"(d[14]), "+f"(d[15]), "+f"(d[16]), "+f"(d[17]), "+f"(d[18]), "+f"(d[19]), "+f"(d[20]), "+f"(d[21]), "+f"(d[22]), "+f"(d[23]), "+f"(d[24]), "+f"(d[25]), "+f"(d[26]), "+f"(d[27]), "+f"(d[28]), "+f"(d[29]), "+f"(d[30]), "+f"(d[31]), "+f"(d[32]), "+f"(d[33]), "+f"(d[34]), "+f"(d[35]), "+f"(d[36]), "+f"(d[37]), "+f"(d[38]), "+f"(d[39]), "+f"(d[40]), "+f"(d[41]), "+f"(d[42]), "+f"(d[43]), "+f"(d[44]), "+f"(d[45]), "+f"(d[46]), "+f"(d[47]), "+f"(d[48]), "+f"(d[49]), "+f"(d[50]), "+f"(d[51]), "+f"(d[52]), "+f"(d[53]), "+f"(d[54]), "+f"(d[55]), "+f"(d[56]), "+f"(d[57]), "+f"(d[58]), "+f"(d[59]), "+f"(d[60]), "+f"(d[61]), "+f"(d[62]), "+f"(d[63]), "+f"(d[64]), "+f"(d[65]), "+f"(d[66]), "+f"(d[67]), "+f"(d[68]), "+f"(d[69]), "+f"(d[70]), "+f"(d[71]), "+f"(d[72]), "+f"(d[73]), "+f"(d[74]), "+f"(d[75]), "+f"(d[76]), "+f"(d[77]), "+f"(d[78]), "+f"(d[79]), "+f"(d[80]), "+f"(d[81]), "+f"(d[82]), "+f"(d[83]), "+f"(d[84]), "+f"(d[85]), "+f"(d[86]), "+f"(d[87]), "+f"(d[88]), "+f"(d[89]), "+f"(d[90]), "+f"(d[91]), "+f"(d[92]), "+f"(d[93]), "+f"(d[94]), "+f"(d[95]), "+f"(d[96]), "+f"(d[97]), "+f"(d[98]), "+f"(d[99]), "+f"(d[100]), "+f"(d[101]), "+f"(d[102]), "+f"(d[103]), "+f"(d[104]), "+f"(d[105]), "+f"(d[106]), "+f"(d[107]), "+f"(d[108]), "+f"(d[109]), "+f"(d[110]), "+f"(d[111])
        : "l"(da), "l"(db), "r"(scale_d));
}
template <int N> __device__ __forceinline__ void fence_acc(float (&d)[N]) {
#pragma unroll
    for (int i = 0; i < N; i++) asm volatile("" : "+f"(d[i]) :: "memory");
}

__device__ __forceinline__ void reduce_store(const uint4 (&v)[4], __nv_bfloat16* __restrict__ out, int ti, int tj, int q, int t2, int lane) {
    float a[8];
#pragma unroll
    for (int e = 0; e < 8; e++) a[e] = 0.f;
#pragma unroll
    for (int s = 0; s < 4; s++) {
        a[0] += bf_lo(v[s].x); a[1] += bf_hi(v[s].x); a[2] += bf_lo(v[s].y); a[3] += bf_hi(v[s].y);
        a[4] += bf_lo(v[s].z); a[5] += bf_hi(v[s].z); a[6] += bf_lo(v[s].w); a[7] += bf_hi(v[s].w);
    }
    const uint32_t lo0 = pack_bf16(a[0], a[1]), lo1 = pack_bf16(a[4], a[5]);
    const uint32_t hi0 = pack_bf16(a[2], a[3]), hi1 = pack_bf16(a[6], a[7]);
    const bool odd = lane & 1;
    const uint32_t sl = __shfl_xor_sync(0xffffffffu, odd ? lo0 : lo1, 1);
    const uint32_t sh = __shfl_xor_sync(0xffffffffu, odd ? hi0 : hi1, 1);
    const uint2 wl = odd ? make_uint2(sl, lo1) : make_uint2(lo0, sl);
    const uint2 wh = odd ? make_uint2(sh, hi1) : make_uint2(hi0, sh);
    __nv_bfloat16* o = out + (size_t)(ti * 128 + tj * 16 + (lane >> 2)) * 512 + q * 128 + t2 * 16 + (odd ? 8 : 0) + (lane & 2) * 2;
    *reinterpret_cast<uint2*>(o) = wl;
    *reinterpret_cast<uint2*>(o + 8 * 512) = wh;
}
__device__ __forceinline__ uint4* part_ptr(int ti, int owner, int q, int t2, int lane) {
    return g_part + (size_t)(((ti * 8 + owner) * 4 + q) * 4) * 256 + t2 * 32 + lane;
}
__device__ __forceinline__ uint4 ldg_relaxed(const uint4* p) {
    uint4 v; asm volatile("ld.relaxed.gpu.global.v4.b32 {%0, %1, %2, %3}, [%4];" : "=r"(v.x), "=r"(v.y), "=r"(v.z), "=r"(v.w) : "l"(p) : "memory"); return v;
}
__device__ __forceinline__ void stg_relaxed(uint4* p, uint4 v) {
    asm volatile("st.relaxed.gpu.global.v4.b32 [%0], {%1, %2, %3, %4};" :: "l"(p), "r"(v.x), "r"(v.y), "r"(v.z), "r"(v.w) : "memory");
}
#define LD_FIRST ldg_relaxed
#define ST_PART stg_relaxed
__device__ __forceinline__ void reduce_items(uint32_t sb, __nv_bfloat16* __restrict__ out, int ti, int tj, uint32_t tag, int lane) {
    for (;;) {
        uint32_t item = 0;
        if (lane == 0) asm volatile("atom.shared.add.u32 %0, [%1], 1;" : "=r"(item) : "r"(sb + ITEM_OFF) : "memory");
        item = __shfl_sync(0xffffffffu, item, 0);
        if (item >= 16) break;
        const int q = item >> 2, t2 = (item & 3) * 2;
        mbar_wait(sb + B_PDONE + 8 * q, 0);
        const uint4* p = part_ptr(ti, tj, q, t2, lane);
        uint4 v[2][4];
#pragma unroll
        for (int n = 0; n < 2; n++)
#pragma unroll
            for (int s = 0; s < 4; s++) v[n][s] = ldg_relaxed(p + s * 256 + n * 32);
        int it = 0;
        for (; it < (1 << 16); it++) {
            bool ok = true;
#pragma unroll
            for (int n = 0; n < 2; n++)
#pragma unroll
                for (int s = 0; s < 4; s++) {
                    const uint32_t bad = ((v[n][s].x ^ tag) | (v[n][s].y ^ tag) | (v[n][s].z ^ tag) | (v[n][s].w ^ tag)) & 1u;
                    if (bad) { v[n][s] = ldg_relaxed(p + s * 256 + n * 32); ok = false; }
                }
            if (__all_sync(0xffffffffu, ok)) break;
        }
        reduce_store(v[0], out, ti, tj, q, t2, lane);
        reduce_store(v[1], out, ti, tj, q, t2 + 1, lane);
    }
}

#define PWAIT() mbar_wait(sb + B_EMPTY + 8 * r.slot, r.phase)
#define CWAIT() mbar_wait(sb + B_FULL + 8 * r.slot, r.phase)
template <bool B> struct BoolTag { static constexpr bool value = B; };
struct Ring {
    int slot; uint32_t phase;
    __device__ __forceinline__ void next() { if (++slot == RING) { slot = 0; phase ^= 1; } }
};

__global__ void __launch_bounds__(384, 1)
fused_kernel(const __grid_constant__ CUtensorMap map_x, const __grid_constant__ CUtensorMap map_qkv,
             const __grid_constant__ CUtensorMap map_w1, const __grid_constant__ CUtensorMap map_w2,
             const __grid_constant__ CUtensorMap map_wo, const __grid_constant__ CUtensorMap map_w1a,
             const __nv_bfloat16* __restrict__ gate_w, __nv_bfloat16* __restrict__ out,
             const uint8_t* __restrict__ w1p, const uint8_t* __restrict__ w2p, const uint8_t* __restrict__ wop,
             const uint8_t* __restrict__ xp, const uint8_t* __restrict__ wqkvp)
{
    extern __shared__ __align__(1024) uint8_t smem_raw[];
    const uint32_t sb = smem_u32(smem_raw);
    const int tid = threadIdx.x, warp = tid >> 5, lane = tid & 31;
    const int ti = blockIdx.x >> 3, tj = blockIdx.x & 7;

    if (tid == 0) { TSG(31); TSX(0); }
    if (tid == 320) {
        asm volatile("prefetch.tensormap [%0];" :: "l"(&map_x) : "memory");
        asm volatile("prefetch.tensormap [%0];" :: "l"(&map_qkv) : "memory");
        asm volatile("prefetch.tensormap [%0];" :: "l"(&map_w1) : "memory");
        asm volatile("prefetch.tensormap [%0];" :: "l"(&map_w2) : "memory");
        asm volatile("prefetch.tensormap [%0];" :: "l"(&map_wo) : "memory");
        asm volatile("prefetch.tensormap [%0];" :: "l"(&map_w1a) : "memory");
    }
    uint32_t gwv[N_QKV / 2];
    if (warp == 8) {
        const unsigned short* gws = reinterpret_cast<const unsigned short*>(gate_w);
#pragma unroll
        for (int n = 0; n < N_QKV / 2; n++) gwv[n] = (uint32_t)__ldg(gws + 64 * n + lane) | ((uint32_t)__ldg(gws + 64 * n + 32 + lane) << 16);
    }
    if (tid == 256) {
        for (int s = 0; s < RING; s++) { mbar_init(sb + B_FULL + 8 * s, 1); mbar_init(sb + B_EMPTY + 8 * s, 8); }
        for (int s = 0; s < 8; s++) mbar_init(sb + B_XFULL + 8 * s, 1);
        mbar_init(sb + B_XDEAD, 8); mbar_init(sb + B_EREADY, 1); mbar_init(sb + B_KVDONE, 8); mbar_init(sb + B_KVREADY, 1);
        for (int s = 0; s < 4; s++) mbar_init(sb + B_PDONE + 8 * s, 8);
        for (int s = 0; s < 3; s++) mbar_init(sb + B_EFULL + 8 * s, 1);
        mbar_init(sb + B_ECONS, 8); mbar_init(sb + B_SFREE, 4); mbar_init(sb + B_SFREE + 8, 4);
        for (int s = 0; s < 8; s++) mbar_init(sb + B_SFULL + 8 * s, 1);
        asm volatile("st.shared.u32 [%0], %1;" :: "r"(sb + ITEM_OFF), "r"(0) : "memory");
        asm volatile("fence.mbarrier_init.release.cluster;" ::: "memory");
        fence_async_smem();
        mbar_expect_tx(sb + B_XFULL, 16384);
        tma_2d(sb + X_OFF, &map_x, sb + B_XFULL, 0, ti * 128);
        mbar_expect_only(sb + B_FULL, 12288);
        tma_4d(sb + RING_OFF, &map_qkv, sb + B_FULL, 0, 0, tj, 0);
    }
    __syncthreads();
    asm volatile("barrier.cluster.arrive.release.aligned;" ::: "memory");

    if (warp >= 8) {
        asm volatile("setmaxnreg.dec.sync.aligned.u32 56;");
        if (warp == 8) {
            Ring r{0, 1};
            const bool leader = elect_one();
#pragma unroll
            for (int n = 0; n < N_QKV; n++) {
                const uint32_t full = sb + B_FULL + 8 * r.slot, dst = sb + RING_OFF + r.slot * SLOT;
                if (n > 0) {
                    if (!(n & 1) && leader) {
                        mbar_expect_tx(sb + B_XFULL + 8 * (n >> 1), 16384);
                        tma_2d(sb + X_OFF + (n >> 1) * 16384, &map_x, sb + B_XFULL + 8 * (n >> 1), (n >> 1) * 64, ti * 128);
                    }
                    if (n >= RING) PWAIT();
                    if (leader) {
                        mbar_expect_only(full, 12288);
                        tma_4d(dst, &map_qkv, full, 0, 32 * n, tj, 0);
                    }
                }
                const uint32_t gv = (n & 1) ? (gwv[n >> 1] >> 16) : (gwv[n >> 1] & 0xFFFFu);
                asm volatile("st.shared.v4.b32 [%0], {%1, %2, %2, %2};" :: "r"(dst + 12288 + lane * 128 + ((lane & 7) << 4)), "r"(gv), "r"(0) : "memory");
                fence_async_smem();
                __syncwarp();
                if (leader) mbar_arrive(full);
                r.next();
            }
            asm volatile("barrier.cluster.wait.acquire.aligned;" ::: "memory");
#pragma unroll 1
            for (int n = 0; n < N_FFN1; n++) {
                const uint32_t full = sb + B_FULL + 8 * r.slot, dst = sb + RING_OFF + r.slot * SLOT;
                PWAIT();
                if (leader) {
                    mbar_expect_tx(full, 16384);
                    tma_4d(dst, &map_w1a, full, 0, 32 * n, 0, tj);
                    tma_2d(dst + 3 * 4096, &map_w1, full, 224 * tj + 192, 32 * n);
                }
                r.next();
            }
            if (lane == 0) TSX(10);
            mbar_wait(sb + B_KVREADY, 0);
            asm volatile("fence.proxy.async.global;" ::: "memory");
            if (lane == 0) TSX(11);
            {
                const int bbase = 8 * ti - 16, b0 = bbase < 0 ? 0 : bbase;
                const uint32_t bytes = (uint32_t)(8 * ti + 8 - b0) * 512;
#pragma unroll 1
                for (int m = 0; m < N_KV; m++) {
                    const uint32_t full = sb + B_FULL + 8 * r.slot, dst = sb + RING_OFF + r.slot * SLOT;
                    if (m == RING) {
                        mbar_wait(sb + B_XDEAD, 0);
                        if (leader) {
#pragma unroll
                            for (int e = 0; e < N_EXTRA; e++) {
                                mbar_expect_tx(sb + B_EFULL + 8 * e, 16384);
                                tma_3d(sb + X_OFF + (5 + e) * 16384, &map_w2, sb + B_EFULL + 8 * e, 0, 224 * tj + 64 * e, 0);
                                tma_3d(sb + X_OFF + (5 + e) * 16384 + 8192, &map_w2, sb + B_EFULL + 8 * e, 0, 224 * tj + 64 * e + 32, 0);
                            }
                        }
                    }
                    PWAIT();
                    if (leader) {
                        const uint4* src = ((m & 1) ? g_vf : g_kf) + ((tj * 4 + (m >> 1)) * 128 + b0) * 32;
                        mbar_expect_tx(full, bytes);
                        bulk_g2s(dst + (b0 - bbase) * 512, src, bytes, full);
                    }
                    r.next();
                }
            }
            {
                int q = 0, rr = 2 * N_EXTRA;
#pragma unroll 1
                for (int n = 0; n < N_FFN2; n++) {
                    const uint32_t full = sb + B_FULL + 8 * r.slot, dst = sb + RING_OFF + r.slot * SLOT;
                    PWAIT();
                    if (leader) mbar_expect_tx(full, 16384);
#pragma unroll
                    for (int h = 0; h < 2; h++) {
                        const bool isw2 = rr < 7;
                        const int row = isw2 ? 224 * tj + 32 * rr : 64 * tj + 32 * (rr - 7);
                        if (leader) tma_3d(dst + h * 8192, isw2 ? &map_w2 : &map_wo, full, 0, row, 2 * q);
                        if (++rr == 9) { rr = 0; q++; }
                    }
                    r.next();
                }
            }
        } else if (warp == 9) {
            unsigned epoch = 0;
            if (lane == 0) {
                epoch = atomicAdd(&g_ticket, 1u) >> 7;
                asm volatile("st.shared.u32 [%0], %1;" :: "r"(sb + EPOCH_OFF), "r"(epoch) : "memory");
                mbar_arrive(sb + B_EREADY);
                mbar_wait(sb + B_XFULL + 8 * PF1_AT, 0);
                prefetch_l2(w1p + (size_t)blockIdx.x * 14336, 14336);
                mbar_wait(sb + B_XFULL + 8 * PF2_AT, 0);
                prefetch_l2(w2p + (size_t)blockIdx.x * 14336, 14336);
                prefetch_l2(wop + (size_t)blockIdx.x * 4096, 4096);
                mbar_wait(sb + B_KVDONE, 0);
                red_release(&g_kvcnt[blockIdx.x * 32], 1u);
            }
            epoch = __shfl_sync(0xffffffffu, epoch, 0);
            asm volatile("barrier.cluster.wait.acquire.aligned;" ::: "memory");
            if (lane < 3 && ti - lane >= 0) wait_counter(&g_kvcnt[((ti - lane) * 8 + tj) * 32], epoch + 1);
            __syncwarp();
            if (lane == 0) mbar_arrive(sb + B_KVREADY);
            reduce_items(sb, out, ti, tj, (epoch + 1) & 1u, lane);
        } else {
            asm volatile("barrier.cluster.wait.acquire.aligned;" ::: "memory");
            mbar_wait(sb + B_EREADY, 0);
            unsigned epoch; asm volatile("ld.shared.u32 %0, [%1];" : "=r"(epoch) : "r"(sb + EPOCH_OFF) : "memory");
            reduce_items(sb, out, ti, tj, (epoch + 1) & 1u, lane);
            if (tid == 320) TSX(13);
        }
    } else {
        asm volatile("setmaxnreg.inc.sync.aligned.u32 224;");
        const int wg = warp >> 2, g = lane >> 2, c = lane & 3;
        const uint32_t xa = sb + X_OFF + wg * 8192;
        Ring r{0, 0};
        uint32_t qf[4][4];
        float g0, g1;
        TS(9);
        {
            float acc[100];
            int prev = 0;
            if (wg == 1) asm volatile("bar.sync 3, 256;" ::: "memory");
            for (int s = 0; s < N_QKV; s++) {
                if (!(s & 1)) mbar_wait(sb + B_XFULL + 8 * (s >> 1), 0);
                CWAIT();
                if (s == 0) TS(1);
                if (s == 2) TS(28);
                if (s == 6) TS(29);
                if (s == 10) TS(20);
                const uint32_t bs = sb + RING_OFF + r.slot * SLOT, as = xa + (s >> 1) * 16384 + (s & 1) * 64;
                wgmma_fence();
                wgmma_ss_n200(acc, desc_a(as), desc_b(bs), s);
                wgmma_ss_n200(acc, desc_a(as + 32), desc_b(bs + 2048), 1);
                wgmma_commit();
                if (wg == 0 && s == LEAD1) asm volatile("bar.arrive 3, 256;" ::: "memory");
                if (s > 0) { wgmma_wait<1>(); if (lane == 0) mbar_arrive(sb + B_EMPTY + 8 * prev); }
                prev = r.slot; r.next();
            }
            wgmma_wait<0>();
            fence_acc(acc);
            if (lane == 0) mbar_arrive(sb + B_EMPTY + 8 * prev);
            TS(2);
            const int blk = ti * 8 + warp;
#pragma unroll
            for (int hh = 0; hh < 4; hh++) {
                const float* t0 = &acc[8 * hh]; const float* t1 = &acc[8 * hh + 4];
                qf[hh][0] = pack_bf16(t0[0], t0[1]); qf[hh][1] = pack_bf16(t0[2], t0[3]);
                qf[hh][2] = pack_bf16(t1[0], t1[1]); qf[hh][3] = pack_bf16(t1[2], t1[3]);
                const float* k0 = &acc[32 + 8 * hh]; const float* k1 = &acc[32 + 8 * hh + 4];
                uint4 kv;
                kv.x = pack_bf16(k0[0], k0[1]); kv.y = pack_bf16(k1[0], k1[1]);
                kv.z = pack_bf16(k0[2], k0[3]); kv.w = pack_bf16(k1[2], k1[3]);
                g_kf[((tj * 4 + hh) * 128 + blk) * 32 + lane] = kv;
                const float* v0 = &acc[64 + 8 * hh]; const float* v1 = &acc[64 + 8 * hh + 4];
                uint4 vv;
                vv.x = movmatrix(pack_bf16(v0[0], v0[1])); vv.y = movmatrix(pack_bf16(v0[2], v0[3]));
                vv.z = movmatrix(pack_bf16(v1[0], v1[1])); vv.w = movmatrix(pack_bf16(v1[2], v1[3]));
                g_vf[((tj * 4 + hh) * 128 + blk) * 32 + lane] = vv;
            }
            __syncwarp();
            if (lane == 0) mbar_arrive(sb + B_KVDONE);
            const float z0 = __shfl_sync(0xffffffffu, acc[96], lane & ~3), z1 = __shfl_sync(0xffffffffu, acc[98], lane & ~3);
            g0 = 1.f / (1.f + __expf(-z0)); g1 = 1.f / (1.f + __expf(-z1));
        }
        TS(3);
        const int wrow = (warp & 3) * 16;
        {
            float acc[112];
            int prev = 0;
            for (int s = 0; s < N_FFN1; s++) {
                CWAIT();
                const uint32_t bs = sb + RING_OFF + r.slot * SLOT, as = xa + (s >> 1) * 16384 + (s & 1) * 64;
                wgmma_fence();
                wgmma_ss_n224(acc, desc_a(as), desc_b(bs), s);
                wgmma_ss_n224(acc, desc_a(as + 32), desc_b(bs + 2048), 1);
                wgmma_commit();
                if (s > 0) { wgmma_wait<1>(); if (lane == 0) mbar_arrive(sb + B_EMPTY + 8 * prev); }
                prev = r.slot; r.next();
            }
            wgmma_wait<0>();
            fence_acc(acc);
            if (lane == 0) mbar_arrive(sb + B_EMPTY + 8 * prev);
            TS(4);
            if (lane == 0) mbar_arrive(sb + B_XDEAD);
            const float s0 = 1.f - g0, s1 = 1.f - g1;
            asm volatile("bar.sync %0, 128;" :: "r"(1 + wg) : "memory");
            const uint32_t strow = xa + (wrow + ((lane >> 3) & 1) * 8 + (lane & 7)) * 128;
#pragma unroll
            for (int p = 0; p < 14; p++) {
                const int nt = 2 * p + (lane >> 4);
                const float* a = &acc[8 * p];
                stmatrix_x4(strow + (p >> 2) * 16384 + (((nt & 7) ^ (lane & 7)) << 4),
                            pack_bf16_relu(a[0] * s0, a[1] * s0), pack_bf16_relu(a[2] * s1, a[3] * s1),
                            pack_bf16_relu(a[4] * s0, a[5] * s0), pack_bf16_relu(a[6] * s1, a[7] * s1));
            }
        }
        TS(5);
        {
            const float SC = 0.25f * 1.4426950408889634f;
            const int gb0 = 8 * ti - 16 + warp;
            int slotK = 0, slotV = 0;
            const uint32_t ostore = xa + 4 * 16384 + (wrow + ((lane >> 3) & 1) * 8 + (lane & 7)) * 128;
#define NHEADS 4
#define ATT_KWAIT(kb) do { slotK = r.slot; CWAIT(); kb = sb + RING_OFF + slotK * SLOT + warp * 512 + lane * 16; r.next(); } while (0)
#define ATT_VWAIT(vb) do { slotV = r.slot; CWAIT(); vb = sb + RING_OFF + slotV * SLOT + warp * 512 + lane * 16; r.next(); TS(21 + hh); } while (0)
#define ATT_KREL() do { __syncwarp(); if (lane == 0) mbar_arrive(sb + B_EMPTY + 8 * slotK); } while (0)
#define ATT_VREL() do { __syncwarp(); if (lane == 0) mbar_arrive(sb + B_EMPTY + 8 * slotV); } while (0)
#define ATT_NEXTQ(h) do { \
                if ((h) == 1) { q0 = qf[1][0]; q1 = qf[1][1]; q2 = qf[1][2]; q3 = qf[1][3]; } \
                else if ((h) == 2) { q0 = qf[2][0]; q1 = qf[2][1]; q2 = qf[2][2]; q3 = qf[2][3]; } \
                else { q0 = qf[3][0]; q1 = qf[3][1]; q2 = qf[3][2]; q3 = qf[3][3]; } } while (0)
#define ATT_STORE(h, r0, r1, r2, r3) stmatrix_x4(ostore + (((2 * (h) + (lane >> 4)) ^ (lane & 7)) << 4), r0, r1, r2, r3)
            auto attention = [&](auto masked_tag) {
            constexpr bool MASKED = decltype(masked_tag)::value;
            const float NEG = -INFINITY;
            const uint32_t ONES = 0x3F803F80u;
            float sa[8][2][4], sb2[8][2][4];
            float o[2][4], ls[4];
            float m0, m1;
            uint32_t q0 = qf[0][0], q1 = qf[0][1], q2 = qf[0][2], q3 = qf[0][3];
            auto qk = [&](float (&s)[8][2][4], int ps, int t, uint32_t kbase) {
                if (ps == 0 && t == 0) {
                    const uint4 kd = lds128(kbase + 16 * 512);
                    const uint4 kf = lds128(kbase);
                    float f[2][4];
                    const float ci = (!MASKED || opaque(gb0) >= 0) ? 0.f : NEG;
                    mma16816_c(s[0][0], q0, q1, q2, q3, kd.x, kd.y, 0.f);
                    mma16816_c(s[0][1], q0, q1, q2, q3, kd.z, kd.w, 0.f);
                    mma16816_c(f[0], q0, q1, q2, q3, kf.x, kf.y, ci);
                    mma16816_c(f[1], q0, q1, q2, q3, kf.z, kf.w, ci);
#pragma unroll
                    for (int u = 0; u < 2; u++)
#pragma unroll
                        for (int e = 0; e < 4; e++) {
                            const int row = g + 8 * (e >> 1), col = 8 * u + 2 * c + (e & 1);
                            s[0][u][e] = (col > row) ? f[u][e] : s[0][u][e];
                        }
                } else {
                    const uint4 kf = lds128(kbase + (8 * ps + t) * 512);
                    const float ci = (!MASKED || opaque(gb0) + 8 * ps + t >= 0) ? 0.f : NEG;
                    mma16816_c(s[t][0], q0, q1, q2, q3, kf.x, kf.y, ci);
                    mma16816_c(s[t][1], q0, q1, q2, q3, kf.z, kf.w, ci);
                }
            };
            auto rowmax = [&](float (&s)[8][2][4], float b0, float b1, float& n0, float& n1) {
                int i0 = __float_as_int(b0), i1 = __float_as_int(b1);
#pragma unroll
                for (int t = 0; t < 8; t++)
#pragma unroll
                    for (int u = 0; u < 2; u++) {
                        i0 = __vimax3_s32(i0, __float_as_int(s[t][u][0]), __float_as_int(s[t][u][1]));
                        i1 = __vimax3_s32(i1, __float_as_int(s[t][u][2]), __float_as_int(s[t][u][3]));
                    }
                i0 = max(i0, __shfl_xor_sync(0xffffffffu, i0, 1)); i1 = max(i1, __shfl_xor_sync(0xffffffffu, i1, 1));
                i0 = max(i0, __shfl_xor_sync(0xffffffffu, i0, 2)); i1 = max(i1, __shfl_xor_sync(0xffffffffu, i1, 2));
                n0 = __int_as_float(i0); n1 = __int_as_float(i1);
                if (__any_sync(0xffffffffu, (i0 | i1) < 0)) {
                    asm volatile("" ::: "memory");
                    n0 = b0; n1 = b1;
#pragma unroll
                    for (int t = 0; t < 8; t++)
#pragma unroll
                        for (int u = 0; u < 2; u++) {
                            n0 = fmaxf(n0, fmaxf(s[t][u][0], s[t][u][1]));
                            n1 = fmaxf(n1, fmaxf(s[t][u][2], s[t][u][3]));
                        }
                    n0 = fmaxf(n0, __shfl_xor_sync(0xffffffffu, n0, 1)); n1 = fmaxf(n1, __shfl_xor_sync(0xffffffffu, n1, 1));
                    n0 = fmaxf(n0, __shfl_xor_sync(0xffffffffu, n0, 2)); n1 = fmaxf(n1, __shfl_xor_sync(0xffffffffu, n1, 2));
                }
            };
            auto pv = [&](const float (&p)[2][4], uint32_t vaddr) {
                const uint4 vf = lds128(vaddr);
                const uint32_t a0 = pack_bf16(p[0][0], p[0][1]), a1 = pack_bf16(p[0][2], p[0][3]);
                const uint32_t a2 = pack_bf16(p[1][0], p[1][1]), a3 = pack_bf16(p[1][2], p[1][3]);
                mma16816(o[0], a0, a1, a2, a3, vf.x, vf.y);
                mma16816(o[1], a0, a1, a2, a3, vf.z, vf.w);
                mma16816(ls, a0, a1, a2, a3, ONES, ONES);
            };
            auto expv = [&](float (&s)[8][2][4], int ps, int t, float mc0, float mc1, uint32_t vbase) {
                float p[2][4];
#pragma unroll
                for (int u = 0; u < 2; u++) {
                    p[u][0] = ex2(fmaf(s[t][u][0], SC, -mc0)); p[u][1] = ex2(fmaf(s[t][u][1], SC, -mc0));
                    p[u][2] = ex2(fmaf(s[t][u][2], SC, -mc1)); p[u][3] = ex2(fmaf(s[t][u][3], SC, -mc1));
                }
                if (ps == 0 && t == 0) {
                    float pd[2][4], pf[2][4];
#pragma unroll
                    for (int u = 0; u < 2; u++)
#pragma unroll
                        for (int e = 0; e < 4; e++) {
                            const int row = g + 8 * (e >> 1), col = 8 * u + 2 * c + (e & 1);
                            pf[u][e] = (col > row) ? p[u][e] : 0.f;
                            pd[u][e] = (col > row) ? 0.f : p[u][e];
                        }
                    pv(pd, vbase + 16 * 512);
                    pv(pf, vbase);
                } else {
                    pv(p, vbase + (8 * ps + t) * 512);
                }
            };
            uint32_t kbase, vbase;
            ATT_KWAIT(kbase);
#pragma unroll
            for (int t = 0; t < 8; t++) qk(sa, 0, t, kbase);
            rowmax(sa, NEG, NEG, m0, m1);
#pragma unroll 1
            for (int hh = 0; hh < NHEADS; hh++) {
                ATT_VWAIT(vbase);
#pragma unroll
                for (int e = 0; e < 4; e++) { o[0][e] = 0.f; o[1][e] = 0.f; ls[e] = 0.f; }
                {
                    const float mc0 = m0 * SC, mc1 = m1 * SC;
#pragma unroll
                    for (int t = 0; t < 8; t++) { qk(sb2, 1, t, kbase); expv(sa, 0, t, mc0, mc1, vbase); }
                    ATT_KREL();
                    float n0, n1;
                    rowmax(sb2, m0, m1, n0, n1);
                    const float a0 = ex2((m0 - n0) * SC), a1 = ex2((m1 - n1) * SC);
                    ls[0] *= a0; ls[2] *= a1;
                    o[0][0] *= a0; o[0][1] *= a0; o[1][0] *= a0; o[1][1] *= a0;
                    o[0][2] *= a1; o[0][3] *= a1; o[1][2] *= a1; o[1][3] *= a1;
                    m0 = n0; m1 = n1;
                }
                {
                    const float mc0 = m0 * SC, mc1 = m1 * SC;
                    const bool more = hh + 1 < NHEADS;
                    if (more) {
                        ATT_KWAIT(kbase);
                        ATT_NEXTQ(hh + 1);
#pragma unroll
                        for (int t = 0; t < 8; t++) { qk(sa, 0, t, kbase); expv(sb2, 1, t, mc0, mc1, vbase); }
                        rowmax(sa, NEG, NEG, m0, m1);
                    } else {
#pragma unroll
                        for (int t = 0; t < 8; t++) expv(sb2, 1, t, mc0, mc1, vbase);
                    }
                    ATT_VREL();
                }
                const float f0 = __fdividef(g0, ls[0]), f1 = __fdividef(g1, ls[2]);
                ATT_STORE(hh, pack_bf16(o[0][0] * f0, o[0][1] * f0), pack_bf16(o[0][2] * f1, o[0][3] * f1),
                              pack_bf16(o[1][0] * f0, o[1][1] * f0), pack_bf16(o[1][2] * f1, o[1][3] * f1));
            }
            };
            if (ti >= 2) attention(BoolTag<false>{}); else attention(BoolTag<true>{});
        }
        fence_async_smem();
        asm volatile("bar.sync 4, 256;" ::: "memory");
        TS(6);
        {
            float accA[64], accB[64];
            mbar_wait(sb + B_EREADY, 0);
            uint32_t tag; asm volatile("ld.shared.u32 %0, [%1];" : "=r"(tag) : "r"(sb + EPOCH_OFF) : "memory");
            tag = (tag + 1) & 1u;
            asm volatile("barrier.cluster.wait.acquire.aligned;" ::: "memory");
            const uint32_t rank = tj & 1, peer = rank ^ 1;
            const bool keeper = (uint32_t)(warp & 1) == rank;
            const uint32_t stg = STG_OFF + (warp >> 1) * 4096 + lane * 16;
            uint4* pdst = part_ptr(ti, warp, 0, 0, lane) + (tj >> 1) * 256;
            auto send = [&](float (&acc)[64], int q) {
                if (keeper) return;
                fence_acc(acc);
                const uint32_t rdst = mapa(sb + stg + (q & 1) * 16384, peer), rbar = mapa(sb + B_SFULL + ((q & 1) * 4 + (warp >> 1)) * 8, peer);
                mbar_wait(sb + B_SFREE + 8 * (q & 1), q >> 1);
#pragma unroll
                for (int t2 = 0; t2 < 8; t2++) {
                    uint4 v;
                    v.x = pack_bf16(acc[8 * t2 + 0], acc[8 * t2 + 1]); v.y = pack_bf16(acc[8 * t2 + 2], acc[8 * t2 + 3]);
                    v.z = pack_bf16(acc[8 * t2 + 4], acc[8 * t2 + 5]); v.w = pack_bf16(acc[8 * t2 + 6], acc[8 * t2 + 7]);
                    st_async_v4(rdst + t2 * 512, v, rbar);
                }
                __syncwarp();
                if (lane == 0) mbar_arrive(sb + B_PDONE + 8 * q);
            };
            auto keep = [&](float (&acc)[64], int q) {
                if (!keeper) return;
                fence_acc(acc);
                const uint32_t fbar = sb + B_SFULL + ((q & 1) * 4 + (warp >> 1)) * 8;
                if (lane == 0) mbar_expect_tx(fbar, 4096);
                mbar_wait_cluster(fbar, q >> 1);
                uint4* p = pdst + (size_t)q * 4 * 256;
#pragma unroll
                for (int t2 = 0; t2 < 8; t2++) {
                    const uint4 o = lds128(sb + stg + (q & 1) * 16384 + t2 * 512);
                    uint4 v;
                    v.x = pack_bf16(acc[8 * t2 + 0] + bf_lo(o.x), acc[8 * t2 + 1] + bf_hi(o.x));
                    v.y = pack_bf16(acc[8 * t2 + 2] + bf_lo(o.y), acc[8 * t2 + 3] + bf_hi(o.y));
                    v.z = pack_bf16(acc[8 * t2 + 4] + bf_lo(o.z), acc[8 * t2 + 5] + bf_hi(o.z));
                    v.w = pack_bf16(acc[8 * t2 + 6] + bf_lo(o.w), acc[8 * t2 + 7] + bf_hi(o.w));
                    stg_relaxed(p + t2 * 32, make_uint4((v.x & ~1u) | tag, (v.y & ~1u) | tag, (v.z & ~1u) | tag, (v.w & ~1u) | tag));
                }
                __syncwarp();
                if (lane == 0) {
                    if (q < 2) mbar_arrive_remote(mapa(sb + B_SFREE + 8 * (q & 1), peer));
                    mbar_arrive(sb + B_PDONE + 8 * q);
                }
            };
            int rel = r.slot;
            if (wg == 1) asm volatile("bar.sync 3, 256;" ::: "memory");
#pragma unroll
            for (int half = 0; half < 2; half++) {
#pragma unroll
                for (int m = 0; m < 9; m++) {
                    const bool ext = (m < N_EXTRA) && (half == 0);
                    const uint32_t bslot = ext ? sb + X_OFF + (5 + m) * 16384 : sb + RING_OFF + r.slot * SLOT;
                    if (ext) mbar_wait(sb + B_EFULL + 8 * m, 0); else CWAIT();
                    wgmma_fence();
#pragma unroll
                    for (int h = 0; h < 2; h++) {
                        const int u = 2 * m + h, rr = u % 9;
                        const uint32_t bs = bslot + h * 8192;
                        const int vk = rr < 7 ? 32 * rr : 256 + 32 * (rr - 7);
                        const uint32_t as = xa + (vk >> 6) * 16384 + (vk & 63) * 2;
                        if (u < 9) {
                            wgmma_ss_n128(accA, desc_a(as), desc_b(bs), rr);
                            wgmma_ss_n128(accA, desc_a(as + 32), desc_b(bs + 2048), 1);
                        } else {
                            wgmma_ss_n128(accB, desc_a(as), desc_b(bs), rr);
                            wgmma_ss_n128(accB, desc_a(as + 32), desc_b(bs + 2048), 1);
                        }
                    }
                    wgmma_commit();
                    if (m == LEAD2 && half == 0 && wg == 0) asm volatile("bar.arrive 3, 256;" ::: "memory");
                    if (!ext) r.next();
                    wgmma_wait<1>();
                    if (m > N_EXTRA || half > 0) {
                        if (lane == 0) mbar_arrive(sb + B_EMPTY + 8 * rel);
                        if (++rel == RING) rel = 0;
                    }
                    if (half == 0 && m == 2 && lane == 0) mbar_arrive(sb + B_ECONS);
                    if (half == 0 && m == 4 && keeper) {
                        mbar_wait(sb + B_ECONS, 0);
                        if (lane == 0) { mbar_arrive_remote(mapa(sb + B_SFREE, peer)); mbar_arrive_remote(mapa(sb + B_SFREE + 8, peer)); }
                    }
                    if (m == 5) { TS(25 + 2 * half); send(accA, 2 * half); }
                    if (m == 7) keep(accA, 2 * half);
                    if (m == 0 && half == 1) { TS(26); send(accB, 1); }
                    if (m == 2 && half == 1) keep(accB, 1);
                }
            }
            wgmma_wait<0>();
            TS(7);
            send(accB, 3);
            keep(accB, 3);
            TS(19);
            reduce_items(sb, out, ti, tj, tag, lane);
            if (tid == 0) TSG(30);
        }
        TS(8);
    }
}

typedef CUresult (*PFN_encodeTiled)(CUtensorMap*, CUtensorMapDataType, cuuint32_t, void*, const cuuint64_t*, const cuuint64_t*,
                                    const cuuint32_t*, const cuuint32_t*, CUtensorMapInterleave, CUtensorMapSwizzle,
                                    CUtensorMapL2promotion, CUtensorMapFloatOOBfill);

void make_map(PFN_encodeTiled enc, CUtensorMap* m, const void* base, int rank, const cuuint64_t* dims, const cuuint64_t* strides, const cuuint32_t* box) {
    cuuint32_t es[5] = {1, 1, 1, 1, 1};
    enc(m, CU_TENSOR_MAP_DATA_TYPE_BFLOAT16, (cuuint32_t)rank, const_cast<void*>(base), dims, strides, box, es,
        CU_TENSOR_MAP_INTERLEAVE_NONE, CU_TENSOR_MAP_SWIZZLE_128B, CU_TENSOR_MAP_L2_PROMOTION_L2_256B, CU_TENSOR_MAP_FLOAT_OOB_FILL_NONE);
}

}

extern "C" void kernel_launch(void* const* d_in, const int* in_sizes, int n_in, void* d_out, int out_size) {
    (void)in_sizes; (void)n_in; (void)out_size;
    const void* x = d_in[0]; const void* wqkv = d_in[1]; const void* wo = d_in[2];
    const void* w1 = d_in[4]; const void* w2 = d_in[5]; const void* gate_w = d_in[6];
    static PFN_encodeTiled enc = nullptr;
    if (!enc) {
        void* fn = nullptr; cudaDriverEntryPointQueryResult st;
        cudaGetDriverEntryPoint("cuTensorMapEncodeTiled", &fn, cudaEnableDefault, &st);
        enc = (PFN_encodeTiled)fn;
        cudaFuncSetAttribute(fused_kernel, cudaFuncAttributeMaxDynamicSharedMemorySize, SMEM_BYTES);
    }
    CUtensorMap mx, mqkv, mw1, mw2, mwo, mw1a;
    { cuuint64_t d[4] = {64, 512, 3, 8}, s[3] = {3584, 128, 448}; cuuint32_t b[4] = {64, 32, 3, 1}; make_map(enc, &mw1a, w1, 4, d, s, b); }
    { cuuint64_t d[2] = {512, 2048}, s[1] = {1024}; cuuint32_t b[2] = {64, 128}; make_map(enc, &mx, x, 2, d, s, b); }
    { cuuint64_t d[4] = {64, 512, 8, 3}, s[3] = {3072, 128, 1024}; cuuint32_t b[4] = {64, 32, 1, 3}; make_map(enc, &mqkv, wqkv, 4, d, s, b); }
    { cuuint64_t d[2] = {1792, 512}, s[1] = {3584}; cuuint32_t b[2] = {64, 32}; make_map(enc, &mw1, w1, 2, d, s, b); }
    { cuuint64_t d[3] = {64, 1792, 8}, s[2] = {1024, 128}; cuuint32_t b[3] = {64, 32, 2}; make_map(enc, &mw2, w2, 3, d, s, b); }
    { cuuint64_t d[3] = {64, 512, 8}, s[2] = {1024, 128}; cuuint32_t b[3] = {64, 32, 2}; make_map(enc, &mwo, wo, 3, d, s, b); }
    cudaLaunchConfig_t cfg = {};
    cfg.gridDim = dim3(128); cfg.blockDim = dim3(384); cfg.dynamicSmemBytes = SMEM_BYTES; cfg.stream = cudaStreamPerThread;
    cudaLaunchAttribute at[1];
    at[0].id = cudaLaunchAttributeClusterDimension; at[0].val.clusterDim.x = 2; at[0].val.clusterDim.y = 1; at[0].val.clusterDim.z = 1;
    cfg.attrs = at; cfg.numAttrs = 1;
    cudaLaunchKernelEx(&cfg, fused_kernel, mx, mqkv, mw1, mw2, mwo, mw1a, (const __nv_bfloat16*)gate_w, (__nv_bfloat16*)d_out,
                       (const uint8_t*)w1, (const uint8_t*)w2, (const uint8_t*)wo, (const uint8_t*)x, (const uint8_t*)wqkv);
}
```

```cpp
#include <cuda_runtime.h>
#include <cuda_bf16.h>
#include <cuda.h>
#include <stdint.h>

namespace {

#define PF1_AT 1
#define PF2_AT 5
#define LEAD1 2
constexpr int RING = 6;
constexpr int SLOT = 16384;
constexpr uint32_t X_OFF = 0;
constexpr uint32_t STG_OFF = X_OFF + 4 * 16384;
constexpr uint32_t RING_OFF = 131072;
constexpr uint32_t BAR_OFF = RING_OFF + RING * SLOT;
constexpr uint32_t B_FULL = BAR_OFF, B_EMPTY = BAR_OFF + 64, B_XFULL = BAR_OFF + 128, B_HDEAD = BAR_OFF + 192,
                   B_EREADY = BAR_OFF + 200, B_KVDONE = BAR_OFF + 208, B_ODONE = BAR_OFF + 224,
                   B_KVREADY = BAR_OFF + 232, B_WOFULL = BAR_OFF + 240, B_HSUM = BAR_OFF + 248, B_PREADY = BAR_OFF + 264,
                   B_SQ = BAR_OFF + 272, B_SF = BAR_OFF + 304;
constexpr uint32_t EPOCH_OFF = BAR_OFF + 256, ITEM_OFF = BAR_OFF + 260;
constexpr uint32_t SMEM_BYTES = BAR_OFF + 1024;

constexpr int N_QKV = 16, N_FFN1 = 16, N_FFN2 = 14, N_KV = 8, N_O = 8;

__device__ uint4 g_kf[32 * 128 * 32];
__device__ uint4 g_vf[32 * 128 * 32];
__device__ uint4 g_part[16 * 8 * 8 * 8 * 4 * 32];
__device__ __nv_bfloat16 g_o[2048 * 512];
__device__ unsigned g_ticket;
__device__ unsigned g_kvcnt[128 * 32];
__device__ unsigned g_pcnt[128 * 32];
__device__ unsigned g_ocnt[128 * 32];
#define TS(k) do {} while (0)
#define TS2(k) do {} while (0)
#define TS2X(k) do {} while (0)
#define TSX(k) do {} while (0)
#define TSG(k) do {} while (0)

__device__ __forceinline__ uint32_t smem_u32(const void* p) { return (uint32_t)__cvta_generic_to_shared(p); }
__device__ __forceinline__ void mbar_init(uint32_t bar, uint32_t cnt) { asm volatile("mbarrier.init.shared::cta.b64 [%0], %1;" :: "r"(bar), "r"(cnt) : "memory"); }
__device__ __forceinline__ void mbar_expect_tx(uint32_t bar, uint32_t bytes) { asm volatile("mbarrier.arrive.expect_tx.shared::cta.b64 _, [%0], %1;" :: "r"(bar), "r"(bytes) : "memory"); }
__device__ __forceinline__ void mbar_expect_only(uint32_t bar, uint32_t bytes) { asm volatile("mbarrier.expect_tx.relaxed.cta.shared::cta.b64 [%0], %1;" :: "r"(bar), "r"(bytes) : "memory"); }
__device__ __forceinline__ void mbar_arrive(uint32_t bar) { asm volatile("mbarrier.arrive.shared::cta.b64 _, [%0];" :: "r"(bar) : "memory"); }
__device__ __forceinline__ void mbar_wait(uint32_t bar, uint32_t parity) {
    asm volatile("{\n.reg .pred P1, P2;\n.reg .u32 n;\nmov.u32 n, 0;\n"
                 "WAIT_LOOP:\n"
                 "mbarrier.try_wait.parity.shared::cta.b64 P1, [%0], %1;\n"
                 "@P1 bra WAIT_DONE;\n"
                 "add.u32 n, n, 1;\n"
                 "setp.lt.u32 P2, n, 0x400000;\n"
                 "@P2 bra WAIT_LOOP;\n"
                 "WAIT_DONE:\n}" :: "r"(bar), "r"(parity) : "memory");
}
__device__ __forceinline__ void tma_2d(uint32_t dst, const void* map, uint32_t bar, int c0, int c1) {
    asm volatile("cp.async.bulk.tensor.2d.shared::cluster.global.mbarrier::complete_tx::bytes [%0], [%1, {%3, %4}], [%2];"
        :: "r"(dst), "l"(map), "r"(bar), "r"(c0), "r"(c1) : "memory");
}
__device__ __forceinline__ void tma_3d(uint32_t dst, const void* map, uint32_t bar, int c0, int c1, int c2) {
    asm volatile("cp.async.bulk.tensor.3d.shared::cluster.global.mbarrier::complete_tx::bytes [%0], [%1, {%3, %4, %5}], [%2];"
        :: "r"(dst), "l"(map), "r"(bar), "r"(c0), "r"(c1), "r"(c2) : "memory");
}
__device__ __forceinline__ void tma_4d(uint32_t dst, const void* map, uint32_t bar, int c0, int c1, int c2, int c3) {
    asm volatile("cp.async.bulk.tensor.4d.shared::cluster.global.mbarrier::complete_tx::bytes [%0], [%1, {%3, %4, %5, %6}], [%2];"
        :: "r"(dst), "l"(map), "r"(bar), "r"(c0), "r"(c1), "r"(c2), "r"(c3) : "memory");
}
__device__ __forceinline__ void bulk_g2s(uint32_t dst, const void* src, uint32_t bytes, uint32_t bar) {
    asm volatile("cp.async.bulk.shared::cluster.global.mbarrier::complete_tx::bytes [%0], [%1], %2, [%3];"
        :: "r"(dst), "l"(src), "r"(bytes), "r"(bar) : "memory");
}
__device__ __forceinline__ void prefetch_l2(const void* src, uint32_t bytes) {
    asm volatile("cp.async.bulk.prefetch.L2.global [%0], %1;" :: "l"(src), "r"(bytes) : "memory");
}
__device__ __forceinline__ bool elect_one() {
    uint32_t p;
    asm volatile("{\n.reg .pred P;\nelect.sync _|P, 0xffffffff;\nselp.u32 %0, 1, 0, P;\n}" : "=r"(p));
    return p != 0;
}
__device__ __forceinline__ void wgmma_fence() { asm volatile("wgmma.fence.sync.aligned;" ::: "memory"); }
__device__ __forceinline__ void wgmma_commit() { asm volatile("wgmma.commit_group.sync.aligned;" ::: "memory"); }
template <int N> __device__ __forceinline__ void wgmma_wait() { asm volatile("wgmma.wait_group.sync.aligned %0;" :: "n"(N) : "memory"); }
__device__ __forceinline__ void fence_async_smem() { asm volatile("fence.proxy.async.shared::cta;" ::: "memory"); }
__device__ __forceinline__ uint64_t desc_a(uint32_t addr) {
    return (uint64_t)((addr & 0x3FFFF) >> 4) | ((uint64_t)1 << 16) | ((uint64_t)(1024 >> 4) << 32) | ((uint64_t)1 << 62);
}
__device__ __forceinline__ uint64_t desc_b(uint32_t addr) {
    return (uint64_t)((addr & 0x3FFFF) >> 4) | ((uint64_t)(4096 >> 4) << 16) | ((uint64_t)(1024 >> 4) << 32) | ((uint64_t)1 << 62);
}
__device__ __forceinline__ uint32_t pack_bf16(float lo, float hi) {
    uint32_t r; asm("cvt.rn.bf16x2.f32 %0, %1, %2;" : "=r"(r) : "f"(hi), "f"(lo)); return r;
}
__device__ __forceinline__ uint32_t pack_bf16_relu(float lo, float hi) {
    uint32_t r; asm("cvt.rn.relu.bf16x2.f32 %0, %1, %2;" : "=r"(r) : "f"(hi), "f"(lo)); return r;
}
__device__ __forceinline__ uint32_t movmatrix(uint32_t a) {
    uint32_t d; asm volatile("movmatrix.sync.aligned.m8n8.trans.b16 %0, %1;" : "=r"(d) : "r"(a)); return d;
}
__device__ __forceinline__ void stmatrix_x4(uint32_t addr, uint32_t r0, uint32_t r1, uint32_t r2, uint32_t r3) {
    asm volatile("stmatrix.sync.aligned.m8n8.x4.shared.b16 [%0], {%1, %2, %3, %4};" :: "r"(addr), "r"(r0), "r"(r1), "r"(r2), "r"(r3) : "memory");
}
__device__ __forceinline__ uint4 lds128(uint32_t addr) {
    uint4 v; asm volatile("ld.shared.v4.b32 {%0, %1, %2, %3}, [%4];" : "=r"(v.x), "=r"(v.y), "=r"(v.z), "=r"(v.w) : "r"(addr) : "memory"); return v;
}
__device__ __forceinline__ void mma16816(float (&c)[4], uint32_t a0, uint32_t a1, uint32_t a2, uint32_t a3, uint32_t b0, uint32_t b1) {
    asm volatile("mma.sync.aligned.m16n8k16.row.col.f32.bf16.bf16.f32 {%0,%1,%2,%3}, {%4,%5,%6,%7}, {%8,%9}, {%0,%1,%2,%3};"
        : "+f"(c[0]), "+f"(c[1]), "+f"(c[2]), "+f"(c[3]) : "r"(a0), "r"(a1), "r"(a2), "r"(a3), "r"(b0), "r"(b1));
}
__device__ __forceinline__ void mma16816_c(float (&c)[4], uint32_t a0, uint32_t a1, uint32_t a2, uint32_t a3, uint32_t b0, uint32_t b1, float ci) {
    asm volatile("mma.sync.aligned.m16n8k16.row.col.f32.bf16.bf16.f32 {%0,%1,%2,%3}, {%4,%5,%6,%7}, {%8,%9}, {%10,%10,%10,%10};"
        : "=f"(c[0]), "=f"(c[1]), "=f"(c[2]), "=f"(c[3]) : "r"(a0), "r"(a1), "r"(a2), "r"(a3), "r"(b0), "r"(b1), "f"(ci));
}
__device__ __forceinline__ int opaque(int v) { asm volatile("" : "+r"(v)); return v; }
__device__ __forceinline__ float ex2(float x) { float y; asm("ex2.approx.ftz.f32 %0, %1;" : "=f"(y) : "f"(x)); return y; }
__device__ __forceinline__ unsigned ld_acquire(const unsigned* p) {
    unsigned v; asm volatile("ld.acquire.gpu.global.u32 %0, [%1];" : "=r"(v) : "l"(p) : "memory"); return v;
}
__device__ __forceinline__ void red_release(unsigned* p, unsigned v) {
    asm volatile("red.release.gpu.global.add.u32 [%0], %1;" :: "l"(p), "r"(v) : "memory");
}
__device__ __forceinline__ void wait_counter(const unsigned* p, unsigned target) {
    uint32_t n = 0;
    while ((int)(ld_acquire(p) - target) < 0) { if (++n > (1u << 20)) break; }
}
__device__ __forceinline__ uint4 ldg_weak(const uint4* p) {
    uint4 v; asm volatile("ld.global.L1::no_allocate.v4.b32 {%0, %1, %2, %3}, [%4];" : "=r"(v.x), "=r"(v.y), "=r"(v.z), "=r"(v.w) : "l"(p) : "memory"); return v;
}
__device__ __forceinline__ float bf_lo(uint32_t v) { return __uint_as_float(v << 16); }
__device__ __forceinline__ float bf_hi(uint32_t v) { return __uint_as_float(v & 0xFFFF0000u); }

__device__ __forceinline__ void wgmma_ss_n64(float (&d)[32], uint64_t da, uint64_t db, int scale_d) {
    asm volatile("{\n.reg .pred p;\nsetp.ne.b32 p, %34, 0;\n"
        "wgmma.mma_async.sync.aligned.m64n64k16.f32.bf16.bf16 {%0, %1, %2, %3, %4, %5, %6, %7, %8, %9, %10, %11, %12, %13, %14, %15, %16, %17, %18, %19, %20, %21, %22, %23, %24, %25, %26, %27, %28, %29, %30, %31}, %32, %33, p, 1, 1, 0, 1;\n}\n"
        : "+f"(d[0]), "+f"(d[1]), "+f"(d[2]), "+f"(d[3]), "+f"(d[4]), "+f"(d[5]), "+f"(d[6]), "+f"(d[7]), "+f"(d[8]), "+f"(d[9]), "+f"(d[10]), "+f"(d[11]), "+f"(d[12]), "+f"(d[13]), "+f"(d[14]), "+f"(d[15]), "+f"(d[16]), "+f"(d[17]), "+f"(d[18]), "+f"(d[19]), "+f"(d[20]), "+f"(d[21]), "+f"(d[22]), "+f"(d[23]), "+f"(d[24]), "+f"(d[25]), "+f"(d[26]), "+f"(d[27]), "+f"(d[28]), "+f"(d[29]), "+f"(d[30]), "+f"(d[31])
        : "l"(da), "l"(db), "r"(scale_d));
}
__device__ __forceinline__ void wgmma_ss_n128(float (&d)[64], uint64_t da, uint64_t db, int scale_d) {
    asm volatile("{\n.reg .pred p;\nsetp.ne.b32 p, %66, 0;\n"
        "wgmma.mma_async.sync.aligned.m64n128k16.f32.bf16.bf16 {%0, %1, %2, %3, %4, %5, %6, %7, %8, %9, %10, %11, %12, %13, %14, %15, %16, %17, %18, %19, %20, %21, %22, %23, %24, %25, %26, %27, %28, %29, %30, %31, %32, %33, %34, %35, %36, %37, %38, %39, %40, %41, %42, %43, %44, %45, %46, %47, %48, %49, %50, %51, %52, %53, %54, %55, %56, %57, %58, %59, %60, %61, %62, %63}, %64, %65, p, 1, 1, 0, 1;\n}\n"
        : "+f"(d[0]), "+f"(d[1]), "+f"(d[2]), "+f"(d[3]), "+f"(d[4]), "+f"(d[5]), "+f"(d[6]), "+f"(d[7]), "+f"(d[8]), "+f"(d[9]), "+f"(d[10]), "+f"(d[11]), "+f"(d[12]), "+f"(d[13]), "+f"(d[14]), "+f"(d[15]), "+f"(d[16]), "+f"(d[17]), "+f"(d[18]), "+f"(d[19]), "+f"(d[20]), "+f"(d[21]), "+f"(d[22]), "+f"(d[23]), "+f"(d[24]), "+f"(d[25]), "+f"(d[26]), "+f"(d[27]), "+f"(d[28]), "+f"(d[29]), "+f"(d[30]), "+f"(d[31]), "+f"(d[32]), "+f"(d[33]), "+f"(d[34]), "+f"(d[35]), "+f"(d[36]), "+f"(d[37]), "+f"(d[38]), "+f"(d[39]), "+f"(d[40]), "+f"(d[41]), "+f"(d[42]), "+f"(d[43]), "+f"(d[44]), "+f"(d[45]), "+f"(d[46]), "+f"(d[47]), "+f"(d[48]), "+f"(d[49]), "+f"(d[50]), "+f"(d[51]), "+f"(d[52]), "+f"(d[53]), "+f"(d[54]), "+f"(d[55]), "+f"(d[56]), "+f"(d[57]), "+f"(d[58]), "+f"(d[59]), "+f"(d[60]), "+f"(d[61]), "+f"(d[62]), "+f"(d[63])
        : "l"(da), "l"(db), "r"(scale_d));
}
__device__ __forceinline__ void wgmma_ss_n200(float (&d)[100], uint64_t da, uint64_t db, int scale_d) {
    asm volatile("{\n.reg .pred p;\nsetp.ne.b32 p, %102, 0;\n"
        "wgmma.mma_async.sync.aligned.m64n200k16.f32.bf16.bf16 {%0, %1, %2, %3, %4, %5, %6, %7, %8, %9, %10, %11, %12, %13, %14, %15, %16, %17, %18, %19, %20, %21, %22, %23, %24, %25, %26, %27, %28, %29, %30, %31, %32, %33, %34, %35, %36, %37, %38, %39, %40, %41, %42, %43, %44, %45, %46, %47, %48, %49, %50, %51, %52, %53, %54, %55, %56, %57, %58, %59, %60, %61, %62, %63, %64, %65, %66, %67, %68, %69, %70, %71, %72, %73, %74, %75, %76, %77, %78, %79, %80, %81, %82, %83, %84, %85, %86, %87, %88, %89, %90, %91, %92, %93, %94, %95, %96, %97, %98, %99}, %100, %101, p, 1, 1, 0, 1;\n}\n"
        : "+f"(d[0]), "+f"(d[1]), "+f"(d[2]), "+f"(d[3]), "+f"(d[4]), "+f"(d[5]), "+f"(d[6]), "+f"(d[7]), "+f"(d[8]), "+f"(d[9]), "+f"(d[10]), "+f"(d[11]), "+f"(d[12]), "+f"(d[13]), "+f"(d[14]), "+f"(d[15]), "+f"(d[16]), "+f"(d[17]), "+f"(d[18]), "+f"(d[19]), "+f"(d[20]), "+f"(d[21]), "+f"(d[22]), "+f"(d[23]), "+f"(d[24]), "+f"(d[25]), "+f"(d[26]), "+f"(d[27]), "+f"(d[28]), "+f"(d[29]), "+f"(d[30]), "+f"(d[31]), "+f"(d[32]), "+f"(d[33]), "+f"(d[34]), "+f"(d[35]), "+f"(d[36]), "+f"(d[37]), "+f"(d[38]), "+f"(d[39]), "+f"(d[40]), "+f"(d[41]), "+f"(d[42]), "+f"(d[43]), "+f"(d[44]), "+f"(d[45]), "+f"(d[46]), "+f"(d[47]), "+f"(d[48]), "+f"(d[49]), "+f"(d[50]), "+f"(d[51]), "+f"(d[52]), "+f"(d[53]), "+f"(d[54]), "+f"(d[55]), "+f"(d[56]), "+f"(d[57]), "+f"(d[58]), "+f"(d[59]), "+f"(d[60]), "+f"(d[61]), "+f"(d[62]), "+f"(d[63]), "+f"(d[64]), "+f"(d[65]), "+f"(d[66]), "+f"(d[67]), "+f"(d[68]), "+f"(d[69]), "+f"(d[70]), "+f"(d[71]), "+f"(d[72]), "+f"(d[73]), "+f"(d[74]), "+f"(d[75]), "+f"(d[76]), "+f"(d[77]), "+f"(d[78]), "+f"(d[79]), "+f"(d[80]), "+f"(d[81]), "+f"(d[82]), "+f"(d[83]), "+f"(d[84]), "+f"(d[85]), "+f"(d[86]), "+f"(d[87]), "+f"(d[88]), "+f"(d[89]), "+f"(d[90]), "+f"(d[91]), "+f"(d[92]), "+f"(d[93]), "+f"(d[94]), "+f"(d[95]), "+f"(d[96]), "+f"(d[97]), "+f"(d[98]), "+f"(d[99])
        : "l"(da), "l"(db), "r"(scale_d));
}
__device__ __forceinline__ void wgmma_ss_n224(float (&d)[112], uint64_t da, uint64_t db, int scale_d) {
    asm volatile("{\n.reg .pred p;\nsetp.ne.b32 p, %114, 0;\n"
        "wgmma.mma_async.sync.aligned.m64n224k16.f32.bf16.bf16 {%0, %1, %2, %3, %4, %5, %6, %7, %8, %9, %10, %11, %12, %13, %14, %15, %16, %17, %18, %19, %20, %21, %22, %23, %24, %25, %26, %27, %28, %29, %30, %31, %32, %33, %34, %35, %36, %37, %38, %39, %40, %41, %42, %43, %44, %45, %46, %47, %48, %49, %50, %51, %52, %53, %54, %55, %56, %57, %58, %59, %60, %61, %62, %63, %64, %65, %66, %67, %68, %69, %70, %71, %72, %73, %74, %75, %76, %77, %78, %79, %80, %81, %82, %83, %84, %85, %86, %87, %88, %89, %90, %91, %92, %93, %94, %95, %96, %97, %98, %99, %100, %101, %102, %103, %104, %105, %106, %107, %108, %109, %110, %111}, %112, %113, p, 1, 1, 0, 1;\n}\n"
        : "+f"(d[0]), "+f"(d[1]), "+f"(d[2]), "+f"(d[3]), "+f"(d[4]), "+f"(d[5]), "+f"(d[6]), "+f"(d[7]), "+f"(d[8]), "+f"(d[9]), "+f"(d[10]), "+f"(d[11]), "+f"(d[12]), "+f"(d[13]), "+f"(d[14]), "+f"(d[15]), "+f"(d[16]), "+f"(d[17]), "+f"(d[18]), "+f"(d[19]), "+f"(d[20]), "+f"(d[21]), "+f"(d[22]), "+f"(d[23]), "+f"(d[24]), "+f"(d[25]), "+f"(d[26]), "+f"(d[27]), "+f"(d[28]), "+f"(d[29]), "+f"(d[30]), "+f"(d[31]), "+f"(d[32]), "+f"(d[33]), "+f"(d[34]), "+f"(d[35]), "+f"(d[36]), "+f"(d[37]), "+f"(d[38]), "+f"(d[39]), "+f"(d[40]), "+f"(d[41]), "+f"(d[42]), "+f"(d[43]), "+f"(d[44]), "+f"(d[45]), "+f"(d[46]), "+f"(d[47]), "+f"(d[48]), "+f"(d[49]), "+f"(d[50]), "+f"(d[51]), "+f"(d[52]), "+f"(d[53]), "+f"(d[54]), "+f"(d[55]), "+f"(d[56]), "+f"(d[57]), "+f"(d[58]), "+f"(d[59]), "+f"(d[60]), "+f"(d[61]), "+f"(d[62]), "+f"(d[63]), "+f"(d[64]), "+f"(d[65]), "+f"(d[66]), "+f"(d[67]), "+f"(d[68]), "+f"(d[69]), "+f"(d[70]), "+f"(d[71]), "+f"(d[72]), "+f"(d[73]), "+f"(d[74]), "+f"(d[75]), "+f"(d[76]), "+f"(d[77]), "+f"(d[78]), "+f"(d[79]), "+f"(d[80]), "+f"(d[81]), "+f"(d[82]), "+f"(d[83]), "+f"(d[84]), "+f"(d[85]), "+f"(d[86]), "+f"(d[87]), "+f"(d[88]), "+f"(d[89]), "+f"(d[90]), "+f"(d[91]), "+f"(d[92]), "+f"(d[93]), "+f"(d[94]), "+f"(d[95]), "+f"(d[96]), "+f"(d[97]), "+f"(d[98]), "+f"(d[99]), "+f"(d[100]), "+f"(d[101]), "+f"(d[102]), "+f"(d[103]), "+f"(d[104]), "+f"(d[105]), "+f"(d[106]), "+f"(d[107]), "+f"(d[108]), "+f"(d[109]), "+f"(d[110]), "+f"(d[111])
        : "l"(da), "l"(db), "r"(scale_d));
}
template <int N> __device__ __forceinline__ void fence_acc(float (&d)[N]) {
#pragma unroll
    for (int i = 0; i < N; i++) asm volatile("" : "+f"(d[i]) :: "memory");
}

__device__ __forceinline__ void bulk_s2g(void* dst, uint32_t src, uint32_t bytes) {
    asm volatile("cp.async.bulk.global.shared::cta.bulk_group [%0], [%1], %2;" :: "l"(dst), "r"(src), "r"(bytes) : "memory");
}
__device__ __forceinline__ void sts128(uint32_t addr, uint4 v) {
    asm volatile("st.shared.v4.b32 [%0], {%1, %2, %3, %4};" :: "r"(addr), "r"(v.x), "r"(v.y), "r"(v.z), "r"(v.w) : "memory");
}
__device__ __forceinline__ void sum_partials(uint32_t sb, int ti, int tj, int lane) {
    for (;;) {
        uint32_t item = 0;
        if (lane == 0) asm volatile("atom.shared.add.u32 %0, [%1], 1;" : "=r"(item) : "r"(sb + ITEM_OFF) : "memory");
        item = __shfl_sync(0xffffffffu, item, 0);
        if (item >= 16) break;
        const uint4* p = g_part + (size_t)((ti * 8 + tj) * 8) * 1024 + item * 64 + lane;
        uint4 v[2][8];
#pragma unroll
        for (int s = 0; s < 8; s++) { v[0][s] = ldg_weak(p + s * 1024); v[1][s] = ldg_weak(p + s * 1024 + 32); }
#pragma unroll
        for (int n = 0; n < 2; n++) {
            float a[8];
#pragma unroll
            for (int e = 0; e < 8; e++) a[e] = 0.f;
#pragma unroll
            for (int s = 0; s < 8; s++) {
                a[0] += bf_lo(v[n][s].x); a[1] += bf_hi(v[n][s].x); a[2] += bf_lo(v[n][s].y); a[3] += bf_hi(v[n][s].y);
                a[4] += bf_lo(v[n][s].z); a[5] += bf_hi(v[n][s].z); a[6] += bf_lo(v[n][s].w); a[7] += bf_hi(v[n][s].w);
            }
            const uint32_t d = sb + STG_OFF + (item * 4 + n * 2) * 512 + lane * 16;
            sts128(d, make_uint4(__float_as_uint(a[0]), __float_as_uint(a[1]), __float_as_uint(a[2]), __float_as_uint(a[3])));
            sts128(d + 512, make_uint4(__float_as_uint(a[4]), __float_as_uint(a[5]), __float_as_uint(a[6]), __float_as_uint(a[7])));
        }
    }
    __syncwarp();
    if (lane == 0) mbar_arrive(sb + B_HSUM);
}

#define PWAIT() mbar_wait(sb + B_EMPTY + 8 * r.slot, r.phase)
#define CWAIT() mbar_wait(sb + B_FULL + 8 * r.slot, r.phase)
template <bool B> struct BoolTag { static constexpr bool value = B; };
struct Ring {
    int slot; uint32_t phase;
    __device__ __forceinline__ void next() { if (++slot == RING) { slot = 0; phase ^= 1; } }
};

__global__ void __launch_bounds__(384, 1)
fused_kernel(const __grid_constant__ CUtensorMap map_x, const __grid_constant__ CUtensorMap map_qkv,
             const __grid_constant__ CUtensorMap map_w1, const __grid_constant__ CUtensorMap map_w2,
             const __grid_constant__ CUtensorMap map_wo, const __grid_constant__ CUtensorMap map_w1a,
             const __grid_constant__ CUtensorMap map_o,
             const __nv_bfloat16* __restrict__ gate_w, __nv_bfloat16* __restrict__ out,
             const uint8_t* __restrict__ w1p, const uint8_t* __restrict__ w2p, const uint8_t* __restrict__ wop)
{
    extern __shared__ __align__(1024) uint8_t smem_raw[];
    const uint32_t sb = smem_u32(smem_raw);
    const int tid = threadIdx.x, warp = tid >> 5, lane = tid & 31;
    const int ti = blockIdx.x >> 3, tj = blockIdx.x & 7;

    if (tid == 0) { TSG(31); TSX(0); }
    if (tid == 320) {
        asm volatile("prefetch.tensormap [%0];" :: "l"(&map_x) : "memory");
        asm volatile("prefetch.tensormap [%0];" :: "l"(&map_qkv) : "memory");
        asm volatile("prefetch.tensormap [%0];" :: "l"(&map_w1) : "memory");
        asm volatile("prefetch.tensormap [%0];" :: "l"(&map_w1a) : "memory");
        asm volatile("prefetch.tensormap [%0];" :: "l"(&map_w2) : "memory");
        asm volatile("prefetch.tensormap [%0];" :: "l"(&map_wo) : "memory");
        asm volatile("prefetch.tensormap [%0];" :: "l"(&map_o) : "memory");
    }
    uint32_t gwv[N_QKV / 2];
    if (warp == 8) {
        const unsigned short* gws = reinterpret_cast<const unsigned short*>(gate_w);
#pragma unroll
        for (int n = 0; n < N_QKV / 2; n++) gwv[n] = (uint32_t)__ldg(gws + 64 * n + lane) | ((uint32_t)__ldg(gws + 64 * n + 32 + lane) << 16);
    }
    if (tid == 256) {
        for (int s = 0; s < RING; s++) { mbar_init(sb + B_FULL + 8 * s, 1); mbar_init(sb + B_EMPTY + 8 * s, 8); }
        for (int s = 0; s < 8; s++) mbar_init(sb + B_XFULL + 8 * s, 1);
        mbar_init(sb + B_HDEAD, 8); mbar_init(sb + B_EREADY, 1); mbar_init(sb + B_KVDONE, 8); mbar_init(sb + B_KVREADY, 1);
        mbar_init(sb + B_ODONE, 8); mbar_init(sb + B_WOFULL, 1); mbar_init(sb + B_HSUM, 3);
        mbar_init(sb + B_PREADY, 1); mbar_init(sb + B_SF, 1); mbar_init(sb + B_SF + 8, 1);
        for (int s = 0; s < 4; s++) mbar_init(sb + B_SQ + 8 * s, 8);
        asm volatile("st.shared.u32 [%0], %1;" :: "r"(sb + ITEM_OFF), "r"(0) : "memory");
        asm volatile("fence.mbarrier_init.release.cluster;" ::: "memory");
        fence_async_smem();
        mbar_expect_tx(sb + B_XFULL, 16384);
        tma_2d(sb + X_OFF, &map_x, sb + B_XFULL, 0, ti * 128);
        mbar_expect_only(sb + B_FULL, 12288);
        tma_4d(sb + RING_OFF, &map_qkv, sb + B_FULL, 0, 0, tj, 0);
    }
    __syncthreads();

    if (warp >= 8) {
        asm volatile("setmaxnreg.dec.sync.aligned.u32 88;");
        if (warp == 8) {
            Ring r{0, 1};
            const bool leader = elect_one();
#pragma unroll
            for (int n = 0; n < N_QKV; n++) {
                const uint32_t full = sb + B_FULL + 8 * r.slot, dst = sb + RING_OFF + r.slot * SLOT;
                if (n > 0) {
                    if (!(n & 1) && leader) {
                        mbar_expect_tx(sb + B_XFULL + 8 * (n >> 1), 16384);
                        tma_2d(sb + X_OFF + (n >> 1) * 16384, &map_x, sb + B_XFULL + 8 * (n >> 1), (n >> 1) * 64, ti * 128);
                    }
                    if (n >= RING) PWAIT();
                    if (leader) {
                        mbar_expect_only(full, 12288);
                        tma_4d(dst, &map_qkv, full, 0, 32 * n, tj, 0);
                    }
                }
                const uint32_t gv = (n & 1) ? (gwv[n >> 1] >> 16) : (gwv[n >> 1] & 0xFFFFu);
                asm volatile("st.shared.v4.b32 [%0], {%1, %2, %2, %2};" :: "r"(dst + 12288 + lane * 128 + ((lane & 7) << 4)), "r"(gv), "r"(0) : "memory");
                fence_async_smem();
                __syncwarp();
                if (leader) mbar_arrive(full);
                r.next();
            }
#pragma unroll 1
            for (int n = 0; n < N_FFN1; n++) {
                const uint32_t full = sb + B_FULL + 8 * r.slot, dst = sb + RING_OFF + r.slot * SLOT;
                PWAIT();
                if (leader) {
                    mbar_expect_tx(full, 16384);
                    tma_4d(dst, &map_w1a, full, 0, 32 * n, 0, tj);
                    tma_2d(dst + 3 * 4096, &map_w1, full, 224 * tj + 192, 32 * n);
                }
                r.next();
            }
            {
                int q = 0, rr = 0;
#pragma unroll 1
                for (int n = 0; n < N_FFN2; n++) {
                    const uint32_t full = sb + B_FULL + 8 * r.slot, dst = sb + RING_OFF + r.slot * SLOT;
                    PWAIT();
                    if (leader) mbar_expect_tx(full, 16384);
#pragma unroll
                    for (int h = 0; h < 2; h++) {
                        if (leader) tma_3d(dst + h * 8192, &map_w2, full, 0, 224 * tj + 32 * rr, 2 * q);
                        if (++rr == 7) { rr = 0; q++; }
                    }
                    r.next();
                }
            }
            mbar_wait(sb + B_KVREADY, 0);
            asm volatile("fence.proxy.async.global;" ::: "memory");
            {
                const int bbase = 8 * ti - 16, b0 = bbase < 0 ? 0 : bbase;
                const uint32_t bytes = (uint32_t)(8 * ti + 8 - b0) * 512;
#pragma unroll 1
                for (int m = 0; m < N_KV; m++) {
                    const uint32_t full = sb + B_FULL + 8 * r.slot, dst = sb + RING_OFF + r.slot * SLOT;
                    if (m == RING) {
                        mbar_wait(sb + B_HDEAD, 0);
                        if (leader) {
                            mbar_expect_tx(sb + B_WOFULL, 65536);
#pragma unroll
                            for (int e = 0; e < 2; e++) tma_2d(sb + X_OFF + e * 32768, &map_wo, sb + B_WOFULL, 64 * tj, 256 * e);
                        }
                    }
                    PWAIT();
                    if (leader) {
                        const uint4* src = ((m & 1) ? g_vf : g_kf) + ((tj * 4 + (m >> 1)) * 128 + b0) * 32;
                        mbar_expect_tx(full, bytes);
                        bulk_g2s(dst + (b0 - bbase) * 512, src, bytes, full);
                    }
                    r.next();
                }
            }
            {
                mbar_wait(sb + B_EREADY, 0);
                unsigned epoch; asm volatile("ld.shared.u32 %0, [%1];" : "=r"(epoch) : "r"(sb + EPOCH_OFF) : "memory");
                mbar_wait(sb + B_ODONE, 0);
                if (leader) red_release(&g_ocnt[blockIdx.x * 32], 1u);
                __syncwarp();
                if (lane < 8) wait_counter(&g_ocnt[(ti * 8 + lane) * 32], epoch + 1);
                __syncwarp();
                asm volatile("fence.proxy.async.global;" ::: "memory");
#pragma unroll 1
                for (int m = 0; m < N_O; m++) {
                    const uint32_t full = sb + B_FULL + 8 * r.slot, dst = sb + RING_OFF + r.slot * SLOT;
                    PWAIT();
                    if (leader) {
                        mbar_expect_tx(full, 16384);
                        tma_2d(dst, &map_o, full, 64 * ((tj + m) & 7), ti * 128);
                    }
                    r.next();
                }
            }
        } else if (warp == 9) {
            unsigned epoch = 0;
            if (lane == 0) {
                epoch = atomicAdd(&g_ticket, 1u) >> 7;
                asm volatile("st.shared.u32 [%0], %1;" :: "r"(sb + EPOCH_OFF), "r"(epoch) : "memory");
                mbar_arrive(sb + B_EREADY);
                mbar_wait(sb + B_XFULL + 8 * PF1_AT, 0);
                prefetch_l2(w1p + (size_t)blockIdx.x * 14336, 14336);
                mbar_wait(sb + B_XFULL + 8 * PF2_AT, 0);
                prefetch_l2(w2p + (size_t)blockIdx.x * 14336, 14336);
                prefetch_l2(wop + (size_t)blockIdx.x * 4096, 4096);
                mbar_wait(sb + B_KVDONE, 0);
                red_release(&g_kvcnt[blockIdx.x * 32], 1u);
            }
            epoch = __shfl_sync(0xffffffffu, epoch, 0);
            if (lane < 3 && ti - lane >= 0) wait_counter(&g_kvcnt[((ti - lane) * 8 + tj) * 32], epoch + 1);
            __syncwarp();
            if (lane == 0) mbar_arrive(sb + B_KVREADY);
            mbar_wait(sb + B_SQ + 24, 0);
            if (lane < 8) wait_counter(&g_pcnt[(ti * 8 + lane) * 32], epoch + 1);
            __syncwarp();
            if (lane == 0) { mbar_arrive(sb + B_PREADY); TSX(13); }
            sum_partials(sb, ti, tj, lane);
            if (lane == 0) TSX(14);
        } else {
            if (warp == 10) {
#pragma unroll 1
                for (int q = 0; q < 4; q++) {
                    mbar_wait(sb + B_SQ + 8 * q, 0);
                    if (lane < 16) {
                        uint4* d = g_part + (size_t)(((ti * 8 + 2 * q + (lane & 1)) * 8 + tj) * 8 + (lane >> 1)) * 128;
                        bulk_s2g(d, sb + STG_OFF + (q & 1) * 32768 + lane * 2048, 2048);
                        asm volatile("cp.async.bulk.commit_group;" ::: "memory");
                        if (q < 2) asm volatile("cp.async.bulk.wait_group.read 0;" ::: "memory");
                    }
                    __syncwarp();
                    if (q < 2 && lane == 0) mbar_arrive(sb + B_SF + 8 * q);
                }
                asm volatile("cp.async.bulk.wait_group 0;" ::: "memory");
                asm volatile("fence.proxy.async.global;" ::: "memory");
                __syncwarp();
                if (lane == 0) { red_release(&g_pcnt[blockIdx.x * 32], 1u); TSX(12); }
            }
            mbar_wait(sb + B_PREADY, 0);
            sum_partials(sb, ti, tj, lane);
        }
    } else {
        asm volatile("setmaxnreg.inc.sync.aligned.u32 208;");
        const int wg = warp >> 2, g = lane >> 2, c = lane & 3;
        const uint32_t xa = sb + X_OFF + wg * 8192;
        Ring r{0, 0};
        uint32_t qf[4][4];
        float g0, g1;
        TS(9);
        {
            float acc[100];
            int prev = 0;
            if (wg == 1) asm volatile("bar.sync 3, 256;" ::: "memory");
            for (int s = 0; s < N_QKV; s++) {
                if (!(s & 1)) mbar_wait(sb + B_XFULL + 8 * (s >> 1), 0);
                CWAIT();
                if (s == 0) TS(1);
                if (s == 2) TS(28);
                if (s == 6) TS(29);
                if (s == 10) TS(20);
                const uint32_t bs = sb + RING_OFF + r.slot * SLOT, as = xa + (s >> 1) * 16384 + (s & 1) * 64;
                wgmma_fence();
                wgmma_ss_n200(acc, desc_a(as), desc_b(bs), s);
                wgmma_ss_n200(acc, desc_a(as + 32), desc_b(bs + 2048), 1);
                wgmma_commit();
                if (wg == 0 && s == LEAD1) asm volatile("bar.arrive 3, 256;" ::: "memory");
                if (s > 0) { wgmma_wait<1>(); if (lane == 0) mbar_arrive(sb + B_EMPTY + 8 * prev); }
                prev = r.slot; r.next();
            }
            wgmma_wait<0>();
            fence_acc(acc);
            if (lane == 0) mbar_arrive(sb + B_EMPTY + 8 * prev);
            TS(2);
            const int blk = ti * 8 + warp;
#pragma unroll
            for (int hh = 0; hh < 4; hh++) {
                const float* t0 = &acc[8 * hh]; const float* t1 = &acc[8 * hh + 4];
                qf[hh][0] = pack_bf16(t0[0], t0[1]); qf[hh][1] = pack_bf16(t0[2], t0[3]);
                qf[hh][2] = pack_bf16(t1[0], t1[1]); qf[hh][3] = pack_bf16(t1[2], t1[3]);
                const float* k0 = &acc[32 + 8 * hh]; const float* k1 = &acc[32 + 8 * hh + 4];
                uint4 kv;
                kv.x = pack_bf16(k0[0], k0[1]); kv.y = pack_bf16(k1[0], k1[1]);
                kv.z = pack_bf16(k0[2], k0[3]); kv.w = pack_bf16(k1[2], k1[3]);
                g_kf[((tj * 4 + hh) * 128 + blk) * 32 + lane] = kv;
                const float* v0 = &acc[64 + 8 * hh]; const float* v1 = &acc[64 + 8 * hh + 4];
                uint4 vv;
                vv.x = movmatrix(pack_bf16(v0[0], v0[1])); vv.y = movmatrix(pack_bf16(v0[2], v0[3]));
                vv.z = movmatrix(pack_bf16(v1[0], v1[1])); vv.w = movmatrix(pack_bf16(v1[2], v1[3]));
                g_vf[((tj * 4 + hh) * 128 + blk) * 32 + lane] = vv;
            }
            __syncwarp();
            if (lane == 0) mbar_arrive(sb + B_KVDONE);
            const float z0 = __shfl_sync(0xffffffffu, acc[96], lane & ~3), z1 = __shfl_sync(0xffffffffu, acc[98], lane & ~3);
            g0 = 1.f / (1.f + __expf(-z0)); g1 = 1.f / (1.f + __expf(-z1));
        }
        TS(3);
        const int wrow = (warp & 3) * 16;
        {
            float acc[112];
            int prev = 0;
            for (int s = 0; s < N_FFN1; s++) {
                CWAIT();
                const uint32_t bs = sb + RING_OFF + r.slot * SLOT, as = xa + (s >> 1) * 16384 + (s & 1) * 64;
                wgmma_fence();
                wgmma_ss_n224(acc, desc_a(as), desc_b(bs), s);
                wgmma_ss_n224(acc, desc_a(as + 32), desc_b(bs + 2048), 1);
                wgmma_commit();
                if (s > 0) { wgmma_wait<1>(); if (lane == 0) mbar_arrive(sb + B_EMPTY + 8 * prev); }
                prev = r.slot; r.next();
            }
            wgmma_wait<0>();
            fence_acc(acc);
            if (lane == 0) mbar_arrive(sb + B_EMPTY + 8 * prev);
            TS(4);
            const float s0 = 1.f - g0, s1 = 1.f - g1;
            asm volatile("bar.sync %0, 128;" :: "r"(1 + wg) : "memory");
            const uint32_t strow = xa + (wrow + ((lane >> 3) & 1) * 8 + (lane & 7)) * 128;
#pragma unroll
            for (int p = 0; p < 14; p++) {
                const int nt = 2 * p + (lane >> 4);
                const float* a = &acc[8 * p];
                stmatrix_x4(strow + (p >> 2) * 16384 + (((nt & 7) ^ (lane & 7)) << 4),
                            pack_bf16_relu(a[0] * s0, a[1] * s0), pack_bf16_relu(a[2] * s1, a[3] * s1),
                            pack_bf16_relu(a[4] * s0, a[5] * s0), pack_bf16_relu(a[6] * s1, a[7] * s1));
            }
        }
        TS(5);
        {
            fence_async_smem();
            asm volatile("bar.sync 4, 256;" ::: "memory");
            float accA[64], accB[64];
            auto epilogue = [&](float (&acc)[64], int q) {
                fence_acc(acc);
                const uint32_t st = sb + STG_OFF + (q & 1) * 32768 + warp * 4096;
                if (q >= 2) mbar_wait(sb + B_SF + 8 * (q & 1), 0);
#pragma unroll
                for (int t2 = 0; t2 < 8; t2++) {
                    uint4 v;
                    v.x = pack_bf16(acc[8 * t2 + 0], acc[8 * t2 + 1]); v.y = pack_bf16(acc[8 * t2 + 2], acc[8 * t2 + 3]);
                    v.z = pack_bf16(acc[8 * t2 + 4], acc[8 * t2 + 5]); v.w = pack_bf16(acc[8 * t2 + 6], acc[8 * t2 + 7]);
                    sts128(st + t2 * 512 + lane * 16, v);
                }
                fence_async_smem();
                __syncwarp();
                if (lane == 0) mbar_arrive(sb + B_SQ + 8 * q);
            };
            int rel = r.slot;
#pragma unroll
            for (int m = 0; m < N_FFN2; m++) {
                CWAIT();
                wgmma_fence();
#pragma unroll
                for (int h = 0; h < 2; h++) {
                    const int u = 2 * m + h, q = u / 7, rr = u % 7;
                    const uint32_t bs = sb + RING_OFF + r.slot * SLOT + h * 8192;
                    const uint32_t as = xa + (rr >> 1) * 16384 + (rr & 1) * 64;
                    if (!(q & 1)) {
                        wgmma_ss_n128(accA, desc_a(as), desc_b(bs), rr);
                        wgmma_ss_n128(accA, desc_a(as + 32), desc_b(bs + 2048), 1);
                    } else {
                        wgmma_ss_n128(accB, desc_a(as), desc_b(bs), rr);
                        wgmma_ss_n128(accB, desc_a(as + 32), desc_b(bs + 2048), 1);
                    }
                }
                wgmma_commit();
                r.next();
                wgmma_wait<1>();
                if (m > 0) {
                    if (lane == 0) mbar_arrive(sb + B_EMPTY + 8 * rel);
                    if (++rel == RING) rel = 0;
                }
                if (m == 4) { TS(25); epilogue(accA, 0); }
                if (m == 7) { TS(26); epilogue(accB, 1); }
                if (m == 11) { TS(27); epilogue(accA, 2); }
            }
            wgmma_wait<0>();
            if (lane == 0) { mbar_arrive(sb + B_EMPTY + 8 * rel); mbar_arrive(sb + B_HDEAD); }
            epilogue(accB, 3);
        }
        TS(6);
        {
            const float SC = 0.25f * 1.4426950408889634f;
            const int gb0 = 8 * ti - 16 + warp;
            int slotK = 0, slotV = 0;
            uint32_t* odst = reinterpret_cast<uint32_t*>(g_o + (size_t)(ti * 128 + warp * 16 + g) * 512 + tj * 64 + ((lane & 1) ? 8 : 0) + (lane & 2) * 2);
#define NHEADS 4
#define ATT_KWAIT(kb) do { slotK = r.slot; CWAIT(); kb = sb + RING_OFF + slotK * SLOT + warp * 512 + lane * 16; r.next(); } while (0)
#define ATT_VWAIT(vb) do { slotV = r.slot; CWAIT(); vb = sb + RING_OFF + slotV * SLOT + warp * 512 + lane * 16; r.next(); TS(21 + hh); } while (0)
#define ATT_KREL() do { __syncwarp(); if (lane == 0) mbar_arrive(sb + B_EMPTY + 8 * slotK); } while (0)
#define ATT_VREL() do { __syncwarp(); if (lane == 0) mbar_arrive(sb + B_EMPTY + 8 * slotV); } while (0)
#define ATT_NEXTQ(h) do { \
                if ((h) == 1) { q0 = qf[1][0]; q1 = qf[1][1]; q2 = qf[1][2]; q3 = qf[1][3]; } \
                else if ((h) == 2) { q0 = qf[2][0]; q1 = qf[2][1]; q2 = qf[2][2]; q3 = qf[2][3]; } \
                else { q0 = qf[3][0]; q1 = qf[3][1]; q2 = qf[3][2]; q3 = qf[3][3]; } } while (0)
#define ATT_STORE(h, r0, r1, r2, r3) do { \
                const bool odd = lane & 1; \
                const uint32_t sl = __shfl_xor_sync(0xffffffffu, odd ? (r0) : (r2), 1), sh = __shfl_xor_sync(0xffffffffu, odd ? (r1) : (r3), 1); \
                *reinterpret_cast<uint2*>(odst + 8 * (h)) = odd ? make_uint2(sl, r2) : make_uint2(r0, sl); \
                *reinterpret_cast<uint2*>(odst + 8 * (h) + 8 * 256) = odd ? make_uint2(sh, r3) : make_uint2(r1, sh); \
                } while (0)
            auto attention = [&](auto masked_tag) {
            constexpr bool MASKED = decltype(masked_tag)::value;
            const float NEG = -INFINITY;
            const uint32_t ONES = 0x3F803F80u;
            float sa[8][2][4], sb2[8][2][4];
            float o[2][4], ls[4];
            float m0, m1;
            uint32_t q0 = qf[0][0], q1 = qf[0][1], q2 = qf[0][2], q3 = qf[0][3];
            auto qk = [&](float (&s)[8][2][4], int ps, int t, uint32_t kbase) {
                if (ps == 0 && t == 0) {
                    const uint4 kd = lds128(kbase + 16 * 512);
                    const uint4 kf = lds128(kbase);
                    float f[2][4];
                    const float ci = (!MASKED || opaque(gb0) >= 0) ? 0.f : NEG;
                    mma16816_c(s[0][0], q0, q1, q2, q3, kd.x, kd.y, 0.f);
                    mma16816_c(s[0][1], q0, q1, q2, q3, kd.z, kd.w, 0.f);
                    mma16816_c(f[0], q0, q1, q2, q3, kf.x, kf.y, ci);
                    mma16816_c(f[1], q0, q1, q2, q3, kf.z, kf.w, ci);
#pragma unroll
                    for (int u = 0; u < 2; u++)
#pragma unroll
                        for (int e = 0; e < 4; e++) {
                            const int row = g + 8 * (e >> 1), col = 8 * u + 2 * c + (e & 1);
                            s[0][u][e] = (col > row) ? f[u][e] : s[0][u][e];
                        }
                } else {
                    const uint4 kf = lds128(kbase + (8 * ps + t) * 512);
                    const float ci = (!MASKED || opaque(gb0) + 8 * ps + t >= 0) ? 0.f : NEG;
                    mma16816_c(s[t][0], q0, q1, q2, q3, kf.x, kf.y, ci);
                    mma16816_c(s[t][1], q0, q1, q2, q3, kf.z, kf.w, ci);
                }
            };
            auto rowmax = [&](float (&s)[8][2][4], float b0, float b1, float& n0, float& n1) {
                int i0 = __float_as_int(b0), i1 = __float_as_int(b1);
#pragma unroll
                for (int t = 0; t < 8; t++)
#pragma unroll
                    for (int u = 0; u < 2; u++) {
                        i0 = __vimax3_s32(i0, __float_as_int(s[t][u][0]), __float_as_int(s[t][u][1]));
                        i1 = __vimax3_s32(i1, __float_as_int(s[t][u][2]), __float_as_int(s[t][u][3]));
                    }
                i0 = max(i0, __shfl_xor_sync(0xffffffffu, i0, 1)); i1 = max(i1, __shfl_xor_sync(0xffffffffu, i1, 1));
                i0 = max(i0, __shfl_xor_sync(0xffffffffu, i0, 2)); i1 = max(i1, __shfl_xor_sync(0xffffffffu, i1, 2));
                n0 = __int_as_float(i0); n1 = __int_as_float(i1);
                if (__any_sync(0xffffffffu, (i0 | i1) < 0)) {
                    asm volatile("" ::: "memory");
                    n0 = b0; n1 = b1;
#pragma unroll
                    for (int t = 0; t < 8; t++)
#pragma unroll
                        for (int u = 0; u < 2; u++) {
                            n0 = fmaxf(n0, fmaxf(s[t][u][0], s[t][u][1]));
                            n1 = fmaxf(n1, fmaxf(s[t][u][2], s[t][u][3]));
                        }
                    n0 = fmaxf(n0, __shfl_xor_sync(0xffffffffu, n0, 1)); n1 = fmaxf(n1, __shfl_xor_sync(0xffffffffu, n1, 1));
                    n0 = fmaxf(n0, __shfl_xor_sync(0xffffffffu, n0, 2)); n1 = fmaxf(n1, __shfl_xor_sync(0xffffffffu, n1, 2));
                }
            };
            auto pv = [&](const float (&p)[2][4], uint32_t vaddr) {
                const uint4 vf = lds128(vaddr);
                const uint32_t a0 = pack_bf16(p[0][0], p[0][1]), a1 = pack_bf16(p[0][2], p[0][3]);
                const uint32_t a2 = pack_bf16(p[1][0], p[1][1]), a3 = pack_bf16(p[1][2], p[1][3]);
                mma16816(o[0], a0, a1, a2, a3, vf.x, vf.y);
                mma16816(o[1], a0, a1, a2, a3, vf.z, vf.w);
                mma16816(ls, a0, a1, a2, a3, ONES, ONES);
            };
            auto expv = [&](float (&s)[8][2][4], int ps, int t, float mc0, float mc1, uint32_t vbase) {
                float p[2][4];
#pragma unroll
                for (int u = 0; u < 2; u++) {
                    p[u][0] = ex2(fmaf(s[t][u][0], SC, -mc0)); p[u][1] = ex2(fmaf(s[t][u][1], SC, -mc0));
                    p[u][2] = ex2(fmaf(s[t][u][2], SC, -mc1)); p[u][3] = ex2(fmaf(s[t][u][3], SC, -mc1));
                }
                if (ps == 0 && t == 0) {
                    float pd[2][4], pf[2][4];
#pragma unroll
                    for (int u = 0; u < 2; u++)
#pragma unroll
                        for (int e = 0; e < 4; e++) {
                            const int row = g + 8 * (e >> 1), col = 8 * u + 2 * c + (e & 1);
                            pf[u][e] = (col > row) ? p[u][e] : 0.f;
                            pd[u][e] = (col > row) ? 0.f : p[u][e];
                        }
                    pv(pd, vbase + 16 * 512);
                    pv(pf, vbase);
                } else {
                    pv(p, vbase + (8 * ps + t) * 512);
                }
            };
            uint32_t kbase, vbase;
            ATT_KWAIT(kbase);
#pragma unroll
            for (int t = 0; t < 8; t++) qk(sa, 0, t, kbase);
            rowmax(sa, NEG, NEG, m0, m1);
#pragma unroll 1
            for (int hh = 0; hh < NHEADS; hh++) {
                ATT_VWAIT(vbase);
#pragma unroll
                for (int e = 0; e < 4; e++) { o[0][e] = 0.f; o[1][e] = 0.f; ls[e] = 0.f; }
                {
                    const float mc0 = m0 * SC, mc1 = m1 * SC;
#pragma unroll
                    for (int t = 0; t < 8; t++) { qk(sb2, 1, t, kbase); expv(sa, 0, t, mc0, mc1, vbase); }
                    ATT_KREL();
                    float n0, n1;
                    rowmax(sb2, m0, m1, n0, n1);
                    const float a0 = ex2((m0 - n0) * SC), a1 = ex2((m1 - n1) * SC);
                    ls[0] *= a0; ls[2] *= a1;
                    o[0][0] *= a0; o[0][1] *= a0; o[1][0] *= a0; o[1][1] *= a0;
                    o[0][2] *= a1; o[0][3] *= a1; o[1][2] *= a1; o[1][3] *= a1;
                    m0 = n0; m1 = n1;
                }
                {
                    const float mc0 = m0 * SC, mc1 = m1 * SC;
                    const bool more = hh + 1 < NHEADS;
                    if (more) {
                        ATT_KWAIT(kbase);
                        ATT_NEXTQ(hh + 1);
#pragma unroll
                        for (int t = 0; t < 8; t++) { qk(sa, 0, t, kbase); expv(sb2, 1, t, mc0, mc1, vbase); }
                        rowmax(sa, NEG, NEG, m0, m1);
                    } else {
#pragma unroll
                        for (int t = 0; t < 8; t++) expv(sb2, 1, t, mc0, mc1, vbase);
                    }
                    ATT_VREL();
                }
                const float f0 = __fdividef(g0, ls[0]), f1 = __fdividef(g1, ls[2]);
                ATT_STORE(hh, pack_bf16(o[0][0] * f0, o[0][1] * f0), pack_bf16(o[0][2] * f1, o[0][3] * f1),
                              pack_bf16(o[1][0] * f0, o[1][1] * f0), pack_bf16(o[1][2] * f1, o[1][3] * f1));
            }
            };
            if (ti >= 2) attention(BoolTag<false>{}); else attention(BoolTag<true>{});
            __syncwarp();
            if (lane == 0) mbar_arrive(sb + B_ODONE);
        }
        TS(7);
        {
            float acc[32];
            mbar_wait(sb + B_HSUM, 0);
#pragma unroll
            for (int k = 0; k < 8; k++) {
                const uint4 v = lds128(sb + STG_OFF + (warp * 8 + k) * 512 + lane * 16);
                acc[4 * k] = __uint_as_float(v.x); acc[4 * k + 1] = __uint_as_float(v.y);
                acc[4 * k + 2] = __uint_as_float(v.z); acc[4 * k + 3] = __uint_as_float(v.w);
            }
            fence_acc(acc);
            mbar_wait(sb + B_WOFULL, 0);
            mbar_wait(sb + B_ODONE, 0);
            TS(15);
            int prev = 0;
#pragma unroll 1
            for (int m = 0; m < N_O; m++) {
                CWAIT();
                if (m == 0) TS(16);
                const uint32_t as = sb + RING_OFF + r.slot * SLOT + wg * 8192;
                const uint32_t bs = sb + X_OFF + ((tj + m) & 7) * 8192;
                wgmma_fence();
#pragma unroll
                for (int k = 0; k < 4; k++) wgmma_ss_n64(acc, desc_a(as + 32 * k), desc_b(bs + 2048 * k), 1);
                wgmma_commit();
                if (m > 0) { wgmma_wait<1>(); if (lane == 0) mbar_arrive(sb + B_EMPTY + 8 * prev); }
                prev = r.slot; r.next();
            }
            wgmma_wait<0>();
            fence_acc(acc);
            TS(17);
            __nv_bfloat16* o = out + (size_t)(ti * 128 + warp * 16 + g) * 512 + tj * 64 + ((lane & 1) ? 8 : 0) + (lane & 2) * 2;
            const bool odd = lane & 1;
#pragma unroll
            for (int t2 = 0; t2 < 4; t2++) {
                const uint32_t lo0 = pack_bf16(acc[8 * t2 + 0], acc[8 * t2 + 1]), hi0 = pack_bf16(acc[8 * t2 + 2], acc[8 * t2 + 3]);
                const uint32_t lo1 = pack_bf16(acc[8 * t2 + 4], acc[8 * t2 + 5]), hi1 = pack_bf16(acc[8 * t2 + 6], acc[8 * t2 + 7]);
                const uint32_t sl = __shfl_xor_sync(0xffffffffu, odd ? lo0 : lo1, 1), sh = __shfl_xor_sync(0xffffffffu, odd ? hi0 : hi1, 1);
                *reinterpret_cast<uint2*>(o + 16 * t2) = odd ? make_uint2(sl, lo1) : make_uint2(lo0, sl);
                *reinterpret_cast<uint2*>(o + 16 * t2 + 8 * 512) = odd ? make_uint2(sh, hi1) : make_uint2(hi0, sh);
            }
            if (tid == 0) TSG(30);
        }
        TS(8);
    }
}

typedef CUresult (*PFN_encodeTiled)(CUtensorMap*, CUtensorMapDataType, cuuint32_t, void*, const cuuint64_t*, const cuuint64_t*,
                                    const cuuint32_t*, const cuuint32_t*, CUtensorMapInterleave, CUtensorMapSwizzle,
                                    CUtensorMapL2promotion, CUtensorMapFloatOOBfill);

void make_map(PFN_encodeTiled enc, CUtensorMap* m, const void* base, int rank, const cuuint64_t* dims, const cuuint64_t* strides, const cuuint32_t* box) {
    cuuint32_t es[5] = {1, 1, 1, 1, 1};
    enc(m, CU_TENSOR_MAP_DATA_TYPE_BFLOAT16, (cuuint32_t)rank, const_cast<void*>(base), dims, strides, box, es,
        CU_TENSOR_MAP_INTERLEAVE_NONE, CU_TENSOR_MAP_SWIZZLE_128B, CU_TENSOR_MAP_L2_PROMOTION_L2_256B, CU_TENSOR_MAP_FLOAT_OOB_FILL_NONE);
}

}

extern "C" void kernel_launch(void* const* d_in, const int* in_sizes, int n_in, void* d_out, int out_size) {
    (void)in_sizes; (void)n_in; (void)out_size;
    const void* x = d_in[0]; const void* wqkv = d_in[1]; const void* wo = d_in[2];
    const void* w1 = d_in[4]; const void* w2 = d_in[5]; const void* gate_w = d_in[6];
    static PFN_encodeTiled enc = nullptr;
    if (!enc) {
        void* fn = nullptr; cudaDriverEntryPointQueryResult st;
        cudaGetDriverEntryPoint("cuTensorMapEncodeTiled", &fn, cudaEnableDefault, &st);
        enc = (PFN_encodeTiled)fn;
        cudaFuncSetAttribute(fused_kernel, cudaFuncAttributeMaxDynamicSharedMemorySize, SMEM_BYTES);
    }
    CUtensorMap mx, mqkv, mw1, mw2, mwo, mw1a, mo;
    void* optr = nullptr;
    cudaGetSymbolAddress(&optr, g_o);
    { cuuint64_t d[2] = {512, 2048}, s[1] = {1024}; cuuint32_t b[2] = {64, 128}; make_map(enc, &mo, optr, 2, d, s, b); }
    { cuuint64_t d[4] = {64, 512, 3, 8}, s[3] = {3584, 128, 448}; cuuint32_t b[4] = {64, 32, 3, 1}; make_map(enc, &mw1a, w1, 4, d, s, b); }
    { cuuint64_t d[2] = {512, 2048}, s[1] = {1024}; cuuint32_t b[2] = {64, 128}; make_map(enc, &mx, x, 2, d, s, b); }
    { cuuint64_t d[4] = {64, 512, 8, 3}, s[3] = {3072, 128, 1024}; cuuint32_t b[4] = {64, 32, 1, 3}; make_map(enc, &mqkv, wqkv, 4, d, s, b); }
    { cuuint64_t d[2] = {1792, 512}, s[1] = {3584}; cuuint32_t b[2] = {64, 32}; make_map(enc, &mw1, w1, 2, d, s, b); }
    { cuuint64_t d[3] = {64, 1792, 8}, s[2] = {1024, 128}; cuuint32_t b[3] = {64, 32, 2}; make_map(enc, &mw2, w2, 3, d, s, b); }
    { cuuint64_t d[2] = {512, 512}, s[1] = {1024}; cuuint32_t b[2] = {64, 256}; make_map(enc, &mwo, wo, 2, d, s, b); }
    fused_kernel<<<128, 384, SMEM_BYTES, cudaStreamPerThread>>>(mx, mqkv, mw1, mw2, mwo, mw1a, mo, (const __nv_bfloat16*)gate_w, (__nv_bfloat16*)d_out,
                                           (const uint8_t*)w1, (const uint8_t*)w2, (const uint8_t*)wo);
}
```

```cpp
#include <cuda_runtime.h>
#include <cuda_bf16.h>
#include <cuda.h>
#include <stdint.h>

namespace {

#define PF1_AT 1
#define PF2_AT 5
#define LEAD1 2
#define NCTA 132
constexpr int RING = 6;
constexpr int SLOT = 16384;
constexpr uint32_t X_OFF = 0;
constexpr uint32_t STG_OFF = X_OFF + 4 * 16384;
constexpr uint32_t RING_OFF = 131072;
constexpr uint32_t BAR_OFF = RING_OFF + RING * SLOT;
constexpr uint32_t B_FULL = BAR_OFF, B_EMPTY = BAR_OFF + 64, B_XFULL = BAR_OFF + 128, B_HDEAD = BAR_OFF + 192,
                   B_EREADY = BAR_OFF + 200, B_KVDONE = BAR_OFF + 208, B_ODONE = BAR_OFF + 224,
                   B_KVREADY = BAR_OFF + 232, B_WOFULL = BAR_OFF + 240, B_HSUM = BAR_OFF + 248, B_PREADY = BAR_OFF + 264,
                   B_SQ = BAR_OFF + 272, B_SF = BAR_OFF + 304;
constexpr uint32_t EPOCH_OFF = BAR_OFF + 256, ITEM_OFF = BAR_OFF + 260;
constexpr uint32_t SMEM_BYTES = BAR_OFF + 1024;

constexpr int N_QKV = 16, N_FFN1 = 16, N_FFN2 = 14, N_KV = 8, N_O = 8;

__device__ uint4 g_kf[32 * 128 * 32];
__device__ uint4 g_vf[32 * 128 * 32];
__device__ uint4 g_part[16 * 8 * 8 * 8 * 4 * 32];
__device__ __nv_bfloat16 g_o[2048 * 512];
__device__ unsigned g_ticket;
__device__ unsigned g_kvcnt[128 * 32];
__device__ unsigned g_pcnt[128 * 32];
__device__ unsigned g_ocnt[128 * 32];
#define TS(k) do {} while (0)
#define TS2(k) do {} while (0)
#define TS2X(k) do {} while (0)
#define TSX(k) do {} while (0)
#define TSG(k) do {} while (0)

__device__ __forceinline__ uint32_t smem_u32(const void* p) { return (uint32_t)__cvta_generic_to_shared(p); }
__device__ __forceinline__ void mbar_init(uint32_t bar, uint32_t cnt) { asm volatile("mbarrier.init.shared::cta.b64 [%0], %1;" :: "r"(bar), "r"(cnt) : "memory"); }
__device__ __forceinline__ void mbar_expect_tx(uint32_t bar, uint32_t bytes) { asm volatile("mbarrier.arrive.expect_tx.shared::cta.b64 _, [%0], %1;" :: "r"(bar), "r"(bytes) : "memory"); }
__device__ __forceinline__ void mbar_expect_only(uint32_t bar, uint32_t bytes) { asm volatile("mbarrier.expect_tx.relaxed.cta.shared::cta.b64 [%0], %1;" :: "r"(bar), "r"(bytes) : "memory"); }
__device__ __forceinline__ void mbar_arrive(uint32_t bar) { asm volatile("mbarrier.arrive.shared::cta.b64 _, [%0];" :: "r"(bar) : "memory"); }
__device__ __forceinline__ void mbar_wait(uint32_t bar, uint32_t parity) {
    asm volatile("{\n.reg .pred P1, P2;\n.reg .u32 n;\nmov.u32 n, 0;\n"
                 "WAIT_LOOP:\n"
                 "mbarrier.try_wait.parity.shared::cta.b64 P1, [%0], %1;\n"
                 "@P1 bra WAIT_DONE;\n"
                 "add.u32 n, n, 1;\n"
                 "setp.lt.u32 P2, n, 0x400000;\n"
                 "@P2 bra WAIT_LOOP;\n"
                 "WAIT_DONE:\n}" :: "r"(bar), "r"(parity) : "memory");
}
__device__ __forceinline__ void tma_2d(uint32_t dst, const void* map, uint32_t bar, int c0, int c1) {
    asm volatile("cp.async.bulk.tensor.2d.shared::cluster.global.mbarrier::complete_tx::bytes [%0], [%1, {%3, %4}], [%2];"
        :: "r"(dst), "l"(map), "r"(bar), "r"(c0), "r"(c1) : "memory");
}
__device__ __forceinline__ void tma_3d(uint32_t dst, const void* map, uint32_t bar, int c0, int c1, int c2) {
    asm volatile("cp.async.bulk.tensor.3d.shared::cluster.global.mbarrier::complete_tx::bytes [%0], [%1, {%3, %4, %5}], [%2];"
        :: "r"(dst), "l"(map), "r"(bar), "r"(c0), "r"(c1), "r"(c2) : "memory");
}
__device__ __forceinline__ void tma_4d(uint32_t dst, const void* map, uint32_t bar, int c0, int c1, int c2, int c3) {
    asm volatile("cp.async.bulk.tensor.4d.shared::cluster.global.mbarrier::complete_tx::bytes [%0], [%1, {%3, %4, %5, %6}], [%2];"
        :: "r"(dst), "l"(map), "r"(bar), "r"(c0), "r"(c1), "r"(c2), "r"(c3) : "memory");
}
__device__ __forceinline__ void bulk_g2s(uint32_t dst, const void* src, uint32_t bytes, uint32_t bar) {
    asm volatile("cp.async.bulk.shared::cluster.global.mbarrier::complete_tx::bytes [%0], [%1], %2, [%3];"
        :: "r"(dst), "l"(src), "r"(bytes), "r"(bar) : "memory");
}
__device__ __forceinline__ void prefetch_l2(const void* src, uint32_t bytes) {
    asm volatile("cp.async.bulk.prefetch.L2.global [%0], %1;" :: "l"(src), "r"(bytes) : "memory");
}
__device__ __forceinline__ bool elect_one() {
    uint32_t p;
    asm volatile("{\n.reg .pred P;\nelect.sync _|P, 0xffffffff;\nselp.u32 %0, 1, 0, P;\n}" : "=r"(p));
    return p != 0;
}
__device__ __forceinline__ void wgmma_fence() { asm volatile("wgmma.fence.sync.aligned;" ::: "memory"); }
__device__ __forceinline__ void wgmma_commit() { asm volatile("wgmma.commit_group.sync.aligned;" ::: "memory"); }
template <int N> __device__ __forceinline__ void wgmma_wait() { asm volatile("wgmma.wait_group.sync.aligned %0;" :: "n"(N) : "memory"); }
__device__ __forceinline__ void fence_async_smem() { asm volatile("fence.proxy.async.shared::cta;" ::: "memory"); }
__device__ __forceinline__ uint64_t desc_a(uint32_t addr) {
    return (uint64_t)((addr & 0x3FFFF) >> 4) | ((uint64_t)1 << 16) | ((uint64_t)(1024 >> 4) << 32) | ((uint64_t)1 << 62);
}
__device__ __forceinline__ uint64_t desc_b(uint32_t addr) {
    return (uint64_t)((addr & 0x3FFFF) >> 4) | ((uint64_t)(4096 >> 4) << 16) | ((uint64_t)(1024 >> 4) << 32) | ((uint64_t)1 << 62);
}
__device__ __forceinline__ uint32_t pack_bf16(float lo, float hi) {
    uint32_t r; asm("cvt.rn.bf16x2.f32 %0, %1, %2;" : "=r"(r) : "f"(hi), "f"(lo)); return r;
}
__device__ __forceinline__ uint32_t pack_bf16_relu(float lo, float hi) {
    uint32_t r; asm("cvt.rn.relu.bf16x2.f32 %0, %1, %2;" : "=r"(r) : "f"(hi), "f"(lo)); return r;
}
__device__ __forceinline__ uint32_t movmatrix(uint32_t a) {
    uint32_t d; asm volatile("movmatrix.sync.aligned.m8n8.trans.b16 %0, %1;" : "=r"(d) : "r"(a)); return d;
}
__device__ __forceinline__ void stmatrix_x4(uint32_t addr, uint32_t r0, uint32_t r1, uint32_t r2, uint32_t r3) {
    asm volatile("stmatrix.sync.aligned.m8n8.x4.shared.b16 [%0], {%1, %2, %3, %4};" :: "r"(addr), "r"(r0), "r"(r1), "r"(r2), "r"(r3) : "memory");
}
__device__ __forceinline__ uint4 lds128(uint32_t addr) {
    uint4 v; asm volatile("ld.shared.v4.b32 {%0, %1, %2, %3}, [%4];" : "=r"(v.x), "=r"(v.y), "=r"(v.z), "=r"(v.w) : "r"(addr) : "memory"); return v;
}
__device__ __forceinline__ void mma16816(float (&c)[4], uint32_t a0, uint32_t a1, uint32_t a2, uint32_t a3, uint32_t b0, uint32_t b1) {
    asm volatile("mma.sync.aligned.m16n8k16.row.col.f32.bf16.bf16.f32 {%0,%1,%2,%3}, {%4,%5,%6,%7}, {%8,%9}, {%0,%1,%2,%3};"
        : "+f"(c[0]), "+f"(c[1]), "+f"(c[2]), "+f"(c[3]) : "r"(a0), "r"(a1), "r"(a2), "r"(a3), "r"(b0), "r"(b1));
}
__device__ __forceinline__ void mma16816_c(float (&c)[4], uint32_t a0, uint32_t a1, uint32_t a2, uint32_t a3, uint32_t b0, uint32_t b1, float ci) {
    asm volatile("mma.sync.aligned.m16n8k16.row.col.f32.bf16.bf16.f32 {%0,%1,%2,%3}, {%4,%5,%6,%7}, {%8,%9}, {%10,%10,%10,%10};"
        : "=f"(c[0]), "=f"(c[1]), "=f"(c[2]), "=f"(c[3]) : "r"(a0), "r"(a1), "r"(a2), "r"(a3), "r"(b0), "r"(b1), "f"(ci));
}
__device__ __forceinline__ int opaque(int v) { asm volatile("" : "+r"(v)); return v; }
__device__ __forceinline__ float ex2(float x) { float y; asm("ex2.approx.ftz.f32 %0, %1;" : "=f"(y) : "f"(x)); return y; }
__device__ __forceinline__ unsigned ld_acquire(const unsigned* p) {
    unsigned v; asm volatile("ld.acquire.gpu.global.u32 %0, [%1];" : "=r"(v) : "l"(p) : "memory"); return v;
}
__device__ __forceinline__ void red_release(unsigned* p, unsigned v) {
    asm volatile("red.release.gpu.global.add.u32 [%0], %1;" :: "l"(p), "r"(v) : "memory");
}
__device__ __forceinline__ void wait_counter(const unsigned* p, unsigned target) {
    uint32_t n = 0;
    while ((int)(ld_acquire(p) - target) < 0) { if (++n > (1u << 20)) break; }
}
__device__ __forceinline__ uint4 ldg_weak(const uint4* p) {
    uint4 v; asm volatile("ld.global.L1::no_allocate.v4.b32 {%0, %1, %2, %3}, [%4];" : "=r"(v.x), "=r"(v.y), "=r"(v.z), "=r"(v.w) : "l"(p) : "memory"); return v;
}
__device__ __forceinline__ float bf_lo(uint32_t v) { return __uint_as_float(v << 16); }
__device__ __forceinline__ float bf_hi(uint32_t v) { return __uint_as_float(v & 0xFFFF0000u); }

__device__ __forceinline__ void wgmma_ss_n64(float (&d)[32], uint64_t da, uint64_t db, int scale_d) {
    asm volatile("{\n.reg .pred p;\nsetp.ne.b32 p, %34, 0;\n"
        "wgmma.mma_async.sync.aligned.m64n64k16.f32.bf16.bf16 {%0, %1, %2, %3, %4, %5, %6, %7, %8, %9, %10, %11, %12, %13, %14, %15, %16, %17, %18, %19, %20, %21, %22, %23, %24, %25, %26, %27, %28, %29, %30, %31}, %32, %33, p, 1, 1, 0, 1;\n}\n"
        : "+f"(d[0]), "+f"(d[1]), "+f"(d[2]), "+f"(d[3]), "+f"(d[4]), "+f"(d[5]), "+f"(d[6]), "+f"(d[7]), "+f"(d[8]), "+f"(d[9]), "+f"(d[10]), "+f"(d[11]), "+f"(d[12]), "+f"(d[13]), "+f"(d[14]), "+f"(d[15]), "+f"(d[16]), "+f"(d[17]), "+f"(d[18]), "+f"(d[19]), "+f"(d[20]), "+f"(d[21]), "+f"(d[22]), "+f"(d[23]), "+f"(d[24]), "+f"(d[25]), "+f"(d[26]), "+f"(d[27]), "+f"(d[28]), "+f"(d[29]), "+f"(d[30]), "+f"(d[31])
        : "l"(da), "l"(db), "r"(scale_d));
}
__device__ __forceinline__ void wgmma_ss_n128(float (&d)[64], uint64_t da, uint64_t db, int scale_d) {
    asm volatile("{\n.reg .pred p;\nsetp.ne.b32 p, %66, 0;\n"
        "wgmma.mma_async.sync.aligned.m64n128k16.f32.bf16.bf16 {%0, %1, %2, %3, %4, %5, %6, %7, %8, %9, %10, %11, %12, %13, %14, %15, %16, %17, %18, %19, %20, %21, %22, %23, %24, %25, %26, %27, %28, %29, %30, %31, %32, %33, %34, %35, %36, %37, %38, %39, %40, %41, %42, %43, %44, %45, %46, %47, %48, %49, %50, %51, %52, %53, %54, %55, %56, %57, %58, %59, %60, %61, %62, %63}, %64, %65, p, 1, 1, 0, 1;\n}\n"
        : "+f"(d[0]), "+f"(d[1]), "+f"(d[2]), "+f"(d[3]), "+f"(d[4]), "+f"(d[5]), "+f"(d[6]), "+f"(d[7]), "+f"(d[8]), "+f"(d[9]), "+f"(d[10]), "+f"(d[11]), "+f"(d[12]), "+f"(d[13]), "+f"(d[14]), "+f"(d[15]), "+f"(d[16]), "+f"(d[17]), "+f"(d[18]), "+f"(d[19]), "+f"(d[20]), "+f"(d[21]), "+f"(d[22]), "+f"(d[23]), "+f"(d[24]), "+f"(d[25]), "+f"(d[26]), "+f"(d[27]), "+f"(d[28]), "+f"(d[29]), "+f"(d[30]), "+f"(d[31]), "+f"(d[32]), "+f"(d[33]), "+f"(d[34]), "+f"(d[35]), "+f"(d[36]), "+f"(d[37]), "+f"(d[38]), "+f"(d[39]), "+f"(d[40]), "+f"(d[41]), "+f"(d[42]), "+f"(d[43]), "+f"(d[44]), "+f"(d[45]), "+f"(d[46]), "+f"(d[47]), "+f"(d[48]), "+f"(d[49]), "+f"(d[50]), "+f"(d[51]), "+f"(d[52]), "+f"(d[53]), "+f"(d[54]), "+f"(d[55]), "+f"(d[56]), "+f"(d[57]), "+f"(d[58]), "+f"(d[59]), "+f"(d[60]), "+f"(d[61]), "+f"(d[62]), "+f"(d[63])
        : "l"(da), "l"(db), "r"(scale_d));
}
__device__ __forceinline__ void wgmma_ss_n200(float (&d)[100], uint64_t da, uint64_t db, int scale_d) {
    asm volatile("{\n.reg .pred p;\nsetp.ne.b32 p, %102, 0;\n"
        "wgmma.mma_async.sync.aligned.m64n200k16.f32.bf16.bf16 {%0, %1, %2, %3, %4, %5, %6, %7, %8, %9, %10, %11, %12, %13, %14, %15, %16, %17, %18, %19, %20, %21, %22, %23, %24, %25, %26, %27, %28, %29, %30, %31, %32, %33, %34, %35, %36, %37, %38, %39, %40, %41, %42, %43, %44, %45, %46, %47, %48, %49, %50, %51, %52, %53, %54, %55, %56, %57, %58, %59, %60, %61, %62, %63, %64, %65, %66, %67, %68, %69, %70, %71, %72, %73, %74, %75, %76, %77, %78, %79, %80, %81, %82, %83, %84, %85, %86, %87, %88, %89, %90, %91, %92, %93, %94, %95, %96, %97, %98, %99}, %100, %101, p, 1, 1, 0, 1;\n}\n"
        : "+f"(d[0]), "+f"(d[1]), "+f"(d[2]), "+f"(d[3]), "+f"(d[4]), "+f"(d[5]), "+f"(d[6]), "+f"(d[7]), "+f"(d[8]), "+f"(d[9]), "+f"(d[10]), "+f"(d[11]), "+f"(d[12]), "+f"(d[13]), "+f"(d[14]), "+f"(d[15]), "+f"(d[16]), "+f"(d[17]), "+f"(d[18]), "+f"(d[19]), "+f"(d[20]), "+f"(d[21]), "+f"(d[22]), "+f"(d[23]), "+f"(d[24]), "+f"(d[25]), "+f"(d[26]), "+f"(d[27]), "+f"(d[28]), "+f"(d[29]), "+f"(d[30]), "+f"(d[31]), "+f"(d[32]), "+f"(d[33]), "+f"(d[34]), "+f"(d[35]), "+f"(d[36]), "+f"(d[37]), "+f"(d[38]), "+f"(d[39]), "+f"(d[40]), "+f"(d[41]), "+f"(d[42]), "+f"(d[43]), "+f"(d[44]), "+f"(d[45]), "+f"(d[46]), "+f"(d[47]), "+f"(d[48]), "+f"(d[49]), "+f"(d[50]), "+f"(d[51]), "+f"(d[52]), "+f"(d[53]), "+f"(d[54]), "+f"(d[55]), "+f"(d[56]), "+f"(d[57]), "+f"(d[58]), "+f"(d[59]), "+f"(d[60]), "+f"(d[61]), "+f"(d[62]), "+f"(d[63]), "+f"(d[64]), "+f"(d[65]), "+f"(d[66]), "+f"(d[67]), "+f"(d[68]), "+f"(d[69]), "+f"(d[70]), "+f"(d[71]), "+f"(d[72]), "+f"(d[73]), "+f"(d[74]), "+f"(d[75]), "+f"(d[76]), "+f"(d[77]), "+f"(d[78]), "+f"(d[79]), "+f"(d[80]), "+f"(d[81]), "+f"(d[82]), "+f"(d[83]), "+f"(d[84]), "+f"(d[85]), "+f"(d[86]), "+f"(d[87]), "+f"(d[88]), "+f"(d[89]), "+f"(d[90]), "+f"(d[91]), "+f"(d[92]), "+f"(d[93]), "+f"(d[94]), "+f"(d[95]), "+f"(d[96]), "+f"(d[97]), "+f"(d[98]), "+f"(d[99])
        : "l"(da), "l"(db), "r"(scale_d));
}
__device__ __forceinline__ void wgmma_ss_n224(float (&d)[112], uint64_t da, uint64_t db, int scale_d) {
    asm volatile("{\n.reg .pred p;\nsetp.ne.b32 p, %114, 0;\n"
        "wgmma.mma_async.sync.aligned.m64n224k16.f32.bf16.bf16 {%0, %1, %2, %3, %4, %5, %6, %7, %8, %9, %10, %11, %12, %13, %14, %15, %16, %17, %18, %19, %20, %21, %22, %23, %24, %25, %26, %27, %28, %29, %30, %31, %32, %33, %34, %35, %36, %37, %38, %39, %40, %41, %42, %43, %44, %45, %46, %47, %48, %49, %50, %51, %52, %53, %54, %55, %56, %57, %58, %59, %60, %61, %62, %63, %64, %65, %66, %67, %68, %69, %70, %71, %72, %73, %74, %75, %76, %77, %78, %79, %80, %81, %82, %83, %84, %85, %86, %87, %88, %89, %90, %91, %92, %93, %94, %95, %96, %97, %98, %99, %100, %101, %102, %103, %104, %105, %106, %107, %108, %109, %110, %111}, %112, %113, p, 1, 1, 0, 1;\n}\n"
        : "+f"(d[0]), "+f"(d[1]), "+f"(d[2]), "+f"(d[3]), "+f"(d[4]), "+f"(d[5]), "+f"(d[6]), "+f"(d[7]), "+f"(d[8]), "+f"(d[9]), "+f"(d[10]), "+f"(d[11]), "+f"(d[12]), "+f"(d[13]), "+f"(d[14]), "+f"(d[15]), "+f"(d[16]), "+f"(d[17]), "+f"(d[18]), "+f"(d[19]), "+f"(d[20]), "+f"(d[21]), "+f"(d[22]), "+f"(d[23]), "+f"(d[24]), "+f"(d[25]), "+f"(d[26]), "+f"(d[27]), "+f"(d[28]), "+f"(d[29]), "+f"(d[30]), "+f"(d[31]), "+f"(d[32]), "+f"(d[33]), "+f"(d[34]), "+f"(d[35]), "+f"(d[36]), "+f"(d[37]), "+f"(d[38]), "+f"(d[39]), "+f"(d[40]), "+f"(d[41]), "+f"(d[42]), "+f"(d[43]), "+f"(d[44]), "+f"(d[45]), "+f"(d[46]), "+f"(d[47]), "+f"(d[48]), "+f"(d[49]), "+f"(d[50]), "+f"(d[51]), "+f"(d[52]), "+f"(d[53]), "+f"(d[54]), "+f"(d[55]), "+f"(d[56]), "+f"(d[57]), "+f"(d[58]), "+f"(d[59]), "+f"(d[60]), "+f"(d[61]), "+f"(d[62]), "+f"(d[63]), "+f"(d[64]), "+f"(d[65]), "+f"(d[66]), "+f"(d[67]), "+f"(d[68]), "+f"(d[69]), "+f"(d[70]), "+f"(d[71]), "+f"(d[72]), "+f"(d[73]), "+f"(d[74]), "+f"(d[75]), "+f"(d[76]), "+f"(d[77]), "+f"(d[78]), "+f"(d[79]), "+f"(d[80]), "+f"(d[81]), "+f"(d[82]), "+f"(d[83]), "+f"(d[84]), "+f"(d[85]), "+f"(d[86]), "+f"(d[87]), "+f"(d[88]), "+f"(d[89]), "+f"(d[90]), "+f"(d[91]), "+f"(d[92]), "+f"(d[93]), "+f"(d[94]), "+f"(d[95]), "+f"(d[96]), "+f"(d[97]), "+f"(d[98]), "+f"(d[99]), "+f"(d[100]), "+f"(d[101]), "+f"(d[102]), "+f"(d[103]), "+f"(d[104]), "+f"(d[105]), "+f"(d[106]), "+f"(d[107]), "+f"(d[108]), "+f"(d[109]), "+f"(d[110]), "+f"(d[111])
        : "l"(da), "l"(db), "r"(scale_d));
}
template <int N> __device__ __forceinline__ void fence_acc(float (&d)[N]) {
#pragma unroll
    for (int i = 0; i < N; i++) asm volatile("" : "+f"(d[i]) :: "memory");
}

__device__ __forceinline__ void bulk_s2g(void* dst, uint32_t src, uint32_t bytes) {
    asm volatile("cp.async.bulk.global.shared::cta.bulk_group [%0], [%1], %2;" :: "l"(dst), "r"(src), "r"(bytes) : "memory");
}
__device__ __forceinline__ void sts128(uint32_t addr, uint4 v) {
    asm volatile("st.shared.v4.b32 [%0], {%1, %2, %3, %4};" :: "r"(addr), "r"(v.x), "r"(v.y), "r"(v.z), "r"(v.w) : "memory");
}
__device__ __forceinline__ void sum_partials(uint32_t sb, int ti, int tj, int lane) {
    for (;;) {
        uint32_t item = 0;
        if (lane == 0) asm volatile("atom.shared.add.u32 %0, [%1], 1;" : "=r"(item) : "r"(sb + ITEM_OFF) : "memory");
        item = __shfl_sync(0xffffffffu, item, 0);
        if (item >= 16) break;
        const uint4* p = g_part + (size_t)((ti * 8 + tj) * 8) * 1024 + item * 64 + lane;
        uint4 v[2][8];
#pragma unroll
        for (int s = 0; s < 8; s++) { v[0][s] = ldg_weak(p + s * 1024); v[1][s] = ldg_weak(p + s * 1024 + 32); }
#pragma unroll
        for (int n = 0; n < 2; n++) {
            float a[8];
#pragma unroll
            for (int e = 0; e < 8; e++) a[e] = 0.f;
#pragma unroll
            for (int s = 0; s < 8; s++) {
                a[0] += bf_lo(v[n][s].x); a[1] += bf_hi(v[n][s].x); a[2] += bf_lo(v[n][s].y); a[3] += bf_hi(v[n][s].y);
                a[4] += bf_lo(v[n][s].z); a[5] += bf_hi(v[n][s].z); a[6] += bf_lo(v[n][s].w); a[7] += bf_hi(v[n][s].w);
            }
            const uint32_t d = sb + STG_OFF + (item * 4 + n * 2) * 512 + lane * 16;
            sts128(d, make_uint4(__float_as_uint(a[0]), __float_as_uint(a[1]), __float_as_uint(a[2]), __float_as_uint(a[3])));
            sts128(d + 512, make_uint4(__float_as_uint(a[4]), __float_as_uint(a[5]), __float_as_uint(a[6]), __float_as_uint(a[7])));
        }
    }
    __syncwarp();
    if (lane == 0) mbar_arrive(sb + B_HSUM);
}

#define PWAIT() mbar_wait(sb + B_EMPTY + 8 * r.slot, r.phase)
#define CWAIT() do { if (!dry) mbar_wait(sb + B_FULL + 8 * r.slot, r.phase); } while (0)
template <bool B> struct BoolTag { static constexpr bool value = B; };
struct Ring {
    int slot; uint32_t phase;
    __device__ __forceinline__ void next() { if (++slot == RING) { slot = 0; phase ^= 1; } }
};

__global__ void __launch_bounds__(384, 1)
fused_kernel(const __grid_constant__ CUtensorMap map_x, const __grid_constant__ CUtensorMap map_qkv,
             const __grid_constant__ CUtensorMap map_w1, const __grid_constant__ CUtensorMap map_w2,
             const __grid_constant__ CUtensorMap map_wo, const __grid_constant__ CUtensorMap map_w1a,
             const __grid_constant__ CUtensorMap map_o,
             const __nv_bfloat16* __restrict__ gate_w, __nv_bfloat16* __restrict__ out,
             const uint8_t* __restrict__ w1p, const uint8_t* __restrict__ w2p, const uint8_t* __restrict__ wop)
{
    extern __shared__ __align__(1024) uint8_t smem_raw[];
    const uint32_t sb = smem_u32(smem_raw);
    const int tid = threadIdx.x, warp = tid >> 5, lane = tid & 31;
    const bool dry = blockIdx.x >= 128;
    const int ti = dry ? (int)(blockIdx.x & 1) * 2 : blockIdx.x >> 3, tj = blockIdx.x & 7;
    if (dry && warp >= 8) {
        asm volatile("setmaxnreg.dec.sync.aligned.u32 88;");
        return;
    }

    if (tid == 0 && !dry) { TSG(31); TSX(0); }
    if (tid == 320) {
        asm volatile("prefetch.tensormap [%0];" :: "l"(&map_x) : "memory");
        asm volatile("prefetch.tensormap [%0];" :: "l"(&map_qkv) : "memory");
        asm volatile("prefetch.tensormap [%0];" :: "l"(&map_w1) : "memory");
        asm volatile("prefetch.tensormap [%0];" :: "l"(&map_w1a) : "memory");
        asm volatile("prefetch.tensormap [%0];" :: "l"(&map_w2) : "memory");
        asm volatile("prefetch.tensormap [%0];" :: "l"(&map_wo) : "memory");
        asm volatile("prefetch.tensormap [%0];" :: "l"(&map_o) : "memory");
    }
    uint32_t gwv[N_QKV / 2];
    if (warp == 8) {
        const unsigned short* gws = reinterpret_cast<const unsigned short*>(gate_w);
#pragma unroll
        for (int n = 0; n < N_QKV / 2; n++) gwv[n] = (uint32_t)__ldg(gws + 64 * n + lane) | ((uint32_t)__ldg(gws + 64 * n + 32 + lane) << 16);
    }
    if (tid == 256) {
        for (int s = 0; s < RING; s++) { mbar_init(sb + B_FULL + 8 * s, 1); mbar_init(sb + B_EMPTY + 8 * s, 8); }
        for (int s = 0; s < 8; s++) mbar_init(sb + B_XFULL + 8 * s, 1);
        mbar_init(sb + B_HDEAD, 8); mbar_init(sb + B_EREADY, 1); mbar_init(sb + B_KVDONE, 8); mbar_init(sb + B_KVREADY, 1);
        mbar_init(sb + B_ODONE, 8); mbar_init(sb + B_WOFULL, 1); mbar_init(sb + B_HSUM, 3);
        mbar_init(sb + B_PREADY, 1); mbar_init(sb + B_SF, 1); mbar_init(sb + B_SF + 8, 1);
        for (int s = 0; s < 4; s++) mbar_init(sb + B_SQ + 8 * s, 8);
        asm volatile("st.shared.u32 [%0], %1;" :: "r"(sb + ITEM_OFF), "r"(0) : "memory");
        asm volatile("fence.mbarrier_init.release.cluster;" ::: "memory");
        fence_async_smem();
        mbar_expect_tx(sb + B_XFULL, 16384);
        tma_2d(sb + X_OFF, &map_x, sb + B_XFULL, 0, ti * 128);
        mbar_expect_only(sb + B_FULL, 12288);
        tma_4d(sb + RING_OFF, &map_qkv, sb + B_FULL, 0, 0, tj, 0);
    }
    if (!dry) __syncthreads();

    if (warp >= 8) {
        asm volatile("setmaxnreg.dec.sync.aligned.u32 88;");
        if (warp == 8) {
            Ring r{0, 1};
            const bool leader = elect_one();
#pragma unroll
            for (int n = 0; n < N_QKV; n++) {
                const uint32_t full = sb + B_FULL + 8 * r.slot, dst = sb + RING_OFF + r.slot * SLOT;
                if (n > 0) {
                    if (!(n & 1) && leader) {
                        mbar_expect_tx(sb + B_XFULL + 8 * (n >> 1), 16384);
                        tma_2d(sb + X_OFF + (n >> 1) * 16384, &map_x, sb + B_XFULL + 8 * (n >> 1), (n >> 1) * 64, ti * 128);
                    }
                    if (n >= RING) PWAIT();
                    if (leader) {
                        mbar_expect_only(full, 12288);
                        tma_4d(dst, &map_qkv, full, 0, 32 * n, tj, 0);
                    }
                }
                const uint32_t gv = (n & 1) ? (gwv[n >> 1] >> 16) : (gwv[n >> 1] & 0xFFFFu);
                asm volatile("st.shared.v4.b32 [%0], {%1, %2, %2, %2};" :: "r"(dst + 12288 + lane * 128 + ((lane & 7) << 4)), "r"(gv), "r"(0) : "memory");
                fence_async_smem();
                __syncwarp();
                if (leader) mbar_arrive(full);
                r.next();
            }
#pragma unroll 1
            for (int n = 0; n < N_FFN1; n++) {
                const uint32_t full = sb + B_FULL + 8 * r.slot, dst = sb + RING_OFF + r.slot * SLOT;
                PWAIT();
                if (leader) {
                    mbar_expect_tx(full, 16384);
                    tma_4d(dst, &map_w1a, full, 0, 32 * n, 0, tj);
                    tma_2d(dst + 3 * 4096, &map_w1, full, 224 * tj + 192, 32 * n);
                }
                r.next();
            }
            {
                int q = 0, rr = 0;
#pragma unroll 1
                for (int n = 0; n < N_FFN2; n++) {
                    const uint32_t full = sb + B_FULL + 8 * r.slot, dst = sb + RING_OFF + r.slot * SLOT;
                    PWAIT();
                    if (leader) mbar_expect_tx(full, 16384);
#pragma unroll
                    for (int h = 0; h < 2; h++) {
                        if (leader) tma_3d(dst + h * 8192, &map_w2, full, 0, 224 * tj + 32 * rr, 2 * q);
                        if (++rr == 7) { rr = 0; q++; }
                    }
                    r.next();
                }
            }
            mbar_wait(sb + B_KVREADY, 0);
            asm volatile("fence.proxy.async.global;" ::: "memory");
            {
                const int bbase = 8 * ti - 16, b0 = bbase < 0 ? 0 : bbase;
                const uint32_t bytes = (uint32_t)(8 * ti + 8 - b0) * 512;
#pragma unroll 1
                for (int m = 0; m < N_KV; m++) {
                    const uint32_t full = sb + B_FULL + 8 * r.slot, dst = sb + RING_OFF + r.slot * SLOT;
                    if (m == RING) {
                        mbar_wait(sb + B_HDEAD, 0);
                        if (leader) {
                            mbar_expect_tx(sb + B_WOFULL, 65536);
#pragma unroll
                            for (int e = 0; e < 2; e++) tma_2d(sb + X_OFF + e * 32768, &map_wo, sb + B_WOFULL, 64 * tj, 256 * e);
                        }
                    }
                    PWAIT();
                    if (leader) {
                        const uint4* src = ((m & 1) ? g_vf : g_kf) + ((tj * 4 + (m >> 1)) * 128 + b0) * 32;
                        mbar_expect_tx(full, bytes);
                        bulk_g2s(dst + (b0 - bbase) * 512, src, bytes, full);
                    }
                    r.next();
                }
            }
            {
                mbar_wait(sb + B_EREADY, 0);
                unsigned epoch; asm volatile("ld.shared.u32 %0, [%1];" : "=r"(epoch) : "r"(sb + EPOCH_OFF) : "memory");
                mbar_wait(sb + B_ODONE, 0);
                if (leader) red_release(&g_ocnt[blockIdx.x * 32], 1u);
                __syncwarp();
                if (lane < 8) wait_counter(&g_ocnt[(ti * 8 + lane) * 32], epoch + 1);
                __syncwarp();
                asm volatile("fence.proxy.async.global;" ::: "memory");
#pragma unroll 1
                for (int m = 0; m < N_O; m++) {
                    const uint32_t full = sb + B_FULL + 8 * r.slot, dst = sb + RING_OFF + r.slot * SLOT;
                    PWAIT();
                    if (leader) {
                        mbar_expect_tx(full, 16384);
                        tma_2d(dst, &map_o, full, 64 * ((tj + m) & 7), ti * 128);
                    }
                    r.next();
                }
            }
        } else if (warp == 9) {
            unsigned epoch = 0;
            if (lane == 0) {
                epoch = atomicAdd(&g_ticket, 1u) >> 7;
                asm volatile("st.shared.u32 [%0], %1;" :: "r"(sb + EPOCH_OFF), "r"(epoch) : "memory");
                mbar_arrive(sb + B_EREADY);
                mbar_wait(sb + B_XFULL + 8 * PF1_AT, 0);
                prefetch_l2(w1p + (size_t)blockIdx.x * 14336, 14336);
                mbar_wait(sb + B_XFULL + 8 * PF2_AT, 0);
                prefetch_l2(w2p + (size_t)blockIdx.x * 14336, 14336);
                prefetch_l2(wop + (size_t)blockIdx.x * 4096, 4096);
                mbar_wait(sb + B_KVDONE, 0);
                red_release(&g_kvcnt[blockIdx.x * 32], 1u);
            }
            epoch = __shfl_sync(0xffffffffu, epoch, 0);
            if (lane < 3 && ti - lane >= 0) wait_counter(&g_kvcnt[((ti - lane) * 8 + tj) * 32], epoch + 1);
            __syncwarp();
            if (lane == 0) mbar_arrive(sb + B_KVREADY);
            mbar_wait(sb + B_SQ + 24, 0);
            if (lane < 8) wait_counter(&g_pcnt[(ti * 8 + lane) * 32], epoch + 1);
            __syncwarp();
            if (lane == 0) { mbar_arrive(sb + B_PREADY); TSX(13); }
            sum_partials(sb, ti, tj, lane);
            if (lane == 0) TSX(14);
        } else {
            if (warp == 10) {
#pragma unroll 1
                for (int q = 0; q < 4; q++) {
                    mbar_wait(sb + B_SQ + 8 * q, 0);
                    if (lane < 16) {
                        uint4* d = g_part + (size_t)(((ti * 8 + 2 * q + (lane & 1)) * 8 + tj) * 8 + (lane >> 1)) * 128;
                        bulk_s2g(d, sb + STG_OFF + (q & 1) * 32768 + lane * 2048, 2048);
                        asm volatile("cp.async.bulk.commit_group;" ::: "memory");
                        if (q < 2) asm volatile("cp.async.bulk.wait_group.read 0;" ::: "memory");
                    }
                    __syncwarp();
                    if (q < 2 && lane == 0) mbar_arrive(sb + B_SF + 8 * q);
                }
                asm volatile("cp.async.bulk.wait_group 0;" ::: "memory");
                asm volatile("fence.proxy.async.global;" ::: "memory");
                __syncwarp();
                if (lane == 0) { red_release(&g_pcnt[blockIdx.x * 32], 1u); TSX(12); }
            }
            mbar_wait(sb + B_PREADY, 0);
            sum_partials(sb, ti, tj, lane);
        }
    } else {
        asm volatile("setmaxnreg.inc.sync.aligned.u32 208;");
        const int wg = warp >> 2, g = lane >> 2, c = lane & 3;
        const uint32_t xa = sb + X_OFF + wg * 8192;
        Ring r{0, 0};
        const bool lane0 = lane == 0 && !dry;
        uint32_t qf[4][4];
        float g0, g1;
        TS(9);
        {
            float acc[100];
            int prev = 0;
            if (wg == 1) asm volatile("bar.sync 3, 256;" ::: "memory");
            for (int s = 0; s < (dry ? 4 : N_QKV); s++) {
                if (!(s & 1) && !dry) mbar_wait(sb + B_XFULL + 8 * (s >> 1), 0);
                CWAIT();
                if (s == 0) TS(1);
                if (s == 2) TS(28);
                if (s == 6) TS(29);
                if (s == 10) TS(20);
                const uint32_t bs = sb + RING_OFF + r.slot * SLOT, as = xa + (s >> 1) * 16384 + (s & 1) * 64;
                wgmma_fence();
                wgmma_ss_n200(acc, desc_a(as), desc_b(bs), s);
                wgmma_ss_n200(acc, desc_a(as + 32), desc_b(bs + 2048), 1);
                wgmma_commit();
                if (wg == 0 && s == LEAD1) asm volatile("bar.arrive 3, 256;" ::: "memory");
                if (s > 0) { wgmma_wait<1>(); if (lane0) mbar_arrive(sb + B_EMPTY + 8 * prev); }
                prev = r.slot; r.next();
            }
            wgmma_wait<0>();
            fence_acc(acc);
            if (lane0) mbar_arrive(sb + B_EMPTY + 8 * prev);
            TS(2);
            const int blk = ti * 8 + warp;
#pragma unroll
            for (int hh = 0; hh < 4; hh++) {
                const float* t0 = &acc[8 * hh]; const float* t1 = &acc[8 * hh + 4];
                qf[hh][0] = pack_bf16(t0[0], t0[1]); qf[hh][1] = pack_bf16(t0[2], t0[3]);
                qf[hh][2] = pack_bf16(t1[0], t1[1]); qf[hh][3] = pack_bf16(t1[2], t1[3]);
                const float* k0 = &acc[32 + 8 * hh]; const float* k1 = &acc[32 + 8 * hh + 4];
                uint4 kv;
                kv.x = pack_bf16(k0[0], k0[1]); kv.y = pack_bf16(k1[0], k1[1]);
                kv.z = pack_bf16(k0[2], k0[3]); kv.w = pack_bf16(k1[2], k1[3]);
                if (!dry) g_kf[((tj * 4 + hh) * 128 + blk) * 32 + lane] = kv;
                const float* v0 = &acc[64 + 8 * hh]; const float* v1 = &acc[64 + 8 * hh + 4];
                uint4 vv;
                vv.x = movmatrix(pack_bf16(v0[0], v0[1])); vv.y = movmatrix(pack_bf16(v0[2], v0[3]));
                vv.z = movmatrix(pack_bf16(v1[0], v1[1])); vv.w = movmatrix(pack_bf16(v1[2], v1[3]));
                if (!dry) g_vf[((tj * 4 + hh) * 128 + blk) * 32 + lane] = vv;
            }
            __syncwarp();
            if (lane0) mbar_arrive(sb + B_KVDONE);
            const float z0 = __shfl_sync(0xffffffffu, acc[96], lane & ~3), z1 = __shfl_sync(0xffffffffu, acc[98], lane & ~3);
            g0 = 1.f / (1.f + __expf(-z0)); g1 = 1.f / (1.f + __expf(-z1));
        }
        TS(3);
        const int wrow = (warp & 3) * 16;
        {
            float acc[112];
            int prev = 0;
            for (int s = 0; s < (dry ? 4 : N_FFN1); s++) {
                CWAIT();
                const uint32_t bs = sb + RING_OFF + r.slot * SLOT, as = xa + (s >> 1) * 16384 + (s & 1) * 64;
                wgmma_fence();
                wgmma_ss_n224(acc, desc_a(as), desc_b(bs), s);
                wgmma_ss_n224(acc, desc_a(as + 32), desc_b(bs + 2048), 1);
                wgmma_commit();
                if (s > 0) { wgmma_wait<1>(); if (lane0) mbar_arrive(sb + B_EMPTY + 8 * prev); }
                prev = r.slot; r.next();
            }
            wgmma_wait<0>();
            fence_acc(acc);
            if (lane0) mbar_arrive(sb + B_EMPTY + 8 * prev);
            TS(4);
            const float s0 = 1.f - g0, s1 = 1.f - g1;
            asm volatile("bar.sync %0, 128;" :: "r"(1 + wg) : "memory");
            const uint32_t strow = xa + (wrow + ((lane >> 3) & 1) * 8 + (lane & 7)) * 128;
#pragma unroll
            for (int p = 0; p < 14; p++) {
                const int nt = 2 * p + (lane >> 4);
                const float* a = &acc[8 * p];
                stmatrix_x4(strow + (p >> 2) * 16384 + (((nt & 7) ^ (lane & 7)) << 4),
                            pack_bf16_relu(a[0] * s0, a[1] * s0), pack_bf16_relu(a[2] * s1, a[3] * s1),
                            pack_bf16_relu(a[4] * s0, a[5] * s0), pack_bf16_relu(a[6] * s1, a[7] * s1));
            }
        }
        TS(5);
        {
            fence_async_smem();
            asm volatile("bar.sync 4, 256;" ::: "memory");
            float accA[64], accB[64];
            auto epilogue = [&](float (&acc)[64], int q) {
                fence_acc(acc);
                const uint32_t st = sb + STG_OFF + (q & 1) * 32768 + warp * 4096;
                if (q >= 2 && !dry) mbar_wait(sb + B_SF + 8 * (q & 1), 0);
#pragma unroll
                for (int t2 = 0; t2 < 8; t2++) {
                    uint4 v;
                    v.x = pack_bf16(acc[8 * t2 + 0], acc[8 * t2 + 1]); v.y = pack_bf16(acc[8 * t2 + 2], acc[8 * t2 + 3]);
                    v.z = pack_bf16(acc[8 * t2 + 4], acc[8 * t2 + 5]); v.w = pack_bf16(acc[8 * t2 + 6], acc[8 * t2 + 7]);
                    sts128(st + t2 * 512 + lane * 16, v);
                }
                fence_async_smem();
                __syncwarp();
                if (lane0) mbar_arrive(sb + B_SQ + 8 * q);
            };
            int rel = r.slot;
#pragma unroll
            for (int m = 0; m < N_FFN2; m++) {
                CWAIT();
                wgmma_fence();
#pragma unroll
                for (int h = 0; h < 2; h++) {
                    const int u = 2 * m + h, q = u / 7, rr = u % 7;
                    const uint32_t bs = sb + RING_OFF + r.slot * SLOT + h * 8192;
                    const uint32_t as = xa + (rr >> 1) * 16384 + (rr & 1) * 64;
                    if (!(q & 1)) {
                        wgmma_ss_n128(accA, desc_a(as), desc_b(bs), rr);
                        wgmma_ss_n128(accA, desc_a(as + 32), desc_b(bs + 2048), 1);
                    } else {
                        wgmma_ss_n128(accB, desc_a(as), desc_b(bs), rr);
                        wgmma_ss_n128(accB, desc_a(as + 32), desc_b(bs + 2048), 1);
                    }
                }
                wgmma_commit();
                r.next();
                wgmma_wait<1>();
                if (m > 0) {
                    if (lane0) mbar_arrive(sb + B_EMPTY + 8 * rel);
                    if (++rel == RING) rel = 0;
                }
                if (m == 4) { TS(25); epilogue(accA, 0); }
                if (m == 7) { TS(26); epilogue(accB, 1); }
                if (m == 11) { TS(27); epilogue(accA, 2); }
            }
            wgmma_wait<0>();
            if (lane0) { mbar_arrive(sb + B_EMPTY + 8 * rel); mbar_arrive(sb + B_HDEAD); }
            epilogue(accB, 3);
        }
        TS(6);
        {
            const float SC = 0.25f * 1.4426950408889634f;
            const int gb0 = 8 * ti - 16 + warp;
            int slotK = 0, slotV = 0;
            uint32_t* odst = reinterpret_cast<uint32_t*>(g_o + (size_t)(ti * 128 + warp * 16 + g) * 512 + tj * 64 + ((lane & 1) ? 8 : 0) + (lane & 2) * 2);
#define NHEADS (dry ? 2 : 4)
#define ATT_KWAIT(kb) do { slotK = r.slot; CWAIT(); kb = sb + RING_OFF + slotK * SLOT + warp * 512 + lane * 16; r.next(); } while (0)
#define ATT_VWAIT(vb) do { slotV = r.slot; CWAIT(); vb = sb + RING_OFF + slotV * SLOT + warp * 512 + lane * 16; r.next(); TS(21 + hh); } while (0)
#define ATT_KREL() do { __syncwarp(); if (lane0) mbar_arrive(sb + B_EMPTY + 8 * slotK); } while (0)
#define ATT_VREL() do { __syncwarp(); if (lane0) mbar_arrive(sb + B_EMPTY + 8 * slotV); } while (0)
#define ATT_NEXTQ(h) do { \
                if ((h) == 1) { q0 = qf[1][0]; q1 = qf[1][1]; q2 = qf[1][2]; q3 = qf[1][3]; } \
                else if ((h) == 2) { q0 = qf[2][0]; q1 = qf[2][1]; q2 = qf[2][2]; q3 = qf[2][3]; } \
                else { q0 = qf[3][0]; q1 = qf[3][1]; q2 = qf[3][2]; q3 = qf[3][3]; } } while (0)
#define ATT_STORE(h, r0, r1, r2, r3) do { \
                const bool odd = lane & 1; \
                const uint32_t sl = __shfl_xor_sync(0xffffffffu, odd ? (r0) : (r2), 1), sh = __shfl_xor_sync(0xffffffffu, odd ? (r1) : (r3), 1); \
                if (!dry) *reinterpret_cast<uint2*>(odst + 8 * (h)) = odd ? make_uint2(sl, r2) : make_uint2(r0, sl); \
                if (!dry) *reinterpret_cast<uint2*>(odst + 8 * (h) + 8 * 256) = odd ? make_uint2(sh, r3) : make_uint2(r1, sh); \
                } while (0)
            auto attention = [&](auto masked_tag) {
            constexpr bool MASKED = decltype(masked_tag)::value;
            const float NEG = -INFINITY;
            const uint32_t ONES = 0x3F803F80u;
            float sa[8][2][4], sb2[8][2][4];
            float o[2][4], ls[4];
            float m0, m1;
            uint32_t q0 = qf[0][0], q1 = qf[0][1], q2 = qf[0][2], q3 = qf[0][3];
            auto qk = [&](float (&s)[8][2][4], int ps, int t, uint32_t kbase) {
                if (ps == 0 && t == 0) {
                    const uint4 kd = lds128(kbase + 16 * 512);
                    const uint4 kf = lds128(kbase);
                    float f[2][4];
                    const float ci = (!MASKED || opaque(gb0) >= 0) ? 0.f : NEG;
                    mma16816_c(s[0][0], q0, q1, q2, q3, kd.x, kd.y, 0.f);
                    mma16816_c(s[0][1], q0, q1, q2, q3, kd.z, kd.w, 0.f);
                    mma16816_c(f[0], q0, q1, q2, q3, kf.x, kf.y, ci);
                    mma16816_c(f[1], q0, q1, q2, q3, kf.z, kf.w, ci);
#pragma unroll
                    for (int u = 0; u < 2; u++)
#pragma unroll
                        for (int e = 0; e < 4; e++) {
                            const int row = g + 8 * (e >> 1), col = 8 * u + 2 * c + (e & 1);
                            s[0][u][e] = (col > row) ? f[u][e] : s[0][u][e];
                        }
                } else {
                    const uint4 kf = lds128(kbase + (8 * ps + t) * 512);
                    const float ci = (!MASKED || opaque(gb0) + 8 * ps + t >= 0) ? 0.f : NEG;
                    mma16816_c(s[t][0], q0, q1, q2, q3, kf.x, kf.y, ci);
                    mma16816_c(s[t][1], q0, q1, q2, q3, kf.z, kf.w, ci);
                }
            };
            auto rowmax = [&](float (&s)[8][2][4], float b0, float b1, float& n0, float& n1) {
                int i0 = __float_as_int(b0), i1 = __float_as_int(b1);
#pragma unroll
                for (int t = 0; t < 8; t++)
#pragma unroll
                    for (int u = 0; u < 2; u++) {
                        i0 = __vimax3_s32(i0, __float_as_int(s[t][u][0]), __float_as_int(s[t][u][1]));
                        i1 = __vimax3_s32(i1, __float_as_int(s[t][u][2]), __float_as_int(s[t][u][3]));
                    }
                i0 = max(i0, __shfl_xor_sync(0xffffffffu, i0, 1)); i1 = max(i1, __shfl_xor_sync(0xffffffffu, i1, 1));
                i0 = max(i0, __shfl_xor_sync(0xffffffffu, i0, 2)); i1 = max(i1, __shfl_xor_sync(0xffffffffu, i1, 2));
                n0 = __int_as_float(i0); n1 = __int_as_float(i1);
                if (__any_sync(0xffffffffu, (i0 | i1) < 0)) {
                    asm volatile("" ::: "memory");
                    n0 = b0; n1 = b1;
#pragma unroll
                    for (int t = 0; t < 8; t++)
#pragma unroll
                        for (int u = 0; u < 2; u++) {
                            n0 = fmaxf(n0, fmaxf(s[t][u][0], s[t][u][1]));
                            n1 = fmaxf(n1, fmaxf(s[t][u][2], s[t][u][3]));
                        }
                    n0 = fmaxf(n0, __shfl_xor_sync(0xffffffffu, n0, 1)); n1 = fmaxf(n1, __shfl_xor_sync(0xffffffffu, n1, 1));
                    n0 = fmaxf(n0, __shfl_xor_sync(0xffffffffu, n0, 2)); n1 = fmaxf(n1, __shfl_xor_sync(0xffffffffu, n1, 2));
                }
            };
            auto pv = [&](const float (&p)[2][4], uint32_t vaddr) {
                const uint4 vf = lds128(vaddr);
                const uint32_t a0 = pack_bf16(p[0][0], p[0][1]), a1 = pack_bf16(p[0][2], p[0][3]);
                const uint32_t a2 = pack_bf16(p[1][0], p[1][1]), a3 = pack_bf16(p[1][2], p[1][3]);
                mma16816(o[0], a0, a1, a2, a3, vf.x, vf.y);
                mma16816(o[1], a0, a1, a2, a3, vf.z, vf.w);
                mma16816(ls, a0, a1, a2, a3, ONES, ONES);
            };
            auto expv = [&](float (&s)[8][2][4], int ps, int t, float mc0, float mc1, uint32_t vbase) {
                float p[2][4];
#pragma unroll
                for (int u = 0; u < 2; u++) {
                    p[u][0] = ex2(fmaf(s[t][u][0], SC, -mc0)); p[u][1] = ex2(fmaf(s[t][u][1], SC, -mc0));
                    p[u][2] = ex2(fmaf(s[t][u][2], SC, -mc1)); p[u][3] = ex2(fmaf(s[t][u][3], SC, -mc1));
                }
                if (ps == 0 && t == 0) {
                    float pd[2][4], pf[2][4];
#pragma unroll
                    for (int u = 0; u < 2; u++)
#pragma unroll
                        for (int e = 0; e < 4; e++) {
                            const int row = g + 8 * (e >> 1), col = 8 * u + 2 * c + (e & 1);
                            pf[u][e] = (col > row) ? p[u][e] : 0.f;
                            pd[u][e] = (col > row) ? 0.f : p[u][e];
                        }
                    pv(pd, vbase + 16 * 512);
                    pv(pf, vbase);
                } else {
                    pv(p, vbase + (8 * ps + t) * 512);
                }
            };
            uint32_t kbase, vbase;
            ATT_KWAIT(kbase);
#pragma unroll
            for (int t = 0; t < 8; t++) qk(sa, 0, t, kbase);
            rowmax(sa, NEG, NEG, m0, m1);
#pragma unroll 1
            for (int hh = 0; hh < NHEADS; hh++) {
                ATT_VWAIT(vbase);
#pragma unroll
                for (int e = 0; e < 4; e++) { o[0][e] = 0.f; o[1][e] = 0.f; ls[e] = 0.f; }
                {
                    const float mc0 = m0 * SC, mc1 = m1 * SC;
#pragma unroll
                    for (int t = 0; t < 8; t++) { qk(sb2, 1, t, kbase); expv(sa, 0, t, mc0, mc1, vbase); }
                    ATT_KREL();
                    float n0, n1;
                    rowmax(sb2, m0, m1, n0, n1);
                    const float a0 = ex2((m0 - n0) * SC), a1 = ex2((m1 - n1) * SC);
                    ls[0] *= a0; ls[2] *= a1;
                    o[0][0] *= a0; o[0][1] *= a0; o[1][0] *= a0; o[1][1] *= a0;
                    o[0][2] *= a1; o[0][3] *= a1; o[1][2] *= a1; o[1][3] *= a1;
                    m0 = n0; m1 = n1;
                }
                {
                    const float mc0 = m0 * SC, mc1 = m1 * SC;
                    const bool more = hh + 1 < NHEADS;
                    if (more) {
                        ATT_KWAIT(kbase);
                        ATT_NEXTQ(hh + 1);
#pragma unroll
                        for (int t = 0; t < 8; t++) { qk(sa, 0, t, kbase); expv(sb2, 1, t, mc0, mc1, vbase); }
                        rowmax(sa, NEG, NEG, m0, m1);
                    } else {
#pragma unroll
                        for (int t = 0; t < 8; t++) expv(sb2, 1, t, mc0, mc1, vbase);
                    }
                    ATT_VREL();
                }
                const float f0 = __fdividef(g0, ls[0]), f1 = __fdividef(g1, ls[2]);
                ATT_STORE(hh, pack_bf16(o[0][0] * f0, o[0][1] * f0), pack_bf16(o[0][2] * f1, o[0][3] * f1),
                              pack_bf16(o[1][0] * f0, o[1][1] * f0), pack_bf16(o[1][2] * f1, o[1][3] * f1));
            }
            };
            if (ti >= 2) attention(BoolTag<false>{}); else attention(BoolTag<true>{});
            __syncwarp();
            if (lane0) mbar_arrive(sb + B_ODONE);
        }
        TS(7);
        {
            float acc[32];
            if (!dry) mbar_wait(sb + B_HSUM, 0);
#pragma unroll
            for (int k = 0; k < 8; k++) {
                const uint4 v = lds128(sb + STG_OFF + (warp * 8 + k) * 512 + lane * 16);
                acc[4 * k] = __uint_as_float(v.x); acc[4 * k + 1] = __uint_as_float(v.y);
                acc[4 * k + 2] = __uint_as_float(v.z); acc[4 * k + 3] = __uint_as_float(v.w);
            }
            fence_acc(acc);
            if (!dry) mbar_wait(sb + B_WOFULL, 0);
            if (!dry) mbar_wait(sb + B_ODONE, 0);
            TS(15);
            int prev = 0;
#pragma unroll 1
            for (int m = 0; m < N_O; m++) {
                CWAIT();
                if (m == 0) TS(16);
                const uint32_t as = sb + RING_OFF + r.slot * SLOT + wg * 8192;
                const uint32_t bs = sb + X_OFF + ((tj + m) & 7) * 8192;
                wgmma_fence();
#pragma unroll
                for (int k = 0; k < 4; k++) wgmma_ss_n64(acc, desc_a(as + 32 * k), desc_b(bs + 2048 * k), 1);
                wgmma_commit();
                if (m > 0) { wgmma_wait<1>(); if (lane0) mbar_arrive(sb + B_EMPTY + 8 * prev); }
                prev = r.slot; r.next();
            }
            wgmma_wait<0>();
            fence_acc(acc);
            TS(17);
            __nv_bfloat16* o = out + (size_t)(ti * 128 + warp * 16 + g) * 512 + tj * 64 + ((lane & 1) ? 8 : 0) + (lane & 2) * 2;
            const bool odd = lane & 1;
#pragma unroll
            for (int t2 = 0; t2 < 4; t2++) {
                const uint32_t lo0 = pack_bf16(acc[8 * t2 + 0], acc[8 * t2 + 1]), hi0 = pack_bf16(acc[8 * t2 + 2], acc[8 * t2 + 3]);
                const uint32_t lo1 = pack_bf16(acc[8 * t2 + 4], acc[8 * t2 + 5]), hi1 = pack_bf16(acc[8 * t2 + 6], acc[8 * t2 + 7]);
                const uint32_t sl = __shfl_xor_sync(0xffffffffu, odd ? lo0 : lo1, 1), sh = __shfl_xor_sync(0xffffffffu, odd ? hi0 : hi1, 1);
                if (!dry) *reinterpret_cast<uint2*>(o + 16 * t2) = odd ? make_uint2(sl, lo1) : make_uint2(lo0, sl);
                if (!dry) *reinterpret_cast<uint2*>(o + 16 * t2 + 8 * 512) = odd ? make_uint2(sh, hi1) : make_uint2(hi0, sh);
            }
            if (tid == 0 && !dry) TSG(30);
        }
        TS(8);
    }
}

typedef CUresult (*PFN_encodeTiled)(CUtensorMap*, CUtensorMapDataType, cuuint32_t, void*, const cuuint64_t*, const cuuint64_t*,
                                    const cuuint32_t*, const cuuint32_t*, CUtensorMapInterleave, CUtensorMapSwizzle,
                                    CUtensorMapL2promotion, CUtensorMapFloatOOBfill);

void make_map(PFN_encodeTiled enc, CUtensorMap* m, const void* base, int rank, const cuuint64_t* dims, const cuuint64_t* strides, const cuuint32_t* box) {
    cuuint32_t es[5] = {1, 1, 1, 1, 1};
    enc(m, CU_TENSOR_MAP_DATA_TYPE_BFLOAT16, (cuuint32_t)rank, const_cast<void*>(base), dims, strides, box, es,
        CU_TENSOR_MAP_INTERLEAVE_NONE, CU_TENSOR_MAP_SWIZZLE_128B, CU_TENSOR_MAP_L2_PROMOTION_L2_256B, CU_TENSOR_MAP_FLOAT_OOB_FILL_NONE);
}

}

extern "C" void kernel_launch(void* const* d_in, const int* in_sizes, int n_in, void* d_out, int out_size) {
    (void)in_sizes; (void)n_in; (void)out_size;
    const void* x = d_in[0]; const void* wqkv = d_in[1]; const void* wo = d_in[2];
    const void* w1 = d_in[4]; const void* w2 = d_in[5]; const void* gate_w = d_in[6];
    static PFN_encodeTiled enc = nullptr;
    if (!enc) {
        void* fn = nullptr; cudaDriverEntryPointQueryResult st;
        cudaGetDriverEntryPoint("cuTensorMapEncodeTiled", &fn, cudaEnableDefault, &st);
        enc = (PFN_encodeTiled)fn;
        cudaFuncSetAttribute(fused_kernel, cudaFuncAttributeMaxDynamicSharedMemorySize, SMEM_BYTES);
    }
    CUtensorMap mx, mqkv, mw1, mw2, mwo, mw1a, mo;
    void* optr = nullptr;
    cudaGetSymbolAddress(&optr, g_o);
    { cuuint64_t d[2] = {512, 2048}, s[1] = {1024}; cuuint32_t b[2] = {64, 128}; make_map(enc, &mo, optr, 2, d, s, b); }
    { cuuint64_t d[4] = {64, 512, 3, 8}, s[3] = {3584, 128, 448}; cuuint32_t b[4] = {64, 32, 3, 1}; make_map(enc, &mw1a, w1, 4, d, s, b); }
    { cuuint64_t d[2] = {512, 2048}, s[1] = {1024}; cuuint32_t b[2] = {64, 128}; make_map(enc, &mx, x, 2, d, s, b); }
    { cuuint64_t d[4] = {64, 512, 8, 3}, s[3] = {3072, 128, 1024}; cuuint32_t b[4] = {64, 32, 1, 3}; make_map(enc, &mqkv, wqkv, 4, d, s, b); }
    { cuuint64_t d[2] = {1792, 512}, s[1] = {3584}; cuuint32_t b[2] = {64, 32}; make_map(enc, &mw1, w1, 2, d, s, b); }
    { cuuint64_t d[3] = {64, 1792, 8}, s[2] = {1024, 128}; cuuint32_t b[3] = {64, 32, 2}; make_map(enc, &mw2, w2, 3, d, s, b); }
    { cuuint64_t d[2] = {512, 512}, s[1] = {1024}; cuuint32_t b[2] = {64, 256}; make_map(enc, &mwo, wo, 2, d, s, b); }
    fused_kernel<<<NCTA, 384, SMEM_BYTES, cudaStreamPerThread>>>(mx, mqkv, mw1, mw2, mwo, mw1a, mo, (const __nv_bfloat16*)gate_w, (__nv_bfloat16*)d_out,
                                           (const uint8_t*)w1, (const uint8_t*)w2, (const uint8_t*)wo);
}
```

```cpp
#include <cuda_runtime.h>
#include <cuda_bf16.h>
#include <cuda.h>
#include <stdint.h>

namespace {

#define PF1_AT 1
#define PF2_AT 5
#define LEAD1 2
#define NCTA 132
constexpr int RING = 6;
constexpr int SLOT = 16384;
constexpr uint32_t X_OFF = 0;
constexpr uint32_t STG_OFF = X_OFF + 4 * 16384;
constexpr uint32_t RING_OFF = 131072;
constexpr uint32_t BAR_OFF = RING_OFF + RING * SLOT;
constexpr uint32_t B_FULL = BAR_OFF, B_EMPTY = BAR_OFF + 64, B_XFULL = BAR_OFF + 128, B_HDEAD = BAR_OFF + 192,
                   B_EREADY = BAR_OFF + 200, B_KVDONE = BAR_OFF + 208, B_ODONE = BAR_OFF + 224,
                   B_KVREADY = BAR_OFF + 232, B_WOFULL = BAR_OFF + 240, B_HSUM = BAR_OFF + 248, B_PREADY = BAR_OFF + 264,
                   B_SQ = BAR_OFF + 272, B_SF = BAR_OFF + 304;
constexpr uint32_t EPOCH_OFF = BAR_OFF + 256, ITEM_OFF = BAR_OFF + 260;
constexpr uint32_t SMEM_BYTES = BAR_OFF + 1024;

constexpr int N_QKV = 16, N_FFN1 = 16, N_FFN2 = 14, N_KV = 8, N_O = 8;

__device__ uint4 g_kf[32 * 128 * 32];
__device__ uint4 g_vf[32 * 128 * 32];
__device__ uint4 g_part[16 * 8 * 8 * 8 * 4 * 32];
__device__ __nv_bfloat16 g_o[2048 * 512];
__device__ unsigned g_ticket;
__device__ unsigned g_kvcnt[128 * 32];
__device__ unsigned g_pcnt[128 * 32];
__device__ unsigned g_ocnt[128 * 32];
#define TS(k) do {} while (0)
#define TS2(k) do {} while (0)
#define TS2X(k) do {} while (0)
#define TSX(k) do {} while (0)
#define TSG(k) do {} while (0)

__device__ __forceinline__ uint32_t smem_u32(const void* p) { return (uint32_t)__cvta_generic_to_shared(p); }
__device__ __forceinline__ void mbar_init(uint32_t bar, uint32_t cnt) { asm volatile("mbarrier.init.shared::cta.b64 [%0], %1;" :: "r"(bar), "r"(cnt) : "memory"); }
__device__ __forceinline__ void mbar_expect_tx(uint32_t bar, uint32_t bytes) { asm volatile("mbarrier.arrive.expect_tx.shared::cta.b64 _, [%0], %1;" :: "r"(bar), "r"(bytes) : "memory"); }
__device__ __forceinline__ void mbar_expect_only(uint32_t bar, uint32_t bytes) { asm volatile("mbarrier.expect_tx.relaxed.cta.shared::cta.b64 [%0], %1;" :: "r"(bar), "r"(bytes) : "memory"); }
__device__ __forceinline__ void mbar_arrive(uint32_t bar) { asm volatile("mbarrier.arrive.shared::cta.b64 _, [%0];" :: "r"(bar) : "memory"); }
__device__ __forceinline__ void mbar_wait(uint32_t bar, uint32_t parity) {
    asm volatile("{\n.reg .pred P1, P2;\n.reg .u32 n;\nmov.u32 n, 0;\n"
                 "WAIT_LOOP:\n"
                 "mbarrier.try_wait.parity.shared::cta.b64 P1, [%0], %1;\n"
                 "@P1 bra WAIT_DONE;\n"
                 "add.u32 n, n, 1;\n"
                 "setp.lt.u32 P2, n, 0x400000;\n"
                 "@P2 bra WAIT_LOOP;\n"
                 "WAIT_DONE:\n}" :: "r"(bar), "r"(parity) : "memory");
}
__device__ __forceinline__ void tma_2d(uint32_t dst, const void* map, uint32_t bar, int c0, int c1) {
    asm volatile("cp.async.bulk.tensor.2d.shared::cluster.global.mbarrier::complete_tx::bytes [%0], [%1, {%3, %4}], [%2];"
        :: "r"(dst), "l"(map), "r"(bar), "r"(c0), "r"(c1) : "memory");
}
__device__ __forceinline__ void tma_3d(uint32_t dst, const void* map, uint32_t bar, int c0, int c1, int c2) {
    asm volatile("cp.async.bulk.tensor.3d.shared::cluster.global.mbarrier::complete_tx::bytes [%0], [%1, {%3, %4, %5}], [%2];"
        :: "r"(dst), "l"(map), "r"(bar), "r"(c0), "r"(c1), "r"(c2) : "memory");
}
__device__ __forceinline__ void tma_4d(uint32_t dst, const void* map, uint32_t bar, int c0, int c1, int c2, int c3) {
    asm volatile("cp.async.bulk.tensor.4d.shared::cluster.global.mbarrier::complete_tx::bytes [%0], [%1, {%3, %4, %5, %6}], [%2];"
        :: "r"(dst), "l"(map), "r"(bar), "r"(c0), "r"(c1), "r"(c2), "r"(c3) : "memory");
}
__device__ __forceinline__ void bulk_g2s(uint32_t dst, const void* src, uint32_t bytes, uint32_t bar) {
    asm volatile("cp.async.bulk.shared::cluster.global.mbarrier::complete_tx::bytes [%0], [%1], %2, [%3];"
        :: "r"(dst), "l"(src), "r"(bytes), "r"(bar) : "memory");
}
__device__ __forceinline__ void prefetch_l2(const void* src, uint32_t bytes) {
    asm volatile("cp.async.bulk.prefetch.L2.global [%0], %1;" :: "l"(src), "r"(bytes) : "memory");
}
__device__ __forceinline__ bool elect_one() {
    uint32_t p;
    asm volatile("{\n.reg .pred P;\nelect.sync _|P, 0xffffffff;\nselp.u32 %0, 1, 0, P;\n}" : "=r"(p));
    return p != 0;
}
__device__ __forceinline__ void wgmma_fence() { asm volatile("wgmma.fence.sync.aligned;" ::: "memory"); }
__device__ __forceinline__ void wgmma_commit() { asm volatile("wgmma.commit_group.sync.aligned;" ::: "memory"); }
template <int N> __device__ __forceinline__ void wgmma_wait() { asm volatile("wgmma.wait_group.sync.aligned %0;" :: "n"(N) : "memory"); }
__device__ __forceinline__ void fence_async_smem() { asm volatile("fence.proxy.async.shared::cta;" ::: "memory"); }
__device__ __forceinline__ uint64_t desc_a(uint32_t addr) {
    return (uint64_t)((addr & 0x3FFFF) >> 4) | ((uint64_t)1 << 16) | ((uint64_t)(1024 >> 4) << 32) | ((uint64_t)1 << 62);
}
__device__ __forceinline__ uint64_t desc_b(uint32_t addr) {
    return (uint64_t)((addr & 0x3FFFF) >> 4) | ((uint64_t)(4096 >> 4) << 16) | ((uint64_t)(1024 >> 4) << 32) | ((uint64_t)1 << 62);
}
__device__ __forceinline__ uint32_t pack_bf16(float lo, float hi) {
    uint32_t r; asm("cvt.rn.bf16x2.f32 %0, %1, %2;" : "=r"(r) : "f"(hi), "f"(lo)); return r;
}
__device__ __forceinline__ uint32_t pack_bf16_relu(float lo, float hi) {
    uint32_t r; asm("cvt.rn.relu.bf16x2.f32 %0, %1, %2;" : "=r"(r) : "f"(hi), "f"(lo)); return r;
}
__device__ __forceinline__ uint32_t movmatrix(uint32_t a) {
    uint32_t d; asm volatile("movmatrix.sync.aligned.m8n8.trans.b16 %0, %1;" : "=r"(d) : "r"(a)); return d;
}
__device__ __forceinline__ void stmatrix_x4(uint32_t addr, uint32_t r0, uint32_t r1, uint32_t r2, uint32_t r3) {
    asm volatile("stmatrix.sync.aligned.m8n8.x4.shared.b16 [%0], {%1, %2, %3, %4};" :: "r"(addr), "r"(r0), "r"(r1), "r"(r2), "r"(r3) : "memory");
}
__device__ __forceinline__ uint4 lds128(uint32_t addr) {
    uint4 v; asm volatile("ld.shared.v4.b32 {%0, %1, %2, %3}, [%4];" : "=r"(v.x), "=r"(v.y), "=r"(v.z), "=r"(v.w) : "r"(addr) : "memory"); return v;
}
__device__ __forceinline__ void mma16816(float (&c)[4], uint32_t a0, uint32_t a1, uint32_t a2, uint32_t a3, uint32_t b0, uint32_t b1) {
    asm volatile("mma.sync.aligned.m16n8k16.row.col.f32.bf16.bf16.f32 {%0,%1,%2,%3}, {%4,%5,%6,%7}, {%8,%9}, {%0,%1,%2,%3};"
        : "+f"(c[0]), "+f"(c[1]), "+f"(c[2]), "+f"(c[3]) : "r"(a0), "r"(a1), "r"(a2), "r"(a3), "r"(b0), "r"(b1));
}
__device__ __forceinline__ void mma16816_c(float (&c)[4], uint32_t a0, uint32_t a1, uint32_t a2, uint32_t a3, uint32_t b0, uint32_t b1, float ci) {
    asm volatile("mma.sync.aligned.m16n8k16.row.col.f32.bf16.bf16.f32 {%0,%1,%2,%3}, {%4,%5,%6,%7}, {%8,%9}, {%10,%10,%10,%10};"
        : "=f"(c[0]), "=f"(c[1]), "=f"(c[2]), "=f"(c[3]) : "r"(a0), "r"(a1), "r"(a2), "r"(a3), "r"(b0), "r"(b1), "f"(ci));
}
__device__ __forceinline__ int opaque(int v) { asm volatile("" : "+r"(v)); return v; }
__device__ __forceinline__ float ex2(float x) { float y; asm("ex2.approx.ftz.f32 %0, %1;" : "=f"(y) : "f"(x)); return y; }
__device__ __forceinline__ unsigned ld_acquire(const unsigned* p) {
    unsigned v; asm volatile("ld.acquire.gpu.global.u32 %0, [%1];" : "=r"(v) : "l"(p) : "memory"); return v;
}
__device__ __forceinline__ void red_release(unsigned* p, unsigned v) {
    asm volatile("red.release.gpu.global.add.u32 [%0], %1;" :: "l"(p), "r"(v) : "memory");
}
__device__ __forceinline__ void wait_counter(const unsigned* p, unsigned target) {
    uint32_t n = 0;
    while ((int)(ld_acquire(p) - target) < 0) { if (++n > (1u << 20)) break; }
}
__device__ __forceinline__ uint4 ldg_weak(const uint4* p) {
    uint4 v; asm volatile("ld.global.L1::no_allocate.v4.b32 {%0, %1, %2, %3}, [%4];" : "=r"(v.x), "=r"(v.y), "=r"(v.z), "=r"(v.w) : "l"(p) : "memory"); return v;
}
__device__ __forceinline__ float bf_lo(uint32_t v) { return __uint_as_float(v << 16); }
__device__ __forceinline__ float bf_hi(uint32_t v) { return __uint_as_float(v & 0xFFFF0000u); }

__device__ __forceinline__ void wgmma_ss_n64(float (&d)[32], uint64_t da, uint64_t db, int scale_d) {
    asm volatile("{\n.reg .pred p;\nsetp.ne.b32 p, %34, 0;\n"
        "wgmma.mma_async.sync.aligned.m64n64k16.f32.bf16.bf16 {%0, %1, %2, %3, %4, %5, %6, %7, %8, %9, %10, %11, %12, %13, %14, %15, %16, %17, %18, %19, %20, %21, %22, %23, %24, %25, %26, %27, %28, %29, %30, %31}, %32, %33, p, 1, 1, 0, 1;\n}\n"
        : "+f"(d[0]), "+f"(d[1]), "+f"(d[2]), "+f"(d[3]), "+f"(d[4]), "+f"(d[5]), "+f"(d[6]), "+f"(d[7]), "+f"(d[8]), "+f"(d[9]), "+f"(d[10]), "+f"(d[11]), "+f"(d[12]), "+f"(d[13]), "+f"(d[14]), "+f"(d[15]), "+f"(d[16]), "+f"(d[17]), "+f"(d[18]), "+f"(d[19]), "+f"(d[20]), "+f"(d[21]), "+f"(d[22]), "+f"(d[23]), "+f"(d[24]), "+f"(d[25]), "+f"(d[26]), "+f"(d[27]), "+f"(d[28]), "+f"(d[29]), "+f"(d[30]), "+f"(d[31])
        : "l"(da), "l"(db), "r"(scale_d));
}
__device__ __forceinline__ void wgmma_ss_n128(float (&d)[64], uint64_t da, uint64_t db, int scale_d) {
    asm volatile("{\n.reg .pred p;\nsetp.ne.b32 p, %66, 0;\n"
        "wgmma.mma_async.sync.aligned.m64n128k16.f32.bf16.bf16 {%0, %1, %2, %3, %4, %5, %6, %7, %8, %9, %10, %11, %12, %13, %14, %15, %16, %17, %18, %19, %20, %21, %22, %23, %24, %25, %26, %27, %28, %29, %30, %31, %32, %33, %34, %35, %36, %37, %38, %39, %40, %41, %42, %43, %44, %45, %46, %47, %48, %49, %50, %51, %52, %53, %54, %55, %56, %57, %58, %59, %60, %61, %62, %63}, %64, %65, p, 1, 1, 0, 1;\n}\n"
        : "+f"(d[0]), "+f"(d[1]), "+f"(d[2]), "+f"(d[3]), "+f"(d[4]), "+f"(d[5]), "+f"(d[6]), "+f"(d[7]), "+f"(d[8]), "+f"(d[9]), "+f"(d[10]), "+f"(d[11]), "+f"(d[12]), "+f"(d[13]), "+f"(d[14]), "+f"(d[15]), "+f"(d[16]), "+f"(d[17]), "+f"(d[18]), "+f"(d[19]), "+f"(d[20]), "+f"(d[21]), "+f"(d[22]), "+f"(d[23]), "+f"(d[24]), "+f"(d[25]), "+f"(d[26]), "+f"(d[27]), "+f"(d[28]), "+f"(d[29]), "+f"(d[30]), "+f"(d[31]), "+f"(d[32]), "+f"(d[33]), "+f"(d[34]), "+f"(d[35]), "+f"(d[36]), "+f"(d[37]), "+f"(d[38]), "+f"(d[39]), "+f"(d[40]), "+f"(d[41]), "+f"(d[42]), "+f"(d[43]), "+f"(d[44]), "+f"(d[45]), "+f"(d[46]), "+f"(d[47]), "+f"(d[48]), "+f"(d[49]), "+f"(d[50]), "+f"(d[51]), "+f"(d[52]), "+f"(d[53]), "+f"(d[54]), "+f"(d[55]), "+f"(d[56]), "+f"(d[57]), "+f"(d[58]), "+f"(d[59]), "+f"(d[60]), "+f"(d[61]), "+f"(d[62]), "+f"(d[63])
        : "l"(da), "l"(db), "r"(scale_d));
}
__device__ __forceinline__ void wgmma_ss_n200(float (&d)[100], uint64_t da, uint64_t db, int scale_d) {
    asm volatile("{\n.reg .pred p;\nsetp.ne.b32 p, %102, 0;\n"
        "wgmma.mma_async.sync.aligned.m64n200k16.f32.bf16.bf16 {%0, %1, %2, %3, %4, %5, %6, %7, %8, %9, %10, %11, %12, %13, %14, %15, %16, %17, %18, %19, %20, %21, %22, %23, %24, %25, %26, %27, %28, %29, %30, %31, %32, %33, %34, %35, %36, %37, %38, %39, %40, %41, %42, %43, %44, %45, %46, %47, %48, %49, %50, %51, %52, %53, %54, %55, %56, %57, %58, %59, %60, %61, %62, %63, %64, %65, %66, %67, %68, %69, %70, %71, %72, %73, %74, %75, %76, %77, %78, %79, %80, %81, %82, %83, %84, %85, %86, %87, %88, %89, %90, %91, %92, %93, %94, %95, %96, %97, %98, %99}, %100, %101, p, 1, 1, 0, 1;\n}\n"
        : "+f"(d[0]), "+f"(d[1]), "+f"(d[2]), "+f"(d[3]), "+f"(d[4]), "+f"(d[5]), "+f"(d[6]), "+f"(d[7]), "+f"(d[8]), "+f"(d[9]), "+f"(d[10]), "+f"(d[11]), "+f"(d[12]), "+f"(d[13]), "+f"(d[14]), "+f"(d[15]), "+f"(d[16]), "+f"(d[17]), "+f"(d[18]), "+f"(d[19]), "+f"(d[20]), "+f"(d[21]), "+f"(d[22]), "+f"(d[23]), "+f"(d[24]), "+f"(d[25]), "+f"(d[26]), "+f"(d[27]), "+f"(d[28]), "+f"(d[29]), "+f"(d[30]), "+f"(d[31]), "+f"(d[32]), "+f"(d[33]), "+f"(d[34]), "+f"(d[35]), "+f"(d[36]), "+f"(d[37]), "+f"(d[38]), "+f"(d[39]), "+f"(d[40]), "+f"(d[41]), "+f"(d[42]), "+f"(d[43]), "+f"(d[44]), "+f"(d[45]), "+f"(d[46]), "+f"(d[47]), "+f"(d[48]), "+f"(d[49]), "+f"(d[50]), "+f"(d[51]), "+f"(d[52]), "+f"(d[53]), "+f"(d[54]), "+f"(d[55]), "+f"(d[56]), "+f"(d[57]), "+f"(d[58]), "+f"(d[59]), "+f"(d[60]), "+f"(d[61]), "+f"(d[62]), "+f"(d[63]), "+f"(d[64]), "+f"(d[65]), "+f"(d[66]), "+f"(d[67]), "+f"(d[68]), "+f"(d[69]), "+f"(d[70]), "+f"(d[71]), "+f"(d[72]), "+f"(d[73]), "+f"(d[74]), "+f"(d[75]), "+f"(d[76]), "+f"(d[77]), "+f"(d[78]), "+f"(d[79]), "+f"(d[80]), "+f"(d[81]), "+f"(d[82]), "+f"(d[83]), "+f"(d[84]), "+f"(d[85]), "+f"(d[86]), "+f"(d[87]), "+f"(d[88]), "+f"(d[89]), "+f"(d[90]), "+f"(d[91]), "+f"(d[92]), "+f"(d[93]), "+f"(d[94]), "+f"(d[95]), "+f"(d[96]), "+f"(d[97]), "+f"(d[98]), "+f"(d[99])
        : "l"(da), "l"(db), "r"(scale_d));
}
__device__ __forceinline__ void wgmma_ss_n224(float (&d)[112], uint64_t da, uint64_t db, int scale_d) {
    asm volatile("{\n.reg .pred p;\nsetp.ne.b32 p, %114, 0;\n"
        "wgmma.mma_async.sync.aligned.m64n224k16.f32.bf16.bf16 {%0, %1, %2, %3, %4, %5, %6, %7, %8, %9, %10, %11, %12, %13, %14, %15, %16, %17, %18, %19, %20, %21, %22, %23, %24, %25, %26, %27, %28, %29, %30, %31, %32, %33, %34, %35, %36, %37, %38, %39, %40, %41, %42, %43, %44, %45, %46, %47, %48, %49, %50, %51, %52, %53, %54, %55, %56, %57, %58, %59, %60, %61, %62, %63, %64, %65, %66, %67, %68, %69, %70, %71, %72, %73, %74, %75, %76, %77, %78, %79, %80, %81, %82, %83, %84, %85, %86, %87, %88, %89, %90, %91, %92, %93, %94, %95, %96, %97, %98, %99, %100, %101, %102, %103, %104, %105, %106, %107, %108, %109, %110, %111}, %112, %113, p, 1, 1, 0, 1;\n}\n"
        : "+f"(d[0]), "+f"(d[1]), "+f"(d[2]), "+f"(d[3]), "+f"(d[4]), "+f"(d[5]), "+f"(d[6]), "+f"(d[7]), "+f"(d[8]), "+f"(d[9]), "+f"(d[10]), "+f"(d[11]), "+f"(d[12]), "+f"(d[13]), "+f"(d[14]), "+f"(d[15]), "+f"(d[16]), "+f"(d[17]), "+f"(d[18]), "+f"(d[19]), "+f"(d[20]), "+f"(d[21]), "+f"(d[22]), "+f"(d[23]), "+f"(d[24]), "+f"(d[25]), "+f"(d[26]), "+f"(d[27]), "+f"(d[28]), "+f"(d[29]), "+f"(d[30]), "+f"(d[31]), "+f"(d[32]), "+f"(d[33]), "+f"(d[34]), "+f"(d[35]), "+f"(d[36]), "+f"(d[37]), "+f"(d[38]), "+f"(d[39]), "+f"(d[40]), "+f"(d[41]), "+f"(d[42]), "+f"(d[43]), "+f"(d[44]), "+f"(d[45]), "+f"(d[46]), "+f"(d[47]), "+f"(d[48]), "+f"(d[49]), "+f"(d[50]), "+f"(d[51]), "+f"(d[52]), "+f"(d[53]), "+f"(d[54]), "+f"(d[55]), "+f"(d[56]), "+f"(d[57]), "+f"(d[58]), "+f"(d[59]), "+f"(d[60]), "+f"(d[61]), "+f"(d[62]), "+f"(d[63]), "+f"(d[64]), "+f"(d[65]), "+f"(d[66]), "+f"(d[67]), "+f"(d[68]), "+f"(d[69]), "+f"(d[70]), "+f"(d[71]), "+f"(d[72]), "+f"(d[73]), "+f"(d[74]), "+f"(d[75]), "+f"(d[76]), "+f"(d[77]), "+f"(d[78]), "+f"(d[79]), "+f"(d[80]), "+f"(d[81]), "+f"(d[82]), "+f"(d[83]), "+f"(d[84]), "+f"(d[85]), "+f"(d[86]), "+f"(d[87]), "+f"(d[88]), "+f"(d[89]), "+f"(d[90]), "+f"(d[91]), "+f"(d[92]), "+f"(d[93]), "+f"(d[94]), "+f"(d[95]), "+f"(d[96]), "+f"(d[97]), "+f"(d[98]), "+f"(d[99]), "+f"(d[100]), "+f"(d[101]), "+f"(d[102]), "+f"(d[103]), "+f"(d[104]), "+f"(d[105]), "+f"(d[106]), "+f"(d[107]), "+f"(d[108]), "+f"(d[109]), "+f"(d[110]), "+f"(d[111])
        : "l"(da), "l"(db), "r"(scale_d));
}
template <int N> __device__ __forceinline__ void fence_acc(float (&d)[N]) {
#pragma unroll
    for (int i = 0; i < N; i++) asm volatile("" : "+f"(d[i]) :: "memory");
}

__device__ __forceinline__ void bulk_s2g(void* dst, uint32_t src, uint32_t bytes) {
    asm volatile("cp.async.bulk.global.shared::cta.bulk_group [%0], [%1], %2;" :: "l"(dst), "r"(src), "r"(bytes) : "memory");
}
__device__ __forceinline__ void sts128(uint32_t addr, uint4 v) {
    asm volatile("st.shared.v4.b32 [%0], {%1, %2, %3, %4};" :: "r"(addr), "r"(v.x), "r"(v.y), "r"(v.z), "r"(v.w) : "memory");
}
__device__ __forceinline__ void sum_partials(uint32_t sb, int ti, int tj, int lane) {
    for (;;) {
        uint32_t item = 0;
        if (lane == 0) asm volatile("atom.shared.add.u32 %0, [%1], 1;" : "=r"(item) : "r"(sb + ITEM_OFF) : "memory");
        item = __shfl_sync(0xffffffffu, item, 0);
        if (item >= 8) break;
        const uint4* p = g_part + (size_t)((ti * 8 + tj) * 8) * 1024 + item * 128 + lane;
        uint4 v[4][4];
#pragma unroll
        for (int s = 0; s < 4; s++)
#pragma unroll
            for (int n = 0; n < 4; n++) v[n][s] = ldg_weak(p + s * 1024 + n * 32);
#pragma unroll
        for (int n = 0; n < 4; n++) {
            float a[8];
#pragma unroll
            for (int e = 0; e < 8; e++) a[e] = 0.f;
#pragma unroll
            for (int s = 0; s < 4; s++) {
                a[0] += bf_lo(v[n][s].x); a[1] += bf_hi(v[n][s].x); a[2] += bf_lo(v[n][s].y); a[3] += bf_hi(v[n][s].y);
                a[4] += bf_lo(v[n][s].z); a[5] += bf_hi(v[n][s].z); a[6] += bf_lo(v[n][s].w); a[7] += bf_hi(v[n][s].w);
            }
            const uint32_t d = sb + STG_OFF + (item * 8 + n * 2) * 512 + lane * 16;
            sts128(d, make_uint4(__float_as_uint(a[0]), __float_as_uint(a[1]), __float_as_uint(a[2]), __float_as_uint(a[3])));
            sts128(d + 512, make_uint4(__float_as_uint(a[4]), __float_as_uint(a[5]), __float_as_uint(a[6]), __float_as_uint(a[7])));
        }
    }
    __syncwarp();
    if (lane == 0) mbar_arrive(sb + B_HSUM);
}

#define PWAIT() mbar_wait(sb + B_EMPTY + 8 * r.slot, r.phase)
#define CWAIT() do { if (!dry) mbar_wait(sb + B_FULL + 8 * r.slot, r.phase); } while (0)
template <bool B> struct BoolTag { static constexpr bool value = B; };
struct Ring {
    int slot; uint32_t phase;
    __device__ __forceinline__ void next() { if (++slot == RING) { slot = 0; phase ^= 1; } }
};

__global__ void __launch_bounds__(384, 1)
fused_kernel(const __grid_constant__ CUtensorMap map_x, const __grid_constant__ CUtensorMap map_qkv,
             const __grid_constant__ CUtensorMap map_w1, const __grid_constant__ CUtensorMap map_w2,
             const __grid_constant__ CUtensorMap map_wo, const __grid_constant__ CUtensorMap map_w1a,
             const __grid_constant__ CUtensorMap map_o,
             const __nv_bfloat16* __restrict__ gate_w, __nv_bfloat16* __restrict__ out,
             const uint8_t* __restrict__ w1p, const uint8_t* __restrict__ w2p, const uint8_t* __restrict__ wop)
{
    extern __shared__ __align__(1024) uint8_t smem_raw[];
    const uint32_t sb = smem_u32(smem_raw);
    const int tid = threadIdx.x, warp = tid >> 5, lane = tid & 31;
    const bool dry = blockIdx.x >= 128;
    const int ti = dry ? (int)(blockIdx.x & 1) * 2 : blockIdx.x >> 3, tj = blockIdx.x & 7;
    if (dry && warp >= 8) {
        asm volatile("setmaxnreg.dec.sync.aligned.u32 88;");
        return;
    }

    if (tid == 0 && !dry) { TSG(31); TSX(0); }
    if (tid == 320) {
        asm volatile("prefetch.tensormap [%0];" :: "l"(&map_x) : "memory");
        asm volatile("prefetch.tensormap [%0];" :: "l"(&map_qkv) : "memory");
        asm volatile("prefetch.tensormap [%0];" :: "l"(&map_w1) : "memory");
        asm volatile("prefetch.tensormap [%0];" :: "l"(&map_w1a) : "memory");
        asm volatile("prefetch.tensormap [%0];" :: "l"(&map_w2) : "memory");
        asm volatile("prefetch.tensormap [%0];" :: "l"(&map_wo) : "memory");
        asm volatile("prefetch.tensormap [%0];" :: "l"(&map_o) : "memory");
    }
    uint32_t gwv[N_QKV / 2];
    if (warp == 8) {
        const unsigned short* gws = reinterpret_cast<const unsigned short*>(gate_w);
#pragma unroll
        for (int n = 0; n < N_QKV / 2; n++) gwv[n] = (uint32_t)__ldg(gws + 64 * n + lane) | ((uint32_t)__ldg(gws + 64 * n + 32 + lane) << 16);
    }
    if (tid == 256) {
        for (int s = 0; s < RING; s++) { mbar_init(sb + B_FULL + 8 * s, 1); mbar_init(sb + B_EMPTY + 8 * s, 8); }
        for (int s = 0; s < 8; s++) mbar_init(sb + B_XFULL + 8 * s, 1);
        mbar_init(sb + B_HDEAD, 8); mbar_init(sb + B_EREADY, 1); mbar_init(sb + B_KVDONE, 8); mbar_init(sb + B_KVREADY, 1);
        mbar_init(sb + B_ODONE, 8); mbar_init(sb + B_WOFULL, 1); mbar_init(sb + B_HSUM, 3);
        mbar_init(sb + B_PREADY, 1); mbar_init(sb + B_SF, 1); mbar_init(sb + B_SF + 8, 1);
        for (int s = 0; s < 4; s++) mbar_init(sb + B_SQ + 8 * s, 8);
        asm volatile("st.shared.u32 [%0], %1;" :: "r"(sb + ITEM_OFF), "r"(0) : "memory");
        asm volatile("fence.mbarrier_init.release.cluster;" ::: "memory");
        fence_async_smem();
        mbar_expect_tx(sb + B_XFULL, 16384);
        tma_2d(sb + X_OFF, &map_x, sb + B_XFULL, 0, ti * 128);
        mbar_expect_only(sb + B_FULL, 12288);
        tma_4d(sb + RING_OFF, &map_qkv, sb + B_FULL, 0, 0, tj, 0);
    }
    if (!dry) __syncthreads();

    if (warp >= 8) {
        asm volatile("setmaxnreg.dec.sync.aligned.u32 88;");
        if (warp == 8) {
            Ring r{0, 1};
            const bool leader = elect_one();
#pragma unroll
            for (int n = 0; n < N_QKV; n++) {
                const uint32_t full = sb + B_FULL + 8 * r.slot, dst = sb + RING_OFF + r.slot * SLOT;
                if (n > 0) {
                    if (!(n & 1) && leader) {
                        mbar_expect_tx(sb + B_XFULL + 8 * (n >> 1), 16384);
                        tma_2d(sb + X_OFF + (n >> 1) * 16384, &map_x, sb + B_XFULL + 8 * (n >> 1), (n >> 1) * 64, ti * 128);
                    }
                    if (n >= RING) PWAIT();
                    if (leader) {
                        mbar_expect_only(full, 12288);
                        tma_4d(dst, &map_qkv, full, 0, 32 * n, tj, 0);
                    }
                }
                const uint32_t gv = (n & 1) ? (gwv[n >> 1] >> 16) : (gwv[n >> 1] & 0xFFFFu);
                asm volatile("st.shared.v4.b32 [%0], {%1, %2, %2, %2};" :: "r"(dst + 12288 + lane * 128 + ((lane & 7) << 4)), "r"(gv), "r"(0) : "memory");
                fence_async_smem();
                __syncwarp();
                if (leader) mbar_arrive(full);
                r.next();
            }
#pragma unroll 1
            for (int n = 0; n < N_FFN1; n++) {
                const uint32_t full = sb + B_FULL + 8 * r.slot, dst = sb + RING_OFF + r.slot * SLOT;
                PWAIT();
                if (leader) {
                    mbar_expect_tx(full, 16384);
                    tma_4d(dst, &map_w1a, full, 0, 32 * n, 0, tj);
                    tma_2d(dst + 3 * 4096, &map_w1, full, 224 * tj + 192, 32 * n);
                }
                r.next();
            }
            {
                int q = 0, rr = 0;
#pragma unroll 1
                for (int n = 0; n < N_FFN2; n++) {
                    const uint32_t full = sb + B_FULL + 8 * r.slot, dst = sb + RING_OFF + r.slot * SLOT;
                    PWAIT();
                    if (leader) mbar_expect_tx(full, 16384);
#pragma unroll
                    for (int h = 0; h < 2; h++) {
                        if (leader) tma_3d(dst + h * 8192, &map_w2, full, 0, 224 * tj + 32 * rr, 2 * q);
                        if (++rr == 7) { rr = 0; q++; }
                    }
                    r.next();
                }
            }
            mbar_wait(sb + B_KVREADY, 0);
            asm volatile("fence.proxy.async.global;" ::: "memory");
            {
                const int bbase = 8 * ti - 16, b0 = bbase < 0 ? 0 : bbase;
                const uint32_t bytes = (uint32_t)(8 * ti + 8 - b0) * 512;
#pragma unroll 1
                for (int m = 0; m < N_KV; m++) {
                    const uint32_t full = sb + B_FULL + 8 * r.slot, dst = sb + RING_OFF + r.slot * SLOT;
                    if (m == RING) {
                        mbar_wait(sb + B_HDEAD, 0);
                        if (leader) {
                            mbar_expect_tx(sb + B_WOFULL, 65536);
#pragma unroll
                            for (int e = 0; e < 2; e++) tma_2d(sb + X_OFF + e * 32768, &map_wo, sb + B_WOFULL, 64 * tj, 256 * e);
                        }
                    }
                    PWAIT();
                    if (leader) {
                        const uint4* src = ((m & 1) ? g_vf : g_kf) + ((tj * 4 + (m >> 1)) * 128 + b0) * 32;
                        mbar_expect_tx(full, bytes);
                        bulk_g2s(dst + (b0 - bbase) * 512, src, bytes, full);
                    }
                    r.next();
                }
            }
            {
                mbar_wait(sb + B_EREADY, 0);
                unsigned epoch; asm volatile("ld.shared.u32 %0, [%1];" : "=r"(epoch) : "r"(sb + EPOCH_OFF) : "memory");
                mbar_wait(sb + B_ODONE, 0);
                if (lane < 8) wait_counter(&g_ocnt[(ti * 8 + lane) * 32], 8 * (epoch + 1));
                __syncwarp();
                asm volatile("fence.proxy.async.global;" ::: "memory");
#pragma unroll 1
                for (int m = 0; m < N_O; m++) {
                    const uint32_t full = sb + B_FULL + 8 * r.slot, dst = sb + RING_OFF + r.slot * SLOT;
                    PWAIT();
                    if (leader) {
                        mbar_expect_tx(full, 16384);
                        tma_2d(dst, &map_o, full, 64 * ((tj + m) & 7), ti * 128);
                    }
                    r.next();
                }
            }
        } else if (warp == 9) {
            unsigned epoch = 0;
            if (lane == 0) {
                epoch = atomicAdd(&g_ticket, 1u) >> 7;
                asm volatile("st.shared.u32 [%0], %1;" :: "r"(sb + EPOCH_OFF), "r"(epoch) : "memory");
                mbar_arrive(sb + B_EREADY);
                mbar_wait(sb + B_XFULL + 8 * PF1_AT, 0);
                prefetch_l2(w1p + (size_t)blockIdx.x * 14336, 14336);
                mbar_wait(sb + B_XFULL + 8 * PF2_AT, 0);
                prefetch_l2(w2p + (size_t)blockIdx.x * 14336, 14336);
                prefetch_l2(wop + (size_t)blockIdx.x * 4096, 4096);
                mbar_wait(sb + B_KVDONE, 0);
                red_release(&g_kvcnt[blockIdx.x * 32], 1u);
            }
            epoch = __shfl_sync(0xffffffffu, epoch, 0);
            if (lane < 3 && ti - lane >= 0) wait_counter(&g_kvcnt[((ti - lane) * 8 + tj) * 32], epoch + 1);
            __syncwarp();
            if (lane == 0) mbar_arrive(sb + B_KVREADY);
            mbar_wait(sb + B_SQ + 24, 0);
            if (lane < 8) wait_counter(&g_pcnt[(ti * 8 + lane) * 32], epoch + 1);
            __syncwarp();
            if (lane == 0) { mbar_arrive(sb + B_PREADY); TSX(13); }
            sum_partials(sb, ti, tj, lane);
            if (lane == 0) TSX(14);
        } else {
            if (warp == 10) {
#pragma unroll 1
                for (int q = 0; q < 4; q++) {
                    mbar_wait(sb + B_SQ + 8 * q, 0);
                    if (lane < 16) {
                        uint4* d = g_part + (size_t)(((ti * 8 + 2 * q + (lane & 1)) * 8 + tj) * 8 + (lane >> 1)) * 128;
                        bulk_s2g(d, sb + STG_OFF + (q & 1) * 32768 + lane * 2048, 2048);
                        asm volatile("cp.async.bulk.commit_group;" ::: "memory");
                        if (q < 2) asm volatile("cp.async.bulk.wait_group.read 0;" ::: "memory");
                    }
                    __syncwarp();
                    if (q < 2 && lane == 0) mbar_arrive(sb + B_SF + 8 * q);
                }
                asm volatile("cp.async.bulk.wait_group 0;" ::: "memory");
                asm volatile("fence.proxy.async.global;" ::: "memory");
                __syncwarp();
                if (lane == 0) { red_release(&g_pcnt[blockIdx.x * 32], 1u); TSX(12); }
            }
            mbar_wait(sb + B_PREADY, 0);
            sum_partials(sb, ti, tj, lane);
        }
    } else {
        asm volatile("setmaxnreg.inc.sync.aligned.u32 208;");
        const int wg = warp >> 2, g = lane >> 2, c = lane & 3;
        const uint32_t xa = sb + X_OFF + wg * 8192;
        Ring r{0, 0};
        const bool lane0 = lane == 0 && !dry;
        uint32_t qf[4][4];
        float g0, g1;
        TS(9);
        {
            float acc[100];
            int prev = 0;
            if (wg == 1) asm volatile("bar.sync 3, 256;" ::: "memory");
            for (int s = 0; s < (dry ? 4 : N_QKV); s++) {
                if (!(s & 1) && !dry) mbar_wait(sb + B_XFULL + 8 * (s >> 1), 0);
                CWAIT();
                if (s == 0) TS(1);
                if (s == 2) TS(28);
                if (s == 6) TS(29);
                if (s == 10) TS(20);
                const uint32_t bs = sb + RING_OFF + r.slot * SLOT, as = xa + (s >> 1) * 16384 + (s & 1) * 64;
                wgmma_fence();
                wgmma_ss_n200(acc, desc_a(as), desc_b(bs), s);
                wgmma_ss_n200(acc, desc_a(as + 32), desc_b(bs + 2048), 1);
                wgmma_commit();
                if (wg == 0 && s == LEAD1) asm volatile("bar.arrive 3, 256;" ::: "memory");
                if (s > 0) { wgmma_wait<1>(); if (lane0) mbar_arrive(sb + B_EMPTY + 8 * prev); }
                prev = r.slot; r.next();
            }
            wgmma_wait<0>();
            fence_acc(acc);
            if (lane0) mbar_arrive(sb + B_EMPTY + 8 * prev);
            TS(2);
            const int blk = ti * 8 + warp;
#pragma unroll
            for (int hh = 0; hh < 4; hh++) {
                const float* t0 = &acc[8 * hh]; const float* t1 = &acc[8 * hh + 4];
                qf[hh][0] = pack_bf16(t0[0], t0[1]); qf[hh][1] = pack_bf16(t0[2], t0[3]);
                qf[hh][2] = pack_bf16(t1[0], t1[1]); qf[hh][3] = pack_bf16(t1[2], t1[3]);
                const float* k0 = &acc[32 + 8 * hh]; const float* k1 = &acc[32 + 8 * hh + 4];
                uint4 kv;
                kv.x = pack_bf16(k0[0], k0[1]); kv.y = pack_bf16(k1[0], k1[1]);
                kv.z = pack_bf16(k0[2], k0[3]); kv.w = pack_bf16(k1[2], k1[3]);
                if (!dry) g_kf[((tj * 4 + hh) * 128 + blk) * 32 + lane] = kv;
                const float* v0 = &acc[64 + 8 * hh]; const float* v1 = &acc[64 + 8 * hh + 4];
                uint4 vv;
                vv.x = movmatrix(pack_bf16(v0[0], v0[1])); vv.y = movmatrix(pack_bf16(v0[2], v0[3]));
                vv.z = movmatrix(pack_bf16(v1[0], v1[1])); vv.w = movmatrix(pack_bf16(v1[2], v1[3]));
                if (!dry) g_vf[((tj * 4 + hh) * 128 + blk) * 32 + lane] = vv;
            }
            __syncwarp();
            if (lane0) mbar_arrive(sb + B_KVDONE);
            const float z0 = __shfl_sync(0xffffffffu, acc[96], lane & ~3), z1 = __shfl_sync(0xffffffffu, acc[98], lane & ~3);
            g0 = 1.f / (1.f + __expf(-z0)); g1 = 1.f / (1.f + __expf(-z1));
        }
        TS(3);
        const int wrow = (warp & 3) * 16;
        {
            float acc[112];
            int prev = 0;
            for (int s = 0; s < (dry ? 4 : N_FFN1); s++) {
                CWAIT();
                const uint32_t bs = sb + RING_OFF + r.slot * SLOT, as = xa + (s >> 1) * 16384 + (s & 1) * 64;
                wgmma_fence();
                wgmma_ss_n224(acc, desc_a(as), desc_b(bs), s);
                wgmma_ss_n224(acc, desc_a(as + 32), desc_b(bs + 2048), 1);
                wgmma_commit();
                if (s > 0) { wgmma_wait<1>(); if (lane0) mbar_arrive(sb + B_EMPTY + 8 * prev); }
                prev = r.slot; r.next();
            }
            wgmma_wait<0>();
            fence_acc(acc);
            if (lane0) mbar_arrive(sb + B_EMPTY + 8 * prev);
            TS(4);
            const float s0 = 1.f - g0, s1 = 1.f - g1;
            asm volatile("bar.sync %0, 128;" :: "r"(1 + wg) : "memory");
            const uint32_t strow = xa + (wrow + ((lane >> 3) & 1) * 8 + (lane & 7)) * 128;
#pragma unroll
            for (int p = 0; p < 14; p++) {
                const int nt = 2 * p + (lane >> 4);
                const float* a = &acc[8 * p];
                stmatrix_x4(strow + (p >> 2) * 16384 + (((nt & 7) ^ (lane & 7)) << 4),
                            pack_bf16_relu(a[0] * s0, a[1] * s0), pack_bf16_relu(a[2] * s1, a[3] * s1),
                            pack_bf16_relu(a[4] * s0, a[5] * s0), pack_bf16_relu(a[6] * s1, a[7] * s1));
            }
        }
        TS(5);
        {
            fence_async_smem();
            asm volatile("bar.sync 4, 256;" ::: "memory");
            float accA[64], accB[64];
            auto epilogue = [&](float (&acc)[64], int q) {
                fence_acc(acc);
                const uint32_t st = sb + STG_OFF + (q & 1) * 32768 + warp * 4096;
                if (q >= 2 && !dry) mbar_wait(sb + B_SF + 8 * (q & 1), 0);
#pragma unroll
                for (int t2 = 0; t2 < 8; t2++) {
                    uint4 v;
                    v.x = pack_bf16(acc[8 * t2 + 0], acc[8 * t2 + 1]); v.y = pack_bf16(acc[8 * t2 + 2], acc[8 * t2 + 3]);
                    v.z = pack_bf16(acc[8 * t2 + 4], acc[8 * t2 + 5]); v.w = pack_bf16(acc[8 * t2 + 6], acc[8 * t2 + 7]);
                    sts128(st + t2 * 512 + lane * 16, v);
                }
                fence_async_smem();
                __syncwarp();
                if (lane0) mbar_arrive(sb + B_SQ + 8 * q);
            };
            int rel = r.slot;
#pragma unroll
            for (int m = 0; m < N_FFN2; m++) {
                CWAIT();
                wgmma_fence();
#pragma unroll
                for (int h = 0; h < 2; h++) {
                    const int u = 2 * m + h, q = u / 7, rr = u % 7;
                    const uint32_t bs = sb + RING_OFF + r.slot * SLOT + h * 8192;
                    const uint32_t as = xa + (rr >> 1) * 16384 + (rr & 1) * 64;
                    if (!(q & 1)) {
                        wgmma_ss_n128(accA, desc_a(as), desc_b(bs), rr);
                        wgmma_ss_n128(accA, desc_a(as + 32), desc_b(bs + 2048), 1);
                    } else {
                        wgmma_ss_n128(accB, desc_a(as), desc_b(bs), rr);
                        wgmma_ss_n128(accB, desc_a(as + 32), desc_b(bs + 2048), 1);
                    }
                }
                wgmma_commit();
                r.next();
                wgmma_wait<1>();
                if (m > 0) {
                    if (lane0) mbar_arrive(sb + B_EMPTY + 8 * rel);
                    if (++rel == RING) rel = 0;
                }
                if (m == 4) { TS(25); epilogue(accA, 0); }
                if (m == 7) { TS(26); epilogue(accB, 1); }
                if (m == 11) { TS(27); epilogue(accA, 2); }
            }
            wgmma_wait<0>();
            if (lane0) { mbar_arrive(sb + B_EMPTY + 8 * rel); mbar_arrive(sb + B_HDEAD); }
            epilogue(accB, 3);
        }
        TS(6);
        {
            const float SC = 0.25f * 1.4426950408889634f;
            const int gb0 = 8 * ti - 16 + warp;
            int slotK = 0, slotV = 0;
            uint32_t* odst = reinterpret_cast<uint32_t*>(g_o + (size_t)(ti * 128 + warp * 16 + g) * 512 + tj * 64 + ((lane & 1) ? 8 : 0) + (lane & 2) * 2);
#define NHEADS (dry ? 2 : 4)
#define ATT_KWAIT(kb) do { slotK = r.slot; CWAIT(); kb = sb + RING_OFF + slotK * SLOT + warp * 512 + lane * 16; r.next(); } while (0)
#define ATT_VWAIT(vb) do { slotV = r.slot; CWAIT(); vb = sb + RING_OFF + slotV * SLOT + warp * 512 + lane * 16; r.next(); TS(21 + hh); } while (0)
#define ATT_KREL() do { __syncwarp(); if (lane0) mbar_arrive(sb + B_EMPTY + 8 * slotK); } while (0)
#define ATT_VREL() do { __syncwarp(); if (lane0) mbar_arrive(sb + B_EMPTY + 8 * slotV); } while (0)
#define ATT_NEXTQ(h) do { \
                if ((h) == 1) { q0 = qf[1][0]; q1 = qf[1][1]; q2 = qf[1][2]; q3 = qf[1][3]; } \
                else if ((h) == 2) { q0 = qf[2][0]; q1 = qf[2][1]; q2 = qf[2][2]; q3 = qf[2][3]; } \
                else { q0 = qf[3][0]; q1 = qf[3][1]; q2 = qf[3][2]; q3 = qf[3][3]; } } while (0)
#define ATT_STORE(h, r0, r1, r2, r3) do { \
                const bool odd = lane & 1; \
                const uint32_t sl = __shfl_xor_sync(0xffffffffu, odd ? (r0) : (r2), 1), sh = __shfl_xor_sync(0xffffffffu, odd ? (r1) : (r3), 1); \
                if (!dry) *reinterpret_cast<uint2*>(odst + 8 * (h)) = odd ? make_uint2(sl, r2) : make_uint2(r0, sl); \
                if (!dry) *reinterpret_cast<uint2*>(odst + 8 * (h) + 8 * 256) = odd ? make_uint2(sh, r3) : make_uint2(r1, sh); \
                } while (0)
            auto attention = [&](auto masked_tag) {
            constexpr bool MASKED = decltype(masked_tag)::value;
            const float NEG = -INFINITY;
            const uint32_t ONES = 0x3F803F80u;
            float sa[8][2][4], sb2[8][2][4];
            float o[2][4], ls[4];
            float m0, m1;
            uint32_t q0 = qf[0][0], q1 = qf[0][1], q2 = qf[0][2], q3 = qf[0][3];
            auto qk = [&](float (&s)[8][2][4], int ps, int t, uint32_t kbase) {
                if (ps == 0 && t == 0) {
                    const uint4 kd = lds128(kbase + 16 * 512);
                    const uint4 kf = lds128(kbase);
                    float f[2][4];
                    const float ci = (!MASKED || opaque(gb0) >= 0) ? 0.f : NEG;
                    mma16816_c(s[0][0], q0, q1, q2, q3, kd.x, kd.y, 0.f);
                    mma16816_c(s[0][1], q0, q1, q2, q3, kd.z, kd.w, 0.f);
                    mma16816_c(f[0], q0, q1, q2, q3, kf.x, kf.y, ci);
                    mma16816_c(f[1], q0, q1, q2, q3, kf.z, kf.w, ci);
#pragma unroll
                    for (int u = 0; u < 2; u++)
#pragma unroll
                        for (int e = 0; e < 4; e++) {
                            const int row = g + 8 * (e >> 1), col = 8 * u + 2 * c + (e & 1);
                            s[0][u][e] = (col > row) ? f[u][e] : s[0][u][e];
                        }
                } else {
                    const uint4 kf = lds128(kbase + (8 * ps + t) * 512);
                    const float ci = (!MASKED || opaque(gb0) + 8 * ps + t >= 0) ? 0.f : NEG;
                    mma16816_c(s[t][0], q0, q1, q2, q3, kf.x, kf.y, ci);
                    mma16816_c(s[t][1], q0, q1, q2, q3, kf.z, kf.w, ci);
                }
            };
            auto rowmax = [&](float (&s)[8][2][4], float b0, float b1, float& n0, float& n1) {
                int i0 = __float_as_int(b0), i1 = __float_as_int(b1);
#pragma unroll
                for (int t = 0; t < 8; t++)
#pragma unroll
                    for (int u = 0; u < 2; u++) {
                        i0 = __vimax3_s32(i0, __float_as_int(s[t][u][0]), __float_as_int(s[t][u][1]));
                        i1 = __vimax3_s32(i1, __float_as_int(s[t][u][2]), __float_as_int(s[t][u][3]));
                    }
                i0 = max(i0, __shfl_xor_sync(0xffffffffu, i0, 1)); i1 = max(i1, __shfl_xor_sync(0xffffffffu, i1, 1));
                i0 = max(i0, __shfl_xor_sync(0xffffffffu, i0, 2)); i1 = max(i1, __shfl_xor_sync(0xffffffffu, i1, 2));
                n0 = __int_as_float(i0); n1 = __int_as_float(i1);
                if (__any_sync(0xffffffffu, (i0 | i1) < 0)) {
                    asm volatile("" ::: "memory");
                    n0 = b0; n1 = b1;
#pragma unroll
                    for (int t = 0; t < 8; t++)
#pragma unroll
                        for (int u = 0; u < 2; u++) {
                            n0 = fmaxf(n0, fmaxf(s[t][u][0], s[t][u][1]));
                            n1 = fmaxf(n1, fmaxf(s[t][u][2], s[t][u][3]));
                        }
                    n0 = fmaxf(n0, __shfl_xor_sync(0xffffffffu, n0, 1)); n1 = fmaxf(n1, __shfl_xor_sync(0xffffffffu, n1, 1));
                    n0 = fmaxf(n0, __shfl_xor_sync(0xffffffffu, n0, 2)); n1 = fmaxf(n1, __shfl_xor_sync(0xffffffffu, n1, 2));
                }
            };
            auto pv = [&](const float (&p)[2][4], uint32_t vaddr) {
                const uint4 vf = lds128(vaddr);
                const uint32_t a0 = pack_bf16(p[0][0], p[0][1]), a1 = pack_bf16(p[0][2], p[0][3]);
                const uint32_t a2 = pack_bf16(p[1][0], p[1][1]), a3 = pack_bf16(p[1][2], p[1][3]);
                mma16816(o[0], a0, a1, a2, a3, vf.x, vf.y);
                mma16816(o[1], a0, a1, a2, a3, vf.z, vf.w);
                mma16816(ls, a0, a1, a2, a3, ONES, ONES);
            };
            auto expv = [&](float (&s)[8][2][4], int ps, int t, float mc0, float mc1, uint32_t vbase) {
                float p[2][4];
#pragma unroll
                for (int u = 0; u < 2; u++) {
                    p[u][0] = ex2(fmaf(s[t][u][0], SC, -mc0)); p[u][1] = ex2(fmaf(s[t][u][1], SC, -mc0));
                    p[u][2] = ex2(fmaf(s[t][u][2], SC, -mc1)); p[u][3] = ex2(fmaf(s[t][u][3], SC, -mc1));
                }
                if (ps == 0 && t == 0) {
                    float pd[2][4], pf[2][4];
#pragma unroll
                    for (int u = 0; u < 2; u++)
#pragma unroll
                        for (int e = 0; e < 4; e++) {
                            const int row = g + 8 * (e >> 1), col = 8 * u + 2 * c + (e & 1);
                            pf[u][e] = (col > row) ? p[u][e] : 0.f;
                            pd[u][e] = (col > row) ? 0.f : p[u][e];
                        }
                    pv(pd, vbase + 16 * 512);
                    pv(pf, vbase);
                } else {
                    pv(p, vbase + (8 * ps + t) * 512);
                }
            };
            uint32_t kbase, vbase;
            ATT_KWAIT(kbase);
#pragma unroll
            for (int t = 0; t < 8; t++) qk(sa, 0, t, kbase);
            rowmax(sa, NEG, NEG, m0, m1);
#pragma unroll 1
            for (int hh = 0; hh < NHEADS; hh++) {
                ATT_VWAIT(vbase);
#pragma unroll
                for (int e = 0; e < 4; e++) { o[0][e] = 0.f; o[1][e] = 0.f; ls[e] = 0.f; }
                {
                    const float mc0 = m0 * SC, mc1 = m1 * SC;
#pragma unroll
                    for (int t = 0; t < 8; t++) { qk(sb2, 1, t, kbase); expv(sa, 0, t, mc0, mc1, vbase); }
                    ATT_KREL();
                    float n0, n1;
                    rowmax(sb2, m0, m1, n0, n1);
                    const float a0 = ex2((m0 - n0) * SC), a1 = ex2((m1 - n1) * SC);
                    ls[0] *= a0; ls[2] *= a1;
                    o[0][0] *= a0; o[0][1] *= a0; o[1][0] *= a0; o[1][1] *= a0;
                    o[0][2] *= a1; o[0][3] *= a1; o[1][2] *= a1; o[1][3] *= a1;
                    m0 = n0; m1 = n1;
                }
                {
                    const float mc0 = m0 * SC, mc1 = m1 * SC;
                    const bool more = hh + 1 < NHEADS;
                    if (more) {
                        ATT_KWAIT(kbase);
                        ATT_NEXTQ(hh + 1);
#pragma unroll
                        for (int t = 0; t < 8; t++) { qk(sa, 0, t, kbase); expv(sb2, 1, t, mc0, mc1, vbase); }
                        rowmax(sa, NEG, NEG, m0, m1);
                    } else {
#pragma unroll
                        for (int t = 0; t < 8; t++) expv(sb2, 1, t, mc0, mc1, vbase);
                    }
                    ATT_VREL();
                }
                const float f0 = __fdividef(g0, ls[0]), f1 = __fdividef(g1, ls[2]);
                ATT_STORE(hh, pack_bf16(o[0][0] * f0, o[0][1] * f0), pack_bf16(o[0][2] * f1, o[0][3] * f1),
                              pack_bf16(o[1][0] * f0, o[1][1] * f0), pack_bf16(o[1][2] * f1, o[1][3] * f1));
            }
            };
            if (ti >= 2) attention(BoolTag<false>{}); else attention(BoolTag<true>{});
            __syncwarp();
            if (lane0) { mbar_arrive(sb + B_ODONE); red_release(&g_ocnt[blockIdx.x * 32], 1u); }
        }
        TS(7);
        {
            float acc[32];
            uint4 pv[4][4];
            if (!dry) mbar_wait(sb + B_PREADY, 0);
            {
                const uint4* p = g_part + (size_t)((ti * 8 + tj) * 8 + 4) * 1024 + warp * 128 + lane;
#pragma unroll
                for (int s = 0; s < 4; s++)
#pragma unroll
                    for (int n = 0; n < 4; n++) pv[n][s] = dry ? make_uint4(0u, 0u, 0u, 0u) : ldg_weak(p + s * 1024 + n * 32);
            }
            if (!dry) mbar_wait(sb + B_WOFULL, 0);
            if (!dry) mbar_wait(sb + B_ODONE, 0);
            TS(15);
            int prev = 0;
#pragma unroll 1
            for (int m = 0; m < N_O; m++) {
                CWAIT();
                if (m == 0) TS(16);
                const uint32_t as = sb + RING_OFF + r.slot * SLOT + wg * 8192;
                const uint32_t bs = sb + X_OFF + ((tj + m) & 7) * 8192;
                wgmma_fence();
#pragma unroll
                for (int k = 0; k < 4; k++) wgmma_ss_n64(acc, desc_a(as + 32 * k), desc_b(bs + 2048 * k), m | k);
                wgmma_commit();
                if (m > 0) { wgmma_wait<1>(); if (lane0) mbar_arrive(sb + B_EMPTY + 8 * prev); }
                prev = r.slot; r.next();
            }
            wgmma_wait<0>();
            fence_acc(acc);
            TS(17);
            if (!dry) mbar_wait(sb + B_HSUM, 0);
#pragma unroll
            for (int n = 0; n < 4; n++) {
                const uint4 u0 = lds128(sb + STG_OFF + (warp * 8 + 2 * n) * 512 + lane * 16), u1 = lds128(sb + STG_OFF + (warp * 8 + 2 * n + 1) * 512 + lane * 16);
                float* a = &acc[8 * n];
                a[0] += __uint_as_float(u0.x); a[1] += __uint_as_float(u0.y); a[2] += __uint_as_float(u0.z); a[3] += __uint_as_float(u0.w);
                a[4] += __uint_as_float(u1.x); a[5] += __uint_as_float(u1.y); a[6] += __uint_as_float(u1.z); a[7] += __uint_as_float(u1.w);
#pragma unroll
                for (int s = 0; s < 4; s++) {
                    a[0] += bf_lo(pv[n][s].x); a[1] += bf_hi(pv[n][s].x); a[2] += bf_lo(pv[n][s].y); a[3] += bf_hi(pv[n][s].y);
                    a[4] += bf_lo(pv[n][s].z); a[5] += bf_hi(pv[n][s].z); a[6] += bf_lo(pv[n][s].w); a[7] += bf_hi(pv[n][s].w);
                }
            }
            __nv_bfloat16* o = out + (size_t)(ti * 128 + warp * 16 + g) * 512 + tj * 64 + ((lane & 1) ? 8 : 0) + (lane & 2) * 2;
            const bool odd = lane & 1;
#pragma unroll
            for (int t2 = 0; t2 < 4; t2++) {
                const uint32_t lo0 = pack_bf16(acc[8 * t2 + 0], acc[8 * t2 + 1]), hi0 = pack_bf16(acc[8 * t2 + 2], acc[8 * t2 + 3]);
                const uint32_t lo1 = pack_bf16(acc[8 * t2 + 4], acc[8 * t2 + 5]), hi1 = pack_bf16(acc[8 * t2 + 6], acc[8 * t2 + 7]);
                const uint32_t sl = __shfl_xor_sync(0xffffffffu, odd ? lo0 : lo1, 1), sh = __shfl_xor_sync(0xffffffffu, odd ? hi0 : hi1, 1);
                if (!dry) *reinterpret_cast<uint2*>(o + 16 * t2) = odd ? make_uint2(sl, lo1) : make_uint2(lo0, sl);
                if (!dry) *reinterpret_cast<uint2*>(o + 16 * t2 + 8 * 512) = odd ? make_uint2(sh, hi1) : make_uint2(hi0, sh);
            }
            if (tid == 0 && !dry) TSG(30);
        }
        TS(8);
    }
}

typedef CUresult (*PFN_encodeTiled)(CUtensorMap*, CUtensorMapDataType, cuuint32_t, void*, const cuuint64_t*, const cuuint64_t*,
                                    const cuuint32_t*, const cuuint32_t*, CUtensorMapInterleave, CUtensorMapSwizzle,
                                    CUtensorMapL2promotion, CUtensorMapFloatOOBfill);

void make_map(PFN_encodeTiled enc, CUtensorMap* m, const void* base, int rank, const cuuint64_t* dims, const cuuint64_t* strides, const cuuint32_t* box) {
    cuuint32_t es[5] = {1, 1, 1, 1, 1};
    enc(m, CU_TENSOR_MAP_DATA_TYPE_BFLOAT16, (cuuint32_t)rank, const_cast<void*>(base), dims, strides, box, es,
        CU_TENSOR_MAP_INTERLEAVE_NONE, CU_TENSOR_MAP_SWIZZLE_128B, CU_TENSOR_MAP_L2_PROMOTION_L2_256B, CU_TENSOR_MAP_FLOAT_OOB_FILL_NONE);
}

}

extern "C" void kernel_launch(void* const* d_in, const int* in_sizes, int n_in, void* d_out, int out_size) {
    (void)in_sizes; (void)n_in; (void)out_size;
    const void* x = d_in[0]; const void* wqkv = d_in[1]; const void* wo = d_in[2];
    const void* w1 = d_in[4]; const void* w2 = d_in[5]; const void* gate_w = d_in[6];
    static PFN_encodeTiled enc = nullptr;
    if (!enc) {
        void* fn = nullptr; cudaDriverEntryPointQueryResult st;
        cudaGetDriverEntryPoint("cuTensorMapEncodeTiled", &fn, cudaEnableDefault, &st);
        enc = (PFN_encodeTiled)fn;
        cudaFuncSetAttribute(fused_kernel, cudaFuncAttributeMaxDynamicSharedMemorySize, SMEM_BYTES);
    }
    CUtensorMap mx, mqkv, mw1, mw2, mwo, mw1a, mo;
    void* optr = nullptr;
    cudaGetSymbolAddress(&optr, g_o);
    { cuuint64_t d[2] = {512, 2048}, s[1] = {1024}; cuuint32_t b[2] = {64, 128}; make_map(enc, &mo, optr, 2, d, s, b); }
    { cuuint64_t d[4] = {64, 512, 3, 8}, s[3] = {3584, 128, 448}; cuuint32_t b[4] = {64, 32, 3, 1}; make_map(enc, &mw1a, w1, 4, d, s, b); }
    { cuuint64_t d[2] = {512, 2048}, s[1] = {1024}; cuuint32_t b[2] = {64, 128}; make_map(enc, &mx, x, 2, d, s, b); }
    { cuuint64_t d[4] = {64, 512, 8, 3}, s[3] = {3072, 128, 1024}; cuuint32_t b[4] = {64, 32, 1, 3}; make_map(enc, &mqkv, wqkv, 4, d, s, b); }
    { cuuint64_t d[2] = {1792, 512}, s[1] = {3584}; cuuint32_t b[2] = {64, 32}; make_map(enc, &mw1, w1, 2, d, s, b); }
    { cuuint64_t d[3] = {64, 1792, 8}, s[2] = {1024, 128}; cuuint32_t b[3] = {64, 32, 2}; make_map(enc, &mw2, w2, 3, d, s, b); }
    { cuuint64_t d[2] = {512, 512}, s[1] = {1024}; cuuint32_t b[2] = {64, 256}; make_map(enc, &mwo, wo, 2, d, s, b); }
    fused_kernel<<<NCTA, 384, SMEM_BYTES, cudaStreamPerThread>>>(mx, mqkv, mw1, mw2, mwo, mw1a, mo, (const __nv_bfloat16*)gate_w, (__nv_bfloat16*)d_out,
                                           (const uint8_t*)w1, (const uint8_t*)w2, (const uint8_t*)wo);
}
```

```cpp
#include <cuda_runtime.h>
#include <cuda_bf16.h>
#include <cuda.h>
#include <stdint.h>

namespace {

#define PF1_AT 1
#define PF2_AT 5
#define LEAD1 2
#define NCTA 132
constexpr int RING = 6;
constexpr int SLOT = 16384;
constexpr uint32_t X_OFF = 0;
constexpr uint32_t STG_OFF = X_OFF + 4 * 16384;
constexpr uint32_t RING_OFF = 131072;
constexpr uint32_t BAR_OFF = RING_OFF + RING * SLOT;
constexpr uint32_t B_FULL = BAR_OFF, B_EMPTY = BAR_OFF + 64, B_XFULL = BAR_OFF + 128, B_HDEAD = BAR_OFF + 192,
                   B_EREADY = BAR_OFF + 200, B_KVDONE = BAR_OFF + 208, B_ODONE = BAR_OFF + 224,
                   B_KVREADY = BAR_OFF + 232, B_WOFULL = BAR_OFF + 240, B_HSUM = BAR_OFF + 248, B_PREADY = BAR_OFF + 264,
                   B_SQ = BAR_OFF + 272, B_SF = BAR_OFF + 304;
constexpr uint32_t EPOCH_OFF = BAR_OFF + 256, ITEM_OFF = BAR_OFF + 260, OSRC_OFF = BAR_OFF + 384;
constexpr uint32_t OWN_OFF = X_OFF + 6 * 16384;
constexpr uint32_t SMEM_BYTES = BAR_OFF + 1024;

constexpr int N_QKV = 16, N_FFN1 = 16, N_FFN2 = 14, N_KV = 8, N_O = 7;

__device__ uint4 g_kf[32 * 128 * 32];
__device__ uint4 g_vf[32 * 128 * 32];
__device__ uint4 g_part[16 * 8 * 8 * 8 * 4 * 32];
__device__ __nv_bfloat16 g_o[2048 * 512];
__device__ unsigned g_ticket;
__device__ unsigned g_kvcnt[128 * 32];
__device__ unsigned g_pcnt[128 * 32];
__device__ unsigned g_ocnt[128 * 32];
#define TS(k) do {} while (0)
#define TS2(k) do {} while (0)
#define TS2X(k) do {} while (0)
#define TSX(k) do {} while (0)
#define TSG(k) do {} while (0)

__device__ __forceinline__ uint32_t smem_u32(const void* p) { return (uint32_t)__cvta_generic_to_shared(p); }
__device__ __forceinline__ void mbar_init(uint32_t bar, uint32_t cnt) { asm volatile("mbarrier.init.shared::cta.b64 [%0], %1;" :: "r"(bar), "r"(cnt) : "memory"); }
__device__ __forceinline__ void mbar_expect_tx(uint32_t bar, uint32_t bytes) { asm volatile("mbarrier.arrive.expect_tx.shared::cta.b64 _, [%0], %1;" :: "r"(bar), "r"(bytes) : "memory"); }
__device__ __forceinline__ void mbar_expect_only(uint32_t bar, uint32_t bytes) { asm volatile("mbarrier.expect_tx.relaxed.cta.shared::cta.b64 [%0], %1;" :: "r"(bar), "r"(bytes) : "memory"); }
__device__ __forceinline__ void mbar_arrive(uint32_t bar) { asm volatile("mbarrier.arrive.shared::cta.b64 _, [%0];" :: "r"(bar) : "memory"); }
__device__ __forceinline__ void mbar_wait(uint32_t bar, uint32_t parity) {
    asm volatile("{\n.reg .pred P1, P2;\n.reg .u32 n;\nmov.u32 n, 0;\n"
                 "WAIT_LOOP:\n"
                 "mbarrier.try_wait.parity.shared::cta.b64 P1, [%0], %1;\n"
                 "@P1 bra WAIT_DONE;\n"
                 "add.u32 n, n, 1;\n"
                 "setp.lt.u32 P2, n, 0x400000;\n"
                 "@P2 bra WAIT_LOOP;\n"
                 "WAIT_DONE:\n}" :: "r"(bar), "r"(parity) : "memory");
}
__device__ __forceinline__ void tma_2d(uint32_t dst, const void* map, uint32_t bar, int c0, int c1) {
    asm volatile("cp.async.bulk.tensor.2d.shared::cluster.global.mbarrier::complete_tx::bytes [%0], [%1, {%3, %4}], [%2];"
        :: "r"(dst), "l"(map), "r"(bar), "r"(c0), "r"(c1) : "memory");
}
__device__ __forceinline__ void tma_3d(uint32_t dst, const void* map, uint32_t bar, int c0, int c1, int c2) {
    asm volatile("cp.async.bulk.tensor.3d.shared::cluster.global.mbarrier::complete_tx::bytes [%0], [%1, {%3, %4, %5}], [%2];"
        :: "r"(dst), "l"(map), "r"(bar), "r"(c0), "r"(c1), "r"(c2) : "memory");
}
__device__ __forceinline__ void tma_4d(uint32_t dst, const void* map, uint32_t bar, int c0, int c1, int c2, int c3) {
    asm volatile("cp.async.bulk.tensor.4d.shared::cluster.global.mbarrier::complete_tx::bytes [%0], [%1, {%3, %4, %5, %6}], [%2];"
        :: "r"(dst), "l"(map), "r"(bar), "r"(c0), "r"(c1), "r"(c2), "r"(c3) : "memory");
}
__device__ __forceinline__ void bulk_g2s(uint32_t dst, const void* src, uint32_t bytes, uint32_t bar) {
    asm volatile("cp.async.bulk.shared::cluster.global.mbarrier::complete_tx::bytes [%0], [%1], %2, [%3];"
        :: "r"(dst), "l"(src), "r"(bytes), "r"(bar) : "memory");
}
__device__ __forceinline__ void prefetch_l2(const void* src, uint32_t bytes) {
    asm volatile("cp.async.bulk.prefetch.L2.global [%0], %1;" :: "l"(src), "r"(bytes) : "memory");
}
__device__ __forceinline__ bool elect_one() {
    uint32_t p;
    asm volatile("{\n.reg .pred P;\nelect.sync _|P, 0xffffffff;\nselp.u32 %0, 1, 0, P;\n}" : "=r"(p));
    return p != 0;
}
__device__ __forceinline__ void wgmma_fence() { asm volatile("wgmma.fence.sync.aligned;" ::: "memory"); }
__device__ __forceinline__ void wgmma_commit() { asm volatile("wgmma.commit_group.sync.aligned;" ::: "memory"); }
template <int N> __device__ __forceinline__ void wgmma_wait() { asm volatile("wgmma.wait_group.sync.aligned %0;" :: "n"(N) : "memory"); }
__device__ __forceinline__ void fence_async_smem() { asm volatile("fence.proxy.async.shared::cta;" ::: "memory"); }
__device__ __forceinline__ uint64_t desc_a(uint32_t addr) {
    return (uint64_t)((addr & 0x3FFFF) >> 4) | ((uint64_t)1 << 16) | ((uint64_t)(1024 >> 4) << 32) | ((uint64_t)1 << 62);
}
__device__ __forceinline__ uint64_t desc_b(uint32_t addr) {
    return (uint64_t)((addr & 0x3FFFF) >> 4) | ((uint64_t)(4096 >> 4) << 16) | ((uint64_t)(1024 >> 4) << 32) | ((uint64_t)1 << 62);
}
__device__ __forceinline__ uint32_t pack_bf16(float lo, float hi) {
    uint32_t r; asm("cvt.rn.bf16x2.f32 %0, %1, %2;" : "=r"(r) : "f"(hi), "f"(lo)); return r;
}
__device__ __forceinline__ uint32_t pack_bf16_relu(float lo, float hi) {
    uint32_t r; asm("cvt.rn.relu.bf16x2.f32 %0, %1, %2;" : "=r"(r) : "f"(hi), "f"(lo)); return r;
}
__device__ __forceinline__ uint32_t movmatrix(uint32_t a) {
    uint32_t d; asm volatile("movmatrix.sync.aligned.m8n8.trans.b16 %0, %1;" : "=r"(d) : "r"(a)); return d;
}
__device__ __forceinline__ void stmatrix_x4(uint32_t addr, uint32_t r0, uint32_t r1, uint32_t r2, uint32_t r3) {
    asm volatile("stmatrix.sync.aligned.m8n8.x4.shared.b16 [%0], {%1, %2, %3, %4};" :: "r"(addr), "r"(r0), "r"(r1), "r"(r2), "r"(r3) : "memory");
}
__device__ __forceinline__ uint4 lds128(uint32_t addr) {
    uint4 v; asm volatile("ld.shared.v4.b32 {%0, %1, %2, %3}, [%4];" : "=r"(v.x), "=r"(v.y), "=r"(v.z), "=r"(v.w) : "r"(addr) : "memory"); return v;
}
__device__ __forceinline__ void mma16816(float (&c)[4], uint32_t a0, uint32_t a1, uint32_t a2, uint32_t a3, uint32_t b0, uint32_t b1) {
    asm volatile("mma.sync.aligned.m16n8k16.row.col.f32.bf16.bf16.f32 {%0,%1,%2,%3}, {%4,%5,%6,%7}, {%8,%9}, {%0,%1,%2,%3};"
        : "+f"(c[0]), "+f"(c[1]), "+f"(c[2]), "+f"(c[3]) : "r"(a0), "r"(a1), "r"(a2), "r"(a3), "r"(b0), "r"(b1));
}
__device__ __forceinline__ void mma16816_c(float (&c)[4], uint32_t a0, uint32_t a1, uint32_t a2, uint32_t a3, uint32_t b0, uint32_t b1, float ci) {
    asm volatile("mma.sync.aligned.m16n8k16.row.col.f32.bf16.bf16.f32 {%0,%1,%2,%3}, {%4,%5,%6,%7}, {%8,%9}, {%10,%10,%10,%10};"
        : "=f"(c[0]), "=f"(c[1]), "=f"(c[2]), "=f"(c[3]) : "r"(a0), "r"(a1), "r"(a2), "r"(a3), "r"(b0), "r"(b1), "f"(ci));
}
__device__ __forceinline__ int opaque(int v) { asm volatile("" : "+r"(v)); return v; }
__device__ __forceinline__ float ex2(float x) { float y; asm("ex2.approx.ftz.f32 %0, %1;" : "=f"(y) : "f"(x)); return y; }
__device__ __forceinline__ unsigned ld_acquire(const unsigned* p) {
    unsigned v; asm volatile("ld.acquire.gpu.global.u32 %0, [%1];" : "=r"(v) : "l"(p) : "memory"); return v;
}
__device__ __forceinline__ void red_release(unsigned* p, unsigned v) {
    asm volatile("red.release.gpu.global.add.u32 [%0], %1;" :: "l"(p), "r"(v) : "memory");
}
__device__ __forceinline__ void wait_counter(const unsigned* p, unsigned target) {
    uint32_t n = 0;
    while ((int)(ld_acquire(p) - target) < 0) { if (++n > (1u << 20)) break; }
}
__device__ __forceinline__ uint4 ldg_weak(const uint4* p) {
    uint4 v; asm volatile("ld.global.L1::no_allocate.v4.b32 {%0, %1, %2, %3}, [%4];" : "=r"(v.x), "=r"(v.y), "=r"(v.z), "=r"(v.w) : "l"(p) : "memory"); return v;
}
__device__ __forceinline__ float bf_lo(uint32_t v) { return __uint_as_float(v << 16); }
__device__ __forceinline__ float bf_hi(uint32_t v) { return __uint_as_float(v & 0xFFFF0000u); }

__device__ __forceinline__ void wgmma_ss_n64(float (&d)[32], uint64_t da, uint64_t db, int scale_d) {
    asm volatile("{\n.reg .pred p;\nsetp.ne.b32 p, %34, 0;\n"
        "wgmma.mma_async.sync.aligned.m64n64k16.f32.bf16.bf16 {%0, %1, %2, %3, %4, %5, %6, %7, %8, %9, %10, %11, %12, %13, %14, %15, %16, %17, %18, %19, %20, %21, %22, %23, %24, %25, %26, %27, %28, %29, %30, %31}, %32, %33, p, 1, 1, 0, 1;\n}\n"
        : "+f"(d[0]), "+f"(d[1]), "+f"(d[2]), "+f"(d[3]), "+f"(d[4]), "+f"(d[5]), "+f"(d[6]), "+f"(d[7]), "+f"(d[8]), "+f"(d[9]), "+f"(d[10]), "+f"(d[11]), "+f"(d[12]), "+f"(d[13]), "+f"(d[14]), "+f"(d[15]), "+f"(d[16]), "+f"(d[17]), "+f"(d[18]), "+f"(d[19]), "+f"(d[20]), "+f"(d[21]), "+f"(d[22]), "+f"(d[23]), "+f"(d[24]), "+f"(d[25]), "+f"(d[26]), "+f"(d[27]), "+f"(d[28]), "+f"(d[29]), "+f"(d[30]), "+f"(d[31])
        : "l"(da), "l"(db), "r"(scale_d));
}
__device__ __forceinline__ void wgmma_ss_n128(float (&d)[64], uint64_t da, uint64_t db, int scale_d) {
    asm volatile("{\n.reg .pred p;\nsetp.ne.b32 p, %66, 0;\n"
        "wgmma.mma_async.sync.aligned.m64n128k16.f32.bf16.bf16 {%0, %1, %2, %3, %4, %5, %6, %7, %8, %9, %10, %11, %12, %13, %14, %15, %16, %17, %18, %19, %20, %21, %22, %23, %24, %25, %26, %27, %28, %29, %30, %31, %32, %33, %34, %35, %36, %37, %38, %39, %40, %41, %42, %43, %44, %45, %46, %47, %48, %49, %50, %51, %52, %53, %54, %55, %56, %57, %58, %59, %60, %61, %62, %63}, %64, %65, p, 1, 1, 0, 1;\n}\n"
        : "+f"(d[0]), "+f"(d[1]), "+f"(d[2]), "+f"(d[3]), "+f"(d[4]), "+f"(d[5]), "+f"(d[6]), "+f"(d[7]), "+f"(d[8]), "+f"(d[9]), "+f"(d[10]), "+f"(d[11]), "+f"(d[12]), "+f"(d[13]), "+f"(d[14]), "+f"(d[15]), "+f"(d[16]), "+f"(d[17]), "+f"(d[18]), "+f"(d[19]), "+f"(d[20]), "+f"(d[21]), "+f"(d[22]), "+f"(d[23]), "+f"(d[24]), "+f"(d[25]), "+f"(d[26]), "+f"(d[27]), "+f"(d[28]), "+f"(d[29]), "+f"(d[30]), "+f"(d[31]), "+f"(d[32]), "+f"(d[33]), "+f"(d[34]), "+f"(d[35]), "+f"(d[36]), "+f"(d[37]), "+f"(d[38]), "+f"(d[39]), "+f"(d[40]), "+f"(d[41]), "+f"(d[42]), "+f"(d[43]), "+f"(d[44]), "+f"(d[45]), "+f"(d[46]), "+f"(d[47]), "+f"(d[48]), "+f"(d[49]), "+f"(d[50]), "+f"(d[51]), "+f"(d[52]), "+f"(d[53]), "+f"(d[54]), "+f"(d[55]), "+f"(d[56]), "+f"(d[57]), "+f"(d[58]), "+f"(d[59]), "+f"(d[60]), "+f"(d[61]), "+f"(d[62]), "+f"(d[63])
        : "l"(da), "l"(db), "r"(scale_d));
}
__device__ __forceinline__ void wgmma_ss_n200(float (&d)[100], uint64_t da, uint64_t db, int scale_d) {
    asm volatile("{\n.reg .pred p;\nsetp.ne.b32 p, %102, 0;\n"
        "wgmma.mma_async.sync.aligned.m64n200k16.f32.bf16.bf16 {%0, %1, %2, %3, %4, %5, %6, %7, %8, %9, %10, %11, %12, %13, %14, %15, %16, %17, %18, %19, %20, %21, %22, %23, %24, %25, %26, %27, %28, %29, %30, %31, %32, %33, %34, %35, %36, %37, %38, %39, %40, %41, %42, %43, %44, %45, %46, %47, %48, %49, %50, %51, %52, %53, %54, %55, %56, %57, %58, %59, %60, %61, %62, %63, %64, %65, %66, %67, %68, %69, %70, %71, %72, %73, %74, %75, %76, %77, %78, %79, %80, %81, %82, %83, %84, %85, %86, %87, %88, %89, %90, %91, %92, %93, %94, %95, %96, %97, %98, %99}, %100, %101, p, 1, 1, 0, 1;\n}\n"
        : "+f"(d[0]), "+f"(d[1]), "+f"(d[2]), "+f"(d[3]), "+f"(d[4]), "+f"(d[5]), "+f"(d[6]), "+f"(d[7]), "+f"(d[8]), "+f"(d[9]), "+f"(d[10]), "+f"(d[11]), "+f"(d[12]), "+f"(d[13]), "+f"(d[14]), "+f"(d[15]), "+f"(d[16]), "+f"(d[17]), "+f"(d[18]), "+f"(d[19]), "+f"(d[20]), "+f"(d[21]), "+f"(d[22]), "+f"(d[23]), "+f"(d[24]), "+f"(d[25]), "+f"(d[26]), "+f"(d[27]), "+f"(d[28]), "+f"(d[29]), "+f"(d[30]), "+f"(d[31]), "+f"(d[32]), "+f"(d[33]), "+f"(d[34]), "+f"(d[35]), "+f"(d[36]), "+f"(d[37]), "+f"(d[38]), "+f"(d[39]), "+f"(d[40]), "+f"(d[41]), "+f"(d[42]), "+f"(d[43]), "+f"(d[44]), "+f"(d[45]), "+f"(d[46]), "+f"(d[47]), "+f"(d[48]), "+f"(d[49]), "+f"(d[50]), "+f"(d[51]), "+f"(d[52]), "+f"(d[53]), "+f"(d[54]), "+f"(d[55]), "+f"(d[56]), "+f"(d[57]), "+f"(d[58]), "+f"(d[59]), "+f"(d[60]), "+f"(d[61]), "+f"(d[62]), "+f"(d[63]), "+f"(d[64]), "+f"(d[65]), "+f"(d[66]), "+f"(d[67]), "+f"(d[68]), "+f"(d[69]), "+f"(d[70]), "+f"(d[71]), "+f"(d[72]), "+f"(d[73]), "+f"(d[74]), "+f"(d[75]), "+f"(d[76]), "+f"(d[77]), "+f"(d[78]), "+f"(d[79]), "+f"(d[80]), "+f"(d[81]), "+f"(d[82]), "+f"(d[83]), "+f"(d[84]), "+f"(d[85]), "+f"(d[86]), "+f"(d[87]), "+f"(d[88]), "+f"(d[89]), "+f"(d[90]), "+f"(d[91]), "+f"(d[92]), "+f"(d[93]), "+f"(d[94]), "+f"(d[95]), "+f"(d[96]), "+f"(d[97]), "+f"(d[98]), "+f"(d[99])
        : "l"(da), "l"(db), "r"(scale_d));
}
__device__ __forceinline__ void wgmma_ss_n224(float (&d)[112], uint64_t da, uint64_t db, int scale_d) {
    asm volatile("{\n.reg .pred p;\nsetp.ne.b32 p, %114, 0;\n"
        "wgmma.mma_async.sync.aligned.m64n224k16.f32.bf16.bf16 {%0, %1, %2, %3, %4, %5, %6, %7, %8, %9, %10, %11, %12, %13, %14, %15, %16, %17, %18, %19, %20, %21, %22, %23, %24, %25, %26, %27, %28, %29, %30, %31, %32, %33, %34, %35, %36, %37, %38, %39, %40, %41, %42, %43, %44, %45, %46, %47, %48, %49, %50, %51, %52, %53, %54, %55, %56, %57, %58, %59, %60, %61, %62, %63, %64, %65, %66, %67, %68, %69, %70, %71, %72, %73, %74, %75, %76, %77, %78, %79, %80, %81, %82, %83, %84, %85, %86, %87, %88, %89, %90, %91, %92, %93, %94, %95, %96, %97, %98, %99, %100, %101, %102, %103, %104, %105, %106, %107, %108, %109, %110, %111}, %112, %113, p, 1, 1, 0, 1;\n}\n"
        : "+f"(d[0]), "+f"(d[1]), "+f"(d[2]), "+f"(d[3]), "+f"(d[4]), "+f"(d[5]), "+f"(d[6]), "+f"(d[7]), "+f"(d[8]), "+f"(d[9]), "+f"(d[10]), "+f"(d[11]), "+f"(d[12]), "+f"(d[13]), "+f"(d[14]), "+f"(d[15]), "+f"(d[16]), "+f"(d[17]), "+f"(d[18]), "+f"(d[19]), "+f"(d[20]), "+f"(d[21]), "+f"(d[22]), "+f"(d[23]), "+f"(d[24]), "+f"(d[25]), "+f"(d[26]), "+f"(d[27]), "+f"(d[28]), "+f"(d[29]), "+f"(d[30]), "+f"(d[31]), "+f"(d[32]), "+f"(d[33]), "+f"(d[34]), "+f"(d[35]), "+f"(d[36]), "+f"(d[37]), "+f"(d[38]), "+f"(d[39]), "+f"(d[40]), "+f"(d[41]), "+f"(d[42]), "+f"(d[43]), "+f"(d[44]), "+f"(d[45]), "+f"(d[46]), "+f"(d[47]), "+f"(d[48]), "+f"(d[49]), "+f"(d[50]), "+f"(d[51]), "+f"(d[52]), "+f"(d[53]), "+f"(d[54]), "+f"(d[55]), "+f"(d[56]), "+f"(d[57]), "+f"(d[58]), "+f"(d[59]), "+f"(d[60]), "+f"(d[61]), "+f"(d[62]), "+f"(d[63]), "+f"(d[64]), "+f"(d[65]), "+f"(d[66]), "+f"(d[67]), "+f"(d[68]), "+f"(d[69]), "+f"(d[70]), "+f"(d[71]), "+f"(d[72]), "+f"(d[73]), "+f"(d[74]), "+f"(d[75]), "+f"(d[76]), "+f"(d[77]), "+f"(d[78]), "+f"(d[79]), "+f"(d[80]), "+f"(d[81]), "+f"(d[82]), "+f"(d[83]), "+f"(d[84]), "+f"(d[85]), "+f"(d[86]), "+f"(d[87]), "+f"(d[88]), "+f"(d[89]), "+f"(d[90]), "+f"(d[91]), "+f"(d[92]), "+f"(d[93]), "+f"(d[94]), "+f"(d[95]), "+f"(d[96]), "+f"(d[97]), "+f"(d[98]), "+f"(d[99]), "+f"(d[100]), "+f"(d[101]), "+f"(d[102]), "+f"(d[103]), "+f"(d[104]), "+f"(d[105]), "+f"(d[106]), "+f"(d[107]), "+f"(d[108]), "+f"(d[109]), "+f"(d[110]), "+f"(d[111])
        : "l"(da), "l"(db), "r"(scale_d));
}
template <int N> __device__ __forceinline__ void fence_acc(float (&d)[N]) {
#pragma unroll
    for (int i = 0; i < N; i++) asm volatile("" : "+f"(d[i]) :: "memory");
}

__device__ __forceinline__ void bulk_s2g(void* dst, uint32_t src, uint32_t bytes) {
    asm volatile("cp.async.bulk.global.shared::cta.bulk_group [%0], [%1], %2;" :: "l"(dst), "r"(src), "r"(bytes) : "memory");
}
__device__ __forceinline__ void sts128(uint32_t addr, uint4 v) {
    asm volatile("st.shared.v4.b32 [%0], {%1, %2, %3, %4};" :: "r"(addr), "r"(v.x), "r"(v.y), "r"(v.z), "r"(v.w) : "memory");
}
__device__ __forceinline__ void sum_partials(uint32_t sb, int ti, int tj, int lane) {
    for (;;) {
        uint32_t item = 0;
        if (lane == 0) asm volatile("atom.shared.add.u32 %0, [%1], 1;" : "=r"(item) : "r"(sb + ITEM_OFF) : "memory");
        item = __shfl_sync(0xffffffffu, item, 0);
        if (item >= 8) break;
        const uint4* p = g_part + (size_t)((ti * 8 + tj) * 8) * 1024 + item * 128 + lane;
        uint4 v[4][4];
#pragma unroll
        for (int s = 0; s < 4; s++)
#pragma unroll
            for (int n = 0; n < 4; n++) v[n][s] = ldg_weak(p + s * 1024 + n * 32);
#pragma unroll
        for (int n = 0; n < 4; n++) {
            float a[8];
#pragma unroll
            for (int e = 0; e < 8; e++) a[e] = 0.f;
#pragma unroll
            for (int s = 0; s < 4; s++) {
                a[0] += bf_lo(v[n][s].x); a[1] += bf_hi(v[n][s].x); a[2] += bf_lo(v[n][s].y); a[3] += bf_hi(v[n][s].y);
                a[4] += bf_lo(v[n][s].z); a[5] += bf_hi(v[n][s].z); a[6] += bf_lo(v[n][s].w); a[7] += bf_hi(v[n][s].w);
            }
            const uint32_t d = sb + STG_OFF + (item * 8 + n * 2) * 512 + lane * 16;
            sts128(d, make_uint4(__float_as_uint(a[0]), __float_as_uint(a[1]), __float_as_uint(a[2]), __float_as_uint(a[3])));
            sts128(d + 512, make_uint4(__float_as_uint(a[4]), __float_as_uint(a[5]), __float_as_uint(a[6]), __float_as_uint(a[7])));
        }
    }
    __syncwarp();
    if (lane == 0) mbar_arrive(sb + B_HSUM);
}

#define PWAIT() mbar_wait(sb + B_EMPTY + 8 * r.slot, r.phase)
#define CWAIT() do { if (!dry) mbar_wait(sb + B_FULL + 8 * r.slot, r.phase); } while (0)
template <bool B> struct BoolTag { static constexpr bool value = B; };
struct Ring {
    int slot; uint32_t phase;
    __device__ __forceinline__ void next() { if (++slot == RING) { slot = 0; phase ^= 1; } }
};

__global__ void __launch_bounds__(384, 1)
fused_kernel(const __grid_constant__ CUtensorMap map_x, const __grid_constant__ CUtensorMap map_qkv,
             const __grid_constant__ CUtensorMap map_w1, const __grid_constant__ CUtensorMap map_w2,
             const __grid_constant__ CUtensorMap map_wo, const __grid_constant__ CUtensorMap map_w1a,
             const __grid_constant__ CUtensorMap map_o,
             const __nv_bfloat16* __restrict__ gate_w, __nv_bfloat16* __restrict__ out,
             const uint8_t* __restrict__ w1p, const uint8_t* __restrict__ w2p, const uint8_t* __restrict__ wop)
{
    extern __shared__ __align__(1024) uint8_t smem_raw[];
    const uint32_t sb = smem_u32(smem_raw);
    const int tid = threadIdx.x, warp = tid >> 5, lane = tid & 31;
    const bool dry = blockIdx.x >= 128;
    const int ti = dry ? (int)(blockIdx.x & 1) * 2 : blockIdx.x >> 3, tj = blockIdx.x & 7;
    if (dry && warp >= 8) {
        asm volatile("setmaxnreg.dec.sync.aligned.u32 88;");
        return;
    }

    if (tid == 0 && !dry) { TSG(31); TSX(0); }
    if (tid == 320) {
        asm volatile("prefetch.tensormap [%0];" :: "l"(&map_x) : "memory");
        asm volatile("prefetch.tensormap [%0];" :: "l"(&map_qkv) : "memory");
        asm volatile("prefetch.tensormap [%0];" :: "l"(&map_w1) : "memory");
        asm volatile("prefetch.tensormap [%0];" :: "l"(&map_w1a) : "memory");
        asm volatile("prefetch.tensormap [%0];" :: "l"(&map_w2) : "memory");
        asm volatile("prefetch.tensormap [%0];" :: "l"(&map_wo) : "memory");
        asm volatile("prefetch.tensormap [%0];" :: "l"(&map_o) : "memory");
    }
    uint32_t gwv[N_QKV / 2];
    if (warp == 8) {
        const unsigned short* gws = reinterpret_cast<const unsigned short*>(gate_w);
#pragma unroll
        for (int n = 0; n < N_QKV / 2; n++) gwv[n] = (uint32_t)__ldg(gws + 64 * n + lane) | ((uint32_t)__ldg(gws + 64 * n + 32 + lane) << 16);
    }
    if (tid == 256) {
        for (int s = 0; s < RING; s++) { mbar_init(sb + B_FULL + 8 * s, 1); mbar_init(sb + B_EMPTY + 8 * s, 8); }
        for (int s = 0; s < 8; s++) mbar_init(sb + B_XFULL + 8 * s, 1);
        mbar_init(sb + B_HDEAD, 8); mbar_init(sb + B_EREADY, 1); mbar_init(sb + B_KVDONE, 8); mbar_init(sb + B_KVREADY, 1);
        mbar_init(sb + B_ODONE, 8); mbar_init(sb + B_WOFULL, 1); mbar_init(sb + B_HSUM, 3);
        mbar_init(sb + B_PREADY, 1); mbar_init(sb + B_SF, 1); mbar_init(sb + B_SF + 8, 1);
        for (int s = 0; s < 4; s++) mbar_init(sb + B_SQ + 8 * s, 8);
        asm volatile("st.shared.u32 [%0], %1;" :: "r"(sb + ITEM_OFF), "r"(0) : "memory");
        asm volatile("fence.mbarrier_init.release.cluster;" ::: "memory");
        fence_async_smem();
        mbar_expect_tx(sb + B_XFULL, 16384);
        tma_2d(sb + X_OFF, &map_x, sb + B_XFULL, 0, ti * 128);
        mbar_expect_only(sb + B_FULL, 12288);
        tma_4d(sb + RING_OFF, &map_qkv, sb + B_FULL, 0, 0, tj, 0);
    }
    if (!dry) __syncthreads();

    if (warp >= 8) {
        asm volatile("setmaxnreg.dec.sync.aligned.u32 88;");
        if (warp == 8) {
            Ring r{0, 1};
            const bool leader = elect_one();
#pragma unroll
            for (int n = 0; n < N_QKV; n++) {
                const uint32_t full = sb + B_FULL + 8 * r.slot, dst = sb + RING_OFF + r.slot * SLOT;
                if (n > 0) {
                    if (!(n & 1) && leader) {
                        mbar_expect_tx(sb + B_XFULL + 8 * (n >> 1), 16384);
                        tma_2d(sb + X_OFF + (n >> 1) * 16384, &map_x, sb + B_XFULL + 8 * (n >> 1), (n >> 1) * 64, ti * 128);
                    }
                    if (n >= RING) PWAIT();
                    if (leader) {
                        mbar_expect_only(full, 12288);
                        tma_4d(dst, &map_qkv, full, 0, 32 * n, tj, 0);
                    }
                }
                const uint32_t gv = (n & 1) ? (gwv[n >> 1] >> 16) : (gwv[n >> 1] & 0xFFFFu);
                asm volatile("st.shared.v4.b32 [%0], {%1, %2, %2, %2};" :: "r"(dst + 12288 + lane * 128 + ((lane & 7) << 4)), "r"(gv), "r"(0) : "memory");
                fence_async_smem();
                __syncwarp();
                if (leader) mbar_arrive(full);
                r.next();
            }
#pragma unroll 1
            for (int n = 0; n < N_FFN1; n++) {
                const uint32_t full = sb + B_FULL + 8 * r.slot, dst = sb + RING_OFF + r.slot * SLOT;
                PWAIT();
                if (leader) {
                    mbar_expect_tx(full, 16384);
                    tma_4d(dst, &map_w1a, full, 0, 32 * n, 0, tj);
                    tma_2d(dst + 3 * 4096, &map_w1, full, 224 * tj + 192, 32 * n);
                }
                r.next();
            }
            {
                int q = 0, rr = 0;
#pragma unroll 1
                for (int n = 0; n < N_FFN2; n++) {
                    const uint32_t full = sb + B_FULL + 8 * r.slot, dst = sb + RING_OFF + r.slot * SLOT;
                    PWAIT();
                    if (leader) mbar_expect_tx(full, 16384);
#pragma unroll
                    for (int h = 0; h < 2; h++) {
                        if (leader) tma_3d(dst + h * 8192, &map_w2, full, 0, 224 * tj + 32 * rr, 2 * q);
                        if (++rr == 7) { rr = 0; q++; }
                    }
                    r.next();
                }
            }
            mbar_wait(sb + B_KVREADY, 0);
            asm volatile("fence.proxy.async.global;" ::: "memory");
            {
                const int bbase = 8 * ti - 16, b0 = bbase < 0 ? 0 : bbase;
                const uint32_t bytes = (uint32_t)(8 * ti + 8 - b0) * 512;
#pragma unroll 1
                for (int m = 0; m < N_KV; m++) {
                    const uint32_t full = sb + B_FULL + 8 * r.slot, dst = sb + RING_OFF + r.slot * SLOT;
                    if (m == RING) {
                        mbar_wait(sb + B_HDEAD, 0);
                        if (leader) {
                            mbar_expect_tx(sb + B_WOFULL, 65536);
#pragma unroll
                            for (int e = 0; e < 2; e++) tma_2d(sb + X_OFF + e * 32768, &map_wo, sb + B_WOFULL, 64 * tj, 256 * e);
                        }
                    }
                    PWAIT();
                    if (leader) {
                        const uint4* src = ((m & 1) ? g_vf : g_kf) + ((tj * 4 + (m >> 1)) * 128 + b0) * 32;
                        mbar_expect_tx(full, bytes);
                        bulk_g2s(dst + (b0 - bbase) * 512, src, bytes, full);
                    }
                    r.next();
                }
            }
            {
                mbar_wait(sb + B_EREADY, 0);
                unsigned epoch; asm volatile("ld.shared.u32 %0, [%1];" : "=r"(epoch) : "r"(sb + EPOCH_OFF) : "memory");
                uint32_t pending = 0xFFu & ~(1u << tj);
#pragma unroll 1
                for (int m = 0; m < N_O; m++) {
                    const uint32_t full = sb + B_FULL + 8 * r.slot, dst = sb + RING_OFF + r.slot * SLOT;
                    PWAIT();
                    uint32_t ready = 0;
                    for (int it = 0; it < (1 << 20) && !ready; it++) {
                        bool ok = false;
                        if (lane < 8 && ((pending >> lane) & 1)) ok = (int)(ld_acquire(&g_ocnt[(ti * 8 + lane) * 32]) - 8 * (epoch + 1)) >= 0;
                        ready = __ballot_sync(0xffffffffu, ok);
                    }
                    const int js = ready ? __ffs(ready) - 1 : __ffs(pending) - 1;
                    pending &= ~(1u << js);
                    asm volatile("fence.proxy.async.global;" ::: "memory");
                    if (leader) {
                        asm volatile("st.shared.u32 [%0], %1;" :: "r"(sb + OSRC_OFF + 4 * m), "r"(js) : "memory");
                        mbar_expect_tx(full, 16384);
                        tma_2d(dst, &map_o, full, 64 * js, ti * 128);
                    }
                    r.next();
                }
            }
        } else if (warp == 9) {
            unsigned epoch = 0;
            if (lane == 0) {
                epoch = atomicAdd(&g_ticket, 1u) >> 7;
                asm volatile("st.shared.u32 [%0], %1;" :: "r"(sb + EPOCH_OFF), "r"(epoch) : "memory");
                mbar_arrive(sb + B_EREADY);
                mbar_wait(sb + B_XFULL + 8 * PF1_AT, 0);
                prefetch_l2(w1p + (size_t)blockIdx.x * 14336, 14336);
                mbar_wait(sb + B_XFULL + 8 * PF2_AT, 0);
                prefetch_l2(w2p + (size_t)blockIdx.x * 14336, 14336);
                prefetch_l2(wop + (size_t)blockIdx.x * 4096, 4096);
                mbar_wait(sb + B_KVDONE, 0);
                red_release(&g_kvcnt[blockIdx.x * 32], 1u);
            }
            epoch = __shfl_sync(0xffffffffu, epoch, 0);
            if (lane < 3 && ti - lane >= 0) wait_counter(&g_kvcnt[((ti - lane) * 8 + tj) * 32], epoch + 1);
            __syncwarp();
            if (lane == 0) mbar_arrive(sb + B_KVREADY);
            mbar_wait(sb + B_SQ + 24, 0);
            if (lane < 8) wait_counter(&g_pcnt[(ti * 8 + lane) * 32], epoch + 1);
            __syncwarp();
            if (lane == 0) { mbar_arrive(sb + B_PREADY); TSX(13); }
            sum_partials(sb, ti, tj, lane);
            if (lane == 0) TSX(14);
        } else {
            if (warp == 10) {
#pragma unroll 1
                for (int q = 0; q < 4; q++) {
                    mbar_wait(sb + B_SQ + 8 * q, 0);
                    if (lane < 16) {
                        uint4* d = g_part + (size_t)(((ti * 8 + 2 * q + (lane & 1)) * 8 + tj) * 8 + (lane >> 1)) * 128;
                        bulk_s2g(d, sb + STG_OFF + (q & 1) * 32768 + lane * 2048, 2048);
                        asm volatile("cp.async.bulk.commit_group;" ::: "memory");
                        asm volatile("cp.async.bulk.wait_group.read 0;" ::: "memory");
                    }
                    __syncwarp();
                    if (lane == 0) mbar_arrive(sb + B_SF + 8 * (q & 1));
                }
                asm volatile("cp.async.bulk.wait_group 0;" ::: "memory");
                asm volatile("fence.proxy.async.global;" ::: "memory");
                __syncwarp();
                if (lane == 0) { red_release(&g_pcnt[blockIdx.x * 32], 1u); TSX(12); }
            }
            mbar_wait(sb + B_PREADY, 0);
            sum_partials(sb, ti, tj, lane);
        }
    } else {
        asm volatile("setmaxnreg.inc.sync.aligned.u32 208;");
        const int wg = warp >> 2, g = lane >> 2, c = lane & 3;
        const uint32_t xa = sb + X_OFF + wg * 8192;
        Ring r{0, 0};
        const bool lane0 = lane == 0 && !dry;
        uint32_t qf[4][4];
        float g0, g1;
        TS(9);
        {
            float acc[100];
            int prev = 0;
            if (wg == 1) asm volatile("bar.sync 3, 256;" ::: "memory");
            for (int s = 0; s < (dry ? 4 : N_QKV); s++) {
                if (!(s & 1) && !dry) mbar_wait(sb + B_XFULL + 8 * (s >> 1), 0);
                CWAIT();
                if (s == 0) TS(1);
                if (s == 2) TS(28);
                if (s == 6) TS(29);
                if (s == 10) TS(20);
                const uint32_t bs = sb + RING_OFF + r.slot * SLOT, as = xa + (s >> 1) * 16384 + (s & 1) * 64;
                wgmma_fence();
                wgmma_ss_n200(acc, desc_a(as), desc_b(bs), s);
                wgmma_ss_n200(acc, desc_a(as + 32), desc_b(bs + 2048), 1);
                wgmma_commit();
                if (wg == 0 && s == LEAD1) asm volatile("bar.arrive 3, 256;" ::: "memory");
                if (s > 0) { wgmma_wait<1>(); if (lane0) mbar_arrive(sb + B_EMPTY + 8 * prev); }
                prev = r.slot; r.next();
            }
            wgmma_wait<0>();
            fence_acc(acc);
            if (lane0) mbar_arrive(sb + B_EMPTY + 8 * prev);
            TS(2);
            const int blk = ti * 8 + warp;
#pragma unroll
            for (int hh = 0; hh < 4; hh++) {
                const float* t0 = &acc[8 * hh]; const float* t1 = &acc[8 * hh + 4];
                qf[hh][0] = pack_bf16(t0[0], t0[1]); qf[hh][1] = pack_bf16(t0[2], t0[3]);
                qf[hh][2] = pack_bf16(t1[0], t1[1]); qf[hh][3] = pack_bf16(t1[2], t1[3]);
                const float* k0 = &acc[32 + 8 * hh]; const float* k1 = &acc[32 + 8 * hh + 4];
                uint4 kv;
                kv.x = pack_bf16(k0[0], k0[1]); kv.y = pack_bf16(k1[0], k1[1]);
                kv.z = pack_bf16(k0[2], k0[3]); kv.w = pack_bf16(k1[2], k1[3]);
                if (!dry) g_kf[((tj * 4 + hh) * 128 + blk) * 32 + lane] = kv;
                const float* v0 = &acc[64 + 8 * hh]; const float* v1 = &acc[64 + 8 * hh + 4];
                uint4 vv;
                vv.x = movmatrix(pack_bf16(v0[0], v0[1])); vv.y = movmatrix(pack_bf16(v0[2], v0[3]));
                vv.z = movmatrix(pack_bf16(v1[0], v1[1])); vv.w = movmatrix(pack_bf16(v1[2], v1[3]));
                if (!dry) g_vf[((tj * 4 + hh) * 128 + blk) * 32 + lane] = vv;
            }
            __syncwarp();
            if (lane0) mbar_arrive(sb + B_KVDONE);
            const float z0 = __shfl_sync(0xffffffffu, acc[96], lane & ~3), z1 = __shfl_sync(0xffffffffu, acc[98], lane & ~3);
            g0 = 1.f / (1.f + __expf(-z0)); g1 = 1.f / (1.f + __expf(-z1));
        }
        TS(3);
        const int wrow = (warp & 3) * 16;
        {
            float acc[112];
            int prev = 0;
            for (int s = 0; s < (dry ? 4 : N_FFN1); s++) {
                CWAIT();
                const uint32_t bs = sb + RING_OFF + r.slot * SLOT, as = xa + (s >> 1) * 16384 + (s & 1) * 64;
                wgmma_fence();
                wgmma_ss_n224(acc, desc_a(as), desc_b(bs), s);
                wgmma_ss_n224(acc, desc_a(as + 32), desc_b(bs + 2048), 1);
                wgmma_commit();
                if (s > 0) { wgmma_wait<1>(); if (lane0) mbar_arrive(sb + B_EMPTY + 8 * prev); }
                prev = r.slot; r.next();
            }
            wgmma_wait<0>();
            fence_acc(acc);
            if (lane0) mbar_arrive(sb + B_EMPTY + 8 * prev);
            TS(4);
            const float s0 = 1.f - g0, s1 = 1.f - g1;
            asm volatile("bar.sync %0, 128;" :: "r"(1 + wg) : "memory");
            const uint32_t strow = xa + (wrow + ((lane >> 3) & 1) * 8 + (lane & 7)) * 128;
#pragma unroll
            for (int p = 0; p < 14; p++) {
                const int nt = 2 * p + (lane >> 4);
                const float* a = &acc[8 * p];
                stmatrix_x4(strow + (p >> 2) * 16384 + (((nt & 7) ^ (lane & 7)) << 4),
                            pack_bf16_relu(a[0] * s0, a[1] * s0), pack_bf16_relu(a[2] * s1, a[3] * s1),
                            pack_bf16_relu(a[4] * s0, a[5] * s0), pack_bf16_relu(a[6] * s1, a[7] * s1));
            }
        }
        TS(5);
        {
            fence_async_smem();
            asm volatile("bar.sync 4, 256;" ::: "memory");
            float accA[64], accB[64];
            auto epilogue = [&](float (&acc)[64], int q) {
                fence_acc(acc);
                const uint32_t st = sb + STG_OFF + (q & 1) * 32768 + warp * 4096;
                if (q >= 2 && !dry) mbar_wait(sb + B_SF + 8 * (q & 1), 0);
#pragma unroll
                for (int t2 = 0; t2 < 8; t2++) {
                    uint4 v;
                    v.x = pack_bf16(acc[8 * t2 + 0], acc[8 * t2 + 1]); v.y = pack_bf16(acc[8 * t2 + 2], acc[8 * t2 + 3]);
                    v.z = pack_bf16(acc[8 * t2 + 4], acc[8 * t2 + 5]); v.w = pack_bf16(acc[8 * t2 + 6], acc[8 * t2 + 7]);
                    sts128(st + t2 * 512 + lane * 16, v);
                }
                fence_async_smem();
                __syncwarp();
                if (lane0) mbar_arrive(sb + B_SQ + 8 * q);
            };
            int rel = r.slot;
#pragma unroll
            for (int m = 0; m < N_FFN2; m++) {
                CWAIT();
                wgmma_fence();
#pragma unroll
                for (int h = 0; h < 2; h++) {
                    const int u = 2 * m + h, q = u / 7, rr = u % 7;
                    const uint32_t bs = sb + RING_OFF + r.slot * SLOT + h * 8192;
                    const uint32_t as = xa + (rr >> 1) * 16384 + (rr & 1) * 64;
                    if (!(q & 1)) {
                        wgmma_ss_n128(accA, desc_a(as), desc_b(bs), rr);
                        wgmma_ss_n128(accA, desc_a(as + 32), desc_b(bs + 2048), 1);
                    } else {
                        wgmma_ss_n128(accB, desc_a(as), desc_b(bs), rr);
                        wgmma_ss_n128(accB, desc_a(as + 32), desc_b(bs + 2048), 1);
                    }
                }
                wgmma_commit();
                r.next();
                wgmma_wait<1>();
                if (m > 0) {
                    if (lane0) mbar_arrive(sb + B_EMPTY + 8 * rel);
                    if (++rel == RING) rel = 0;
                }
                if (m == 4) { TS(25); epilogue(accA, 0); }
                if (m == 7) { TS(26); epilogue(accB, 1); }
                if (m == 11) { TS(27); epilogue(accA, 2); }
            }
            wgmma_wait<0>();
            if (lane0) { mbar_arrive(sb + B_EMPTY + 8 * rel); mbar_arrive(sb + B_HDEAD); }
            epilogue(accB, 3);
        }
        TS(6);
        {
            const float SC = 0.25f * 1.4426950408889634f;
            const int gb0 = 8 * ti - 16 + warp;
            int slotK = 0, slotV = 0;
            const uint32_t ostore = sb + OWN_OFF + (warp * 16 + ((lane >> 3) & 1) * 8 + (lane & 7)) * 128;
            uint32_t* odst = reinterpret_cast<uint32_t*>(g_o + (size_t)(ti * 128 + warp * 16 + g) * 512 + tj * 64 + ((lane & 1) ? 8 : 0) + (lane & 2) * 2);
#define NHEADS (dry ? 2 : 4)
#define ATT_KWAIT(kb) do { slotK = r.slot; CWAIT(); kb = sb + RING_OFF + slotK * SLOT + warp * 512 + lane * 16; r.next(); } while (0)
#define ATT_VWAIT(vb) do { slotV = r.slot; CWAIT(); vb = sb + RING_OFF + slotV * SLOT + warp * 512 + lane * 16; r.next(); TS(21 + hh); } while (0)
#define ATT_KREL() do { __syncwarp(); if (lane0) mbar_arrive(sb + B_EMPTY + 8 * slotK); } while (0)
#define ATT_VREL() do { __syncwarp(); if (lane0) mbar_arrive(sb + B_EMPTY + 8 * slotV); } while (0)
#define ATT_NEXTQ(h) do { \
                if ((h) == 1) { q0 = qf[1][0]; q1 = qf[1][1]; q2 = qf[1][2]; q3 = qf[1][3]; } \
                else if ((h) == 2) { q0 = qf[2][0]; q1 = qf[2][1]; q2 = qf[2][2]; q3 = qf[2][3]; } \
                else { q0 = qf[3][0]; q1 = qf[3][1]; q2 = qf[3][2]; q3 = qf[3][3]; } } while (0)
#define ATT_STORE(h, r0, r1, r2, r3) do { \
                if ((h) == 0 && !dry) mbar_wait(sb + B_SF + 8, 1);        \
                stmatrix_x4(ostore + (((2 * (h) + (lane >> 4)) ^ (lane & 7)) << 4), r0, r1, r2, r3); \
                const bool odd = lane & 1; \
                const uint32_t sl = __shfl_xor_sync(0xffffffffu, odd ? (r0) : (r2), 1), sh = __shfl_xor_sync(0xffffffffu, odd ? (r1) : (r3), 1); \
                if (!dry) *reinterpret_cast<uint2*>(odst + 8 * (h)) = odd ? make_uint2(sl, r2) : make_uint2(r0, sl); \
                if (!dry) *reinterpret_cast<uint2*>(odst + 8 * (h) + 8 * 256) = odd ? make_uint2(sh, r3) : make_uint2(r1, sh); \
                } while (0)
            auto attention = [&](auto masked_tag) {
            constexpr bool MASKED = decltype(masked_tag)::value;
            const float NEG = -INFINITY;
            const uint32_t ONES = 0x3F803F80u;
            float sa[8][2][4], sb2[8][2][4];
            float o[2][4], ls[4];
            float m0, m1;
            uint32_t q0 = qf[0][0], q1 = qf[0][1], q2 = qf[0][2], q3 = qf[0][3];
            auto qk = [&](float (&s)[8][2][4], int ps, int t, uint32_t kbase) {
                if (ps == 0 && t == 0) {
                    const uint4 kd = lds128(kbase + 16 * 512);
                    const uint4 kf = lds128(kbase);
                    float f[2][4];
                    const float ci = (!MASKED || opaque(gb0) >= 0) ? 0.f : NEG;
                    mma16816_c(s[0][0], q0, q1, q2, q3, kd.x, kd.y, 0.f);
                    mma16816_c(s[0][1], q0, q1, q2, q3, kd.z, kd.w, 0.f);
                    mma16816_c(f[0], q0, q1, q2, q3, kf.x, kf.y, ci);
                    mma16816_c(f[1], q0, q1, q2, q3, kf.z, kf.w, ci);
#pragma unroll
                    for (int u = 0; u < 2; u++)
#pragma unroll
                        for (int e = 0; e < 4; e++) {
                            const int row = g + 8 * (e >> 1), col = 8 * u + 2 * c + (e & 1);
                            s[0][u][e] = (col > row) ? f[u][e] : s[0][u][e];
                        }
                } else {
                    const uint4 kf = lds128(kbase + (8 * ps + t) * 512);
                    const float ci = (!MASKED || opaque(gb0) + 8 * ps + t >= 0) ? 0.f : NEG;
                    mma16816_c(s[t][0], q0, q1, q2, q3, kf.x, kf.y, ci);
                    mma16816_c(s[t][1], q0, q1, q2, q3, kf.z, kf.w, ci);
                }
            };
            auto rowmax = [&](float (&s)[8][2][4], float b0, float b1, float& n0, float& n1) {
                int i0 = __float_as_int(b0), i1 = __float_as_int(b1);
#pragma unroll
                for (int t = 0; t < 8; t++)
#pragma unroll
                    for (int u = 0; u < 2; u++) {
                        i0 = __vimax3_s32(i0, __float_as_int(s[t][u][0]), __float_as_int(s[t][u][1]));
                        i1 = __vimax3_s32(i1, __float_as_int(s[t][u][2]), __float_as_int(s[t][u][3]));
                    }
                i0 = max(i0, __shfl_xor_sync(0xffffffffu, i0, 1)); i1 = max(i1, __shfl_xor_sync(0xffffffffu, i1, 1));
                i0 = max(i0, __shfl_xor_sync(0xffffffffu, i0, 2)); i1 = max(i1, __shfl_xor_sync(0xffffffffu, i1, 2));
                n0 = __int_as_float(i0); n1 = __int_as_float(i1);
                if (__any_sync(0xffffffffu, (i0 | i1) < 0)) {
                    asm volatile("" ::: "memory");
                    n0 = b0; n1 = b1;
#pragma unroll
                    for (int t = 0; t < 8; t++)
#pragma unroll
                        for (int u = 0; u < 2; u++) {
                            n0 = fmaxf(n0, fmaxf(s[t][u][0], s[t][u][1]));
                            n1 = fmaxf(n1, fmaxf(s[t][u][2], s[t][u][3]));
                        }
                    n0 = fmaxf(n0, __shfl_xor_sync(0xffffffffu, n0, 1)); n1 = fmaxf(n1, __shfl_xor_sync(0xffffffffu, n1, 1));
                    n0 = fmaxf(n0, __shfl_xor_sync(0xffffffffu, n0, 2)); n1 = fmaxf(n1, __shfl_xor_sync(0xffffffffu, n1, 2));
                }
            };
            auto pv = [&](const float (&p)[2][4], uint32_t vaddr) {
                const uint4 vf = lds128(vaddr);
                const uint32_t a0 = pack_bf16(p[0][0], p[0][1]), a1 = pack_bf16(p[0][2], p[0][3]);
                const uint32_t a2 = pack_bf16(p[1][0], p[1][1]), a3 = pack_bf16(p[1][2], p[1][3]);
                mma16816(o[0], a0, a1, a2, a3, vf.x, vf.y);
                mma16816(o[1], a0, a1, a2, a3, vf.z, vf.w);
                mma16816(ls, a0, a1, a2, a3, ONES, ONES);
            };
            auto expv = [&](float (&s)[8][2][4], int ps, int t, float mc0, float mc1, uint32_t vbase) {
                float p[2][4];
#pragma unroll
                for (int u = 0; u < 2; u++) {
                    p[u][0] = ex2(fmaf(s[t][u][0], SC, -mc0)); p[u][1] = ex2(fmaf(s[t][u][1], SC, -mc0));
                    p[u][2] = ex2(fmaf(s[t][u][2], SC, -mc1)); p[u][3] = ex2(fmaf(s[t][u][3], SC, -mc1));
                }
                if (ps == 0 && t == 0) {
                    float pd[2][4], pf[2][4];
#pragma unroll
                    for (int u = 0; u < 2; u++)
#pragma unroll
                        for (int e = 0; e < 4; e++) {
                            const int row = g + 8 * (e >> 1), col = 8 * u + 2 * c + (e & 1);
                            pf[u][e] = (col > row) ? p[u][e] : 0.f;
                            pd[u][e] = (col > row) ? 0.f : p[u][e];
                        }
                    pv(pd, vbase + 16 * 512);
                    pv(pf, vbase);
                } else {
                    pv(p, vbase + (8 * ps + t) * 512);
                }
            };
            uint32_t kbase, vbase;
            ATT_KWAIT(kbase);
#pragma unroll
            for (int t = 0; t < 8; t++) qk(sa, 0, t, kbase);
            rowmax(sa, NEG, NEG, m0, m1);
#pragma unroll 1
            for (int hh = 0; hh < NHEADS; hh++) {
                ATT_VWAIT(vbase);
#pragma unroll
                for (int e = 0; e < 4; e++) { o[0][e] = 0.f; o[1][e] = 0.f; ls[e] = 0.f; }
                {
                    const float mc0 = m0 * SC, mc1 = m1 * SC;
#pragma unroll
                    for (int t = 0; t < 8; t++) { qk(sb2, 1, t, kbase); expv(sa, 0, t, mc0, mc1, vbase); }
                    ATT_KREL();
                    float n0, n1;
                    rowmax(sb2, m0, m1, n0, n1);
                    const float a0 = ex2((m0 - n0) * SC), a1 = ex2((m1 - n1) * SC);
                    ls[0] *= a0; ls[2] *= a1;
                    o[0][0] *= a0; o[0][1] *= a0; o[1][0] *= a0; o[1][1] *= a0;
                    o[0][2] *= a1; o[0][3] *= a1; o[1][2] *= a1; o[1][3] *= a1;
                    m0 = n0; m1 = n1;
                }
                {
                    const float mc0 = m0 * SC, mc1 = m1 * SC;
                    const bool more = hh + 1 < NHEADS;
                    if (more) {
                        ATT_KWAIT(kbase);
                        ATT_NEXTQ(hh + 1);
#pragma unroll
                        for (int t = 0; t < 8; t++) { qk(sa, 0, t, kbase); expv(sb2, 1, t, mc0, mc1, vbase); }
                        rowmax(sa, NEG, NEG, m0, m1);
                    } else {
#pragma unroll
                        for (int t = 0; t < 8; t++) expv(sb2, 1, t, mc0, mc1, vbase);
                    }
                    ATT_VREL();
                }
                const float f0 = __fdividef(g0, ls[0]), f1 = __fdividef(g1, ls[2]);
                ATT_STORE(hh, pack_bf16(o[0][0] * f0, o[0][1] * f0), pack_bf16(o[0][2] * f1, o[0][3] * f1),
                              pack_bf16(o[1][0] * f0, o[1][1] * f0), pack_bf16(o[1][2] * f1, o[1][3] * f1));
            }
            };
            if (ti >= 2) attention(BoolTag<false>{}); else attention(BoolTag<true>{});
            fence_async_smem();
            __syncwarp();
            if (lane0) { mbar_arrive(sb + B_ODONE); red_release(&g_ocnt[blockIdx.x * 32], 1u); }
        }
        TS(7);
        {
            float acc[32];
            uint4 pv[4][4];
            if (!dry) mbar_wait(sb + B_PREADY, 0);
            {
                const uint4* p = g_part + (size_t)((ti * 8 + tj) * 8 + 4) * 1024 + warp * 128 + lane;
#pragma unroll
                for (int s = 0; s < 4; s++)
#pragma unroll
                    for (int n = 0; n < 4; n++) pv[n][s] = dry ? make_uint4(0u, 0u, 0u, 0u) : ldg_weak(p + s * 1024 + n * 32);
            }
            if (!dry) mbar_wait(sb + B_WOFULL, 0);
            if (!dry) mbar_wait(sb + B_ODONE, 0);
            TS(15);
            wgmma_fence();
#pragma unroll
            for (int k = 0; k < 4; k++) wgmma_ss_n64(acc, desc_a(sb + OWN_OFF + wg * 8192 + 32 * k), desc_b(sb + X_OFF + tj * 8192 + 2048 * k), k);
            wgmma_commit();
            float base[32];
            if (!dry) mbar_wait(sb + B_HSUM, 0);
#pragma unroll
            for (int n = 0; n < 4; n++) {
                const uint4 u0 = lds128(sb + STG_OFF + (warp * 8 + 2 * n) * 512 + lane * 16), u1 = lds128(sb + STG_OFF + (warp * 8 + 2 * n + 1) * 512 + lane * 16);
                float* a = &base[8 * n];
                a[0] = __uint_as_float(u0.x); a[1] = __uint_as_float(u0.y); a[2] = __uint_as_float(u0.z); a[3] = __uint_as_float(u0.w);
                a[4] = __uint_as_float(u1.x); a[5] = __uint_as_float(u1.y); a[6] = __uint_as_float(u1.z); a[7] = __uint_as_float(u1.w);
#pragma unroll
                for (int s = 0; s < 4; s++) {
                    a[0] += bf_lo(pv[n][s].x); a[1] += bf_hi(pv[n][s].x); a[2] += bf_lo(pv[n][s].y); a[3] += bf_hi(pv[n][s].y);
                    a[4] += bf_lo(pv[n][s].z); a[5] += bf_hi(pv[n][s].z); a[6] += bf_lo(pv[n][s].w); a[7] += bf_hi(pv[n][s].w);
                }
            }
            fence_acc(base);
            TS(16);
#pragma unroll 1
            for (int m = 0; m < N_O; m++) {
                CWAIT();
                uint32_t js; asm volatile("ld.shared.u32 %0, [%1];" : "=r"(js) : "r"(sb + OSRC_OFF + 4 * m) : "memory");
                const uint32_t as = sb + RING_OFF + r.slot * SLOT + wg * 8192;
                const uint32_t bs = sb + X_OFF + (js & 7) * 8192;
                wgmma_fence();
#pragma unroll
                for (int k = 0; k < 4; k++) wgmma_ss_n64(acc, desc_a(as + 32 * k), desc_b(bs + 2048 * k), 1);
                wgmma_commit();
                if (m == 0) { wgmma_wait<0>(); if (lane0) mbar_arrive(sb + B_EMPTY + 8 * r.slot); }
                r.next();
            }
            wgmma_wait<0>();
            fence_acc(acc);
            TS(17);
#pragma unroll
            for (int k = 0; k < 32; k++) acc[k] += base[k];
            __nv_bfloat16* o = out + (size_t)(ti * 128 + warp * 16 + g) * 512 + tj * 64 + ((lane & 1) ? 8 : 0) + (lane & 2) * 2;
            const bool odd = lane & 1;
#pragma unroll
            for (int t2 = 0; t2 < 4; t2++) {
                const uint32_t lo0 = pack_bf16(acc[8 * t2 + 0], acc[8 * t2 + 1]), hi0 = pack_bf16(acc[8 * t2 + 2], acc[8 * t2 + 3]);
                const uint32_t lo1 = pack_bf16(acc[8 * t2 + 4], acc[8 * t2 + 5]), hi1 = pack_bf16(acc[8 * t2 + 6], acc[8 * t2 + 7]);
                const uint32_t sl = __shfl_xor_sync(0xffffffffu, odd ? lo0 : lo1, 1), sh = __shfl_xor_sync(0xffffffffu, odd ? hi0 : hi1, 1);
                if (!dry) *reinterpret_cast<uint2*>(o + 16 * t2) = odd ? make_uint2(sl, lo1) : make_uint2(lo0, sl);
                if (!dry) *reinterpret_cast<uint2*>(o + 16 * t2 + 8 * 512) = odd ? make_uint2(sh, hi1) : make_uint2(hi0, sh);
            }
            if (tid == 0 && !dry) TSG(30);
        }
        TS(8);
    }
}

typedef CUresult (*PFN_encodeTiled)(CUtensorMap*, CUtensorMapDataType, cuuint32_t, void*, const cuuint64_t*, const cuuint64_t*,
                                    const cuuint32_t*, const cuuint32_t*, CUtensorMapInterleave, CUtensorMapSwizzle,
                                    CUtensorMapL2promotion, CUtensorMapFloatOOBfill);

void make_map(PFN_encodeTiled enc, CUtensorMap* m, const void* base, int rank, const cuuint64_t* dims, const cuuint64_t* strides, const cuuint32_t* box) {
    cuuint32_t es[5] = {1, 1, 1, 1, 1};
    enc(m, CU_TENSOR_MAP_DATA_TYPE_BFLOAT16, (cuuint32_t)rank, const_cast<void*>(base), dims, strides, box, es,
        CU_TENSOR_MAP_INTERLEAVE_NONE, CU_TENSOR_MAP_SWIZZLE_128B, CU_TENSOR_MAP_L2_PROMOTION_L2_256B, CU_TENSOR_MAP_FLOAT_OOB_FILL_NONE);
}

}

extern "C" void kernel_launch(void* const* d_in, const int* in_sizes, int n_in, void* d_out, int out_size) {
    (void)in_sizes; (void)n_in; (void)out_size;
    const void* x = d_in[0]; const void* wqkv = d_in[1]; const void* wo = d_in[2];
    const void* w1 = d_in[4]; const void* w2 = d_in[5]; const void* gate_w = d_in[6];
    static PFN_encodeTiled enc = nullptr;
    if (!enc) {
        void* fn = nullptr; cudaDriverEntryPointQueryResult st;
        cudaGetDriverEntryPoint("cuTensorMapEncodeTiled", &fn, cudaEnableDefault, &st);
        enc = (PFN_encodeTiled)fn;
        cudaFuncSetAttribute(fused_kernel, cudaFuncAttributeMaxDynamicSharedMemorySize, SMEM_BYTES);
    }
    CUtensorMap mx, mqkv, mw1, mw2, mwo, mw1a, mo;
    void* optr = nullptr;
    cudaGetSymbolAddress(&optr, g_o);
    { cuuint64_t d[2] = {512, 2048}, s[1] = {1024}; cuuint32_t b[2] = {64, 128}; make_map(enc, &mo, optr, 2, d, s, b); }
    { cuuint64_t d[4] = {64, 512, 3, 8}, s[3] = {3584, 128, 448}; cuuint32_t b[4] = {64, 32, 3, 1}; make_map(enc, &mw1a, w1, 4, d, s, b); }
    { cuuint64_t d[2] = {512, 2048}, s[1] = {1024}; cuuint32_t b[2] = {64, 128}; make_map(enc, &mx, x, 2, d, s, b); }
    { cuuint64_t d[4] = {64, 512, 8, 3}, s[3] = {3072, 128, 1024}; cuuint32_t b[4] = {64, 32, 1, 3}; make_map(enc, &mqkv, wqkv, 4, d, s, b); }
    { cuuint64_t d[2] = {1792, 512}, s[1] = {3584}; cuuint32_t b[2] = {64, 32}; make_map(enc, &mw1, w1, 2, d, s, b); }
    { cuuint64_t d[3] = {64, 1792, 8}, s[2] = {1024, 128}; cuuint32_t b[3] = {64, 32, 2}; make_map(enc, &mw2, w2, 3, d, s, b); }
    { cuuint64_t d[2] = {512, 512}, s[1] = {1024}; cuuint32_t b[2] = {64, 256}; make_map(enc, &mwo, wo, 2, d, s, b); }
    fused_kernel<<<NCTA, 384, SMEM_BYTES, cudaStreamPerThread>>>(mx, mqkv, mw1, mw2, mwo, mw1a, mo, (const __nv_bfloat16*)gate_w, (__nv_bfloat16*)d_out,
                                           (const uint8_t*)w1, (const uint8_t*)w2, (const uint8_t*)wo);
}
```

```cpp
#include <cuda_runtime.h>
#include <cuda_bf16.h>
#include <cuda.h>
#include <stdint.h>

namespace {

#define PF1_AT 1
#define PF2_AT 5
#define LEAD1 2
#define NCTA 132
constexpr int RING = 6;
constexpr int SLOT = 16384;
constexpr uint32_t X_OFF = 0;
constexpr uint32_t STG_OFF = X_OFF + 4 * 16384;
constexpr uint32_t RING_OFF = 131072;
constexpr uint32_t BAR_OFF = RING_OFF + RING * SLOT;
constexpr uint32_t B_FULL = BAR_OFF, B_EMPTY = BAR_OFF + 64, B_XFULL = BAR_OFF + 128, B_HDEAD = BAR_OFF + 192,
                   B_EREADY = BAR_OFF + 200, B_KVDONE = BAR_OFF + 208, B_ODONE = BAR_OFF + 224,
                   B_KVREADY = BAR_OFF + 232, B_WOFULL = BAR_OFF + 240, B_HSUM = BAR_OFF + 248, B_PREADY = BAR_OFF + 264,
                   B_SQ = BAR_OFF + 272, B_SF = BAR_OFF + 304;
constexpr uint32_t EPOCH_OFF = BAR_OFF + 256, ITEM_OFF = BAR_OFF + 260, OSRC_OFF = BAR_OFF + 384;
constexpr uint32_t OWN_OFF = X_OFF + 6 * 16384;
constexpr uint32_t SMEM_BYTES = BAR_OFF + 1024;

constexpr int N_QKV = 16, N_FFN1 = 16, N_FFN2 = 14, N_KV = 8, N_O = 7;

__device__ uint4 g_kf[32 * 128 * 32];
__device__ uint4 g_vf[32 * 128 * 32];
__device__ uint4 g_part[16 * 8 * 8 * 8 * 4 * 32];
__device__ __nv_bfloat16 g_o[2048 * 512];
__device__ unsigned g_ticket;
__device__ unsigned g_kvcnt[128 * 32];
__device__ unsigned g_pcnt[128 * 32];
__device__ unsigned g_ocnt[128 * 32];
#define TS(k) do {} while (0)
#define TS2(k) do {} while (0)
#define TS2X(k) do {} while (0)
#define TSX(k) do {} while (0)
#define TSG(k) do {} while (0)

__device__ __forceinline__ uint32_t smem_u32(const void* p) { return (uint32_t)__cvta_generic_to_shared(p); }
__device__ __forceinline__ void mbar_init(uint32_t bar, uint32_t cnt) { asm volatile("mbarrier.init.shared::cta.b64 [%0], %1;" :: "r"(bar), "r"(cnt) : "memory"); }
__device__ __forceinline__ void mbar_expect_tx(uint32_t bar, uint32_t bytes) { asm volatile("mbarrier.arrive.expect_tx.shared::cta.b64 _, [%0], %1;" :: "r"(bar), "r"(bytes) : "memory"); }
__device__ __forceinline__ void mbar_expect_only(uint32_t bar, uint32_t bytes) { asm volatile("mbarrier.expect_tx.relaxed.cta.shared::cta.b64 [%0], %1;" :: "r"(bar), "r"(bytes) : "memory"); }
__device__ __forceinline__ void mbar_arrive(uint32_t bar) { asm volatile("mbarrier.arrive.shared::cta.b64 _, [%0];" :: "r"(bar) : "memory"); }
__device__ __forceinline__ void mbar_wait(uint32_t bar, uint32_t parity) {
    asm volatile("{\n.reg .pred P1, P2;\n.reg .u32 n;\nmov.u32 n, 0;\n"
                 "WAIT_LOOP:\n"
                 "mbarrier.try_wait.parity.shared::cta.b64 P1, [%0], %1;\n"
                 "@P1 bra WAIT_DONE;\n"
                 "add.u32 n, n, 1;\n"
                 "setp.lt.u32 P2, n, 0x400000;\n"
                 "@P2 bra WAIT_LOOP;\n"
                 "WAIT_DONE:\n}" :: "r"(bar), "r"(parity) : "memory");
}
__device__ __forceinline__ void tma_2d(uint32_t dst, const void* map, uint32_t bar, int c0, int c1) {
    asm volatile("cp.async.bulk.tensor.2d.shared::cluster.global.mbarrier::complete_tx::bytes [%0], [%1, {%3, %4}], [%2];"
        :: "r"(dst), "l"(map), "r"(bar), "r"(c0), "r"(c1) : "memory");
}
__device__ __forceinline__ void tma_3d(uint32_t dst, const void* map, uint32_t bar, int c0, int c1, int c2) {
    asm volatile("cp.async.bulk.tensor.3d.shared::cluster.global.mbarrier::complete_tx::bytes [%0], [%1, {%3, %4, %5}], [%2];"
        :: "r"(dst), "l"(map), "r"(bar), "r"(c0), "r"(c1), "r"(c2) : "memory");
}
__device__ __forceinline__ void tma_4d(uint32_t dst, const void* map, uint32_t bar, int c0, int c1, int c2, int c3) {
    asm volatile("cp.async.bulk.tensor.4d.shared::cluster.global.mbarrier::complete_tx::bytes [%0], [%1, {%3, %4, %5, %6}], [%2];"
        :: "r"(dst), "l"(map), "r"(bar), "r"(c0), "r"(c1), "r"(c2), "r"(c3) : "memory");
}
__device__ __forceinline__ void bulk_g2s(uint32_t dst, const void* src, uint32_t bytes, uint32_t bar) {
    asm volatile("cp.async.bulk.shared::cluster.global.mbarrier::complete_tx::bytes [%0], [%1], %2, [%3];"
        :: "r"(dst), "l"(src), "r"(bytes), "r"(bar) : "memory");
}
__device__ __forceinline__ void prefetch_l2(const void* src, uint32_t bytes) {
    asm volatile("cp.async.bulk.prefetch.L2.global [%0], %1;" :: "l"(src), "r"(bytes) : "memory");
}
__device__ __forceinline__ bool elect_one() {
    uint32_t p;
    asm volatile("{\n.reg .pred P;\nelect.sync _|P, 0xffffffff;\nselp.u32 %0, 1, 0, P;\n}" : "=r"(p));
    return p != 0;
}
__device__ __forceinline__ void wgmma_fence() { asm volatile("wgmma.fence.sync.aligned;" ::: "memory"); }
__device__ __forceinline__ void wgmma_commit() { asm volatile("wgmma.commit_group.sync.aligned;" ::: "memory"); }
template <int N> __device__ __forceinline__ void wgmma_wait() { asm volatile("wgmma.wait_group.sync.aligned %0;" :: "n"(N) : "memory"); }
__device__ __forceinline__ void fence_async_smem() { asm volatile("fence.proxy.async.shared::cta;" ::: "memory"); }
__device__ __forceinline__ uint64_t desc_a(uint32_t addr) {
    return (uint64_t)((addr & 0x3FFFF) >> 4) | ((uint64_t)1 << 16) | ((uint64_t)(1024 >> 4) << 32) | ((uint64_t)1 << 62);
}
__device__ __forceinline__ uint64_t desc_b(uint32_t addr) {
    return (uint64_t)((addr & 0x3FFFF) >> 4) | ((uint64_t)(4096 >> 4) << 16) | ((uint64_t)(1024 >> 4) << 32) | ((uint64_t)1 << 62);
}
__device__ __forceinline__ uint32_t pack_bf16(float lo, float hi) {
    uint32_t r; asm("cvt.rn.bf16x2.f32 %0, %1, %2;" : "=r"(r) : "f"(hi), "f"(lo)); return r;
}
__device__ __forceinline__ uint32_t pack_bf16_relu(float lo, float hi) {
    uint32_t r; asm("cvt.rn.relu.bf16x2.f32 %0, %1, %2;" : "=r"(r) : "f"(hi), "f"(lo)); return r;
}
__device__ __forceinline__ uint32_t movmatrix(uint32_t a) {
    uint32_t d; asm volatile("movmatrix.sync.aligned.m8n8.trans.b16 %0, %1;" : "=r"(d) : "r"(a)); return d;
}
__device__ __forceinline__ void stmatrix_x4(uint32_t addr, uint32_t r0, uint32_t r1, uint32_t r2, uint32_t r3) {
    asm volatile("stmatrix.sync.aligned.m8n8.x4.shared.b16 [%0], {%1, %2, %3, %4};" :: "r"(addr), "r"(r0), "r"(r1), "r"(r2), "r"(r3) : "memory");
}
__device__ __forceinline__ uint4 lds128(uint32_t addr) {
    uint4 v; asm volatile("ld.shared.v4.b32 {%0, %1, %2, %3}, [%4];" : "=r"(v.x), "=r"(v.y), "=r"(v.z), "=r"(v.w) : "r"(addr) : "memory"); return v;
}
__device__ __forceinline__ void mma16816(float (&c)[4], uint32_t a0, uint32_t a1, uint32_t a2, uint32_t a3, uint32_t b0, uint32_t b1) {
    asm volatile("mma.sync.aligned.m16n8k16.row.col.f32.bf16.bf16.f32 {%0,%1,%2,%3}, {%4,%5,%6,%7}, {%8,%9}, {%0,%1,%2,%3};"
        : "+f"(c[0]), "+f"(c[1]), "+f"(c[2]), "+f"(c[3]) : "r"(a0), "r"(a1), "r"(a2), "r"(a3), "r"(b0), "r"(b1));
}
__device__ __forceinline__ void mma16816_c(float (&c)[4], uint32_t a0, uint32_t a1, uint32_t a2, uint32_t a3, uint32_t b0, uint32_t b1, float ci) {
    asm volatile("mma.sync.aligned.m16n8k16.row.col.f32.bf16.bf16.f32 {%0,%1,%2,%3}, {%4,%5,%6,%7}, {%8,%9}, {%10,%10,%10,%10};"
        : "=f"(c[0]), "=f"(c[1]), "=f"(c[2]), "=f"(c[3]) : "r"(a0), "r"(a1), "r"(a2), "r"(a3), "r"(b0), "r"(b1), "f"(ci));
}
__device__ __forceinline__ int opaque(int v) { asm volatile("" : "+r"(v)); return v; }
__device__ __forceinline__ float ex2(float x) { float y; asm("ex2.approx.ftz.f32 %0, %1;" : "=f"(y) : "f"(x)); return y; }
__device__ __forceinline__ unsigned ld_acquire(const unsigned* p) {
    unsigned v; asm volatile("ld.acquire.gpu.global.u32 %0, [%1];" : "=r"(v) : "l"(p) : "memory"); return v;
}
__device__ __forceinline__ void red_release(unsigned* p, unsigned v) {
    asm volatile("red.release.gpu.global.add.u32 [%0], %1;" :: "l"(p), "r"(v) : "memory");
}
__device__ __forceinline__ void wait_counter(const unsigned* p, unsigned target) {
    uint32_t n = 0;
    while ((int)(ld_acquire(p) - target) < 0) { if (++n > (1u << 20)) break; }
}
__device__ __forceinline__ uint4 ldg_weak(const uint4* p) {
    uint4 v; asm volatile("ld.global.L1::no_allocate.v4.b32 {%0, %1, %2, %3}, [%4];" : "=r"(v.x), "=r"(v.y), "=r"(v.z), "=r"(v.w) : "l"(p) : "memory"); return v;
}
__device__ __forceinline__ float bf_lo(uint32_t v) { return __uint_as_float(v << 16); }
__device__ __forceinline__ float bf_hi(uint32_t v) { return __uint_as_float(v & 0xFFFF0000u); }

__device__ __forceinline__ void wgmma_ss_n64(float (&d)[32], uint64_t da, uint64_t db, int scale_d) {
    asm volatile("{\n.reg .pred p;\nsetp.ne.b32 p, %34, 0;\n"
        "wgmma.mma_async.sync.aligned.m64n64k16.f32.bf16.bf16 {%0, %1, %2, %3, %4, %5, %6, %7, %8, %9, %10, %11, %12, %13, %14, %15, %16, %17, %18, %19, %20, %21, %22, %23, %24, %25, %26, %27, %28, %29, %30, %31}, %32, %33, p, 1, 1, 0, 1;\n}\n"
        : "+f"(d[0]), "+f"(d[1]), "+f"(d[2]), "+f"(d[3]), "+f"(d[4]), "+f"(d[5]), "+f"(d[6]), "+f"(d[7]), "+f"(d[8]), "+f"(d[9]), "+f"(d[10]), "+f"(d[11]), "+f"(d[12]), "+f"(d[13]), "+f"(d[14]), "+f"(d[15]), "+f"(d[16]), "+f"(d[17]), "+f"(d[18]), "+f"(d[19]), "+f"(d[20]), "+f"(d[21]), "+f"(d[22]), "+f"(d[23]), "+f"(d[24]), "+f"(d[25]), "+f"(d[26]), "+f"(d[27]), "+f"(d[28]), "+f"(d[29]), "+f"(d[30]), "+f"(d[31])
        : "l"(da), "l"(db), "r"(scale_d));
}
__device__ __forceinline__ void wgmma_ss_n128(float (&d)[64], uint64_t da, uint64_t db, int scale_d) {
    asm volatile("{\n.reg .pred p;\nsetp.ne.b32 p, %66, 0;\n"
        "wgmma.mma_async.sync.aligned.m64n128k16.f32.bf16.bf16 {%0, %1, %2, %3, %4, %5, %6, %7, %8, %9, %10, %11, %12, %13, %14, %15, %16, %17, %18, %19, %20, %21, %22, %23, %24, %25, %26, %27, %28, %29, %30, %31, %32, %33, %34, %35, %36, %37, %38, %39, %40, %41, %42, %43, %44, %45, %46, %47, %48, %49, %50, %51, %52, %53, %54, %55, %56, %57, %58, %59, %60, %61, %62, %63}, %64, %65, p, 1, 1, 0, 1;\n}\n"
        : "+f"(d[0]), "+f"(d[1]), "+f"(d[2]), "+f"(d[3]), "+f"(d[4]), "+f"(d[5]), "+f"(d[6]), "+f"(d[7]), "+f"(d[8]), "+f"(d[9]), "+f"(d[10]), "+f"(d[11]), "+f"(d[12]), "+f"(d[13]), "+f"(d[14]), "+f"(d[15]), "+f"(d[16]), "+f"(d[17]), "+f"(d[18]), "+f"(d[19]), "+f"(d[20]), "+f"(d[21]), "+f"(d[22]), "+f"(d[23]), "+f"(d[24]), "+f"(d[25]), "+f"(d[26]), "+f"(d[27]), "+f"(d[28]), "+f"(d[29]), "+f"(d[30]), "+f"(d[31]), "+f"(d[32]), "+f"(d[33]), "+f"(d[34]), "+f"(d[35]), "+f"(d[36]), "+f"(d[37]), "+f"(d[38]), "+f"(d[39]), "+f"(d[40]), "+f"(d[41]), "+f"(d[42]), "+f"(d[43]), "+f"(d[44]), "+f"(d[45]), "+f"(d[46]), "+f"(d[47]), "+f"(d[48]), "+f"(d[49]), "+f"(d[50]), "+f"(d[51]), "+f"(d[52]), "+f"(d[53]), "+f"(d[54]), "+f"(d[55]), "+f"(d[56]), "+f"(d[57]), "+f"(d[58]), "+f"(d[59]), "+f"(d[60]), "+f"(d[61]), "+f"(d[62]), "+f"(d[63])
        : "l"(da), "l"(db), "r"(scale_d));
}
__device__ __forceinline__ void wgmma_ss_n200(float (&d)[100], uint64_t da, uint64_t db, int scale_d) {
    asm volatile("{\n.reg .pred p;\nsetp.ne.b32 p, %102, 0;\n"
        "wgmma.mma_async.sync.aligned.m64n200k16.f32.bf16.bf16 {%0, %1, %2, %3, %4, %5, %6, %7, %8, %9, %10, %11, %12, %13, %14, %15, %16, %17, %18, %19, %20, %21, %22, %23, %24, %25, %26, %27, %28, %29, %30, %31, %32, %33, %34, %35, %36, %37, %38, %39, %40, %41, %42, %43, %44, %45, %46, %47, %48, %49, %50, %51, %52, %53, %54, %55, %56, %57, %58, %59, %60, %61, %62, %63, %64, %65, %66, %67, %68, %69, %70, %71, %72, %73, %74, %75, %76, %77, %78, %79, %80, %81, %82, %83, %84, %85, %86, %87, %88, %89, %90, %91, %92, %93, %94, %95, %96, %97, %98, %99}, %100, %101, p, 1, 1, 0, 1;\n}\n"
        : "+f"(d[0]), "+f"(d[1]), "+f"(d[2]), "+f"(d[3]), "+f"(d[4]), "+f"(d[5]), "+f"(d[6]), "+f"(d[7]), "+f"(d[8]), "+f"(d[9]), "+f"(d[10]), "+f"(d[11]), "+f"(d[12]), "+f"(d[13]), "+f"(d[14]), "+f"(d[15]), "+f"(d[16]), "+f"(d[17]), "+f"(d[18]), "+f"(d[19]), "+f"(d[20]), "+f"(d[21]), "+f"(d[22]), "+f"(d[23]), "+f"(d[24]), "+f"(d[25]), "+f"(d[26]), "+f"(d[27]), "+f"(d[28]), "+f"(d[29]), "+f"(d[30]), "+f"(d[31]), "+f"(d[32]), "+f"(d[33]), "+f"(d[34]), "+f"(d[35]), "+f"(d[36]), "+f"(d[37]), "+f"(d[38]), "+f"(d[39]), "+f"(d[40]), "+f"(d[41]), "+f"(d[42]), "+f"(d[43]), "+f"(d[44]), "+f"(d[45]), "+f"(d[46]), "+f"(d[47]), "+f"(d[48]), "+f"(d[49]), "+f"(d[50]), "+f"(d[51]), "+f"(d[52]), "+f"(d[53]), "+f"(d[54]), "+f"(d[55]), "+f"(d[56]), "+f"(d[57]), "+f"(d[58]), "+f"(d[59]), "+f"(d[60]), "+f"(d[61]), "+f"(d[62]), "+f"(d[63]), "+f"(d[64]), "+f"(d[65]), "+f"(d[66]), "+f"(d[67]), "+f"(d[68]), "+f"(d[69]), "+f"(d[70]), "+f"(d[71]), "+f"(d[72]), "+f"(d[73]), "+f"(d[74]), "+f"(d[75]), "+f"(d[76]), "+f"(d[77]), "+f"(d[78]), "+f"(d[79]), "+f"(d[80]), "+f"(d[81]), "+f"(d[82]), "+f"(d[83]), "+f"(d[84]), "+f"(d[85]), "+f"(d[86]), "+f"(d[87]), "+f"(d[88]), "+f"(d[89]), "+f"(d[90]), "+f"(d[91]), "+f"(d[92]), "+f"(d[93]), "+f"(d[94]), "+f"(d[95]), "+f"(d[96]), "+f"(d[97]), "+f"(d[98]), "+f"(d[99])
        : "l"(da), "l"(db), "r"(scale_d));
}
__device__ __forceinline__ void wgmma_ss_n224(float (&d)[112], uint64_t da, uint64_t db, int scale_d) {
    asm volatile("{\n.reg .pred p;\nsetp.ne.b32 p, %114, 0;\n"
        "wgmma.mma_async.sync.aligned.m64n224k16.f32.bf16.bf16 {%0, %1, %2, %3, %4, %5, %6, %7, %8, %9, %10, %11, %12, %13, %14, %15, %16, %17, %18, %19, %20, %21, %22, %23, %24, %25, %26, %27, %28, %29, %30, %31, %32, %33, %34, %35, %36, %37, %38, %39, %40, %41, %42, %43, %44, %45, %46, %47, %48, %49, %50, %51, %52, %53, %54, %55, %56, %57, %58, %59, %60, %61, %62, %63, %64, %65, %66, %67, %68, %69, %70, %71, %72, %73, %74, %75, %76, %77, %78, %79, %80, %81, %82, %83, %84, %85, %86, %87, %88, %89, %90, %91, %92, %93, %94, %95, %96, %97, %98, %99, %100, %101, %102, %103, %104, %105, %106, %107, %108, %109, %110, %111}, %112, %113, p, 1, 1, 0, 1;\n}\n"
        : "+f"(d[0]), "+f"(d[1]), "+f"(d[2]), "+f"(d[3]), "+f"(d[4]), "+f"(d[5]), "+f"(d[6]), "+f"(d[7]), "+f"(d[8]), "+f"(d[9]), "+f"(d[10]), "+f"(d[11]), "+f"(d[12]), "+f"(d[13]), "+f"(d[14]), "+f"(d[15]), "+f"(d[16]), "+f"(d[17]), "+f"(d[18]), "+f"(d[19]), "+f"(d[20]), "+f"(d[21]), "+f"(d[22]), "+f"(d[23]), "+f"(d[24]), "+f"(d[25]), "+f"(d[26]), "+f"(d[27]), "+f"(d[28]), "+f"(d[29]), "+f"(d[30]), "+f"(d[31]), "+f"(d[32]), "+f"(d[33]), "+f"(d[34]), "+f"(d[35]), "+f"(d[36]), "+f"(d[37]), "+f"(d[38]), "+f"(d[39]), "+f"(d[40]), "+f"(d[41]), "+f"(d[42]), "+f"(d[43]), "+f"(d[44]), "+f"(d[45]), "+f"(d[46]), "+f"(d[47]), "+f"(d[48]), "+f"(d[49]), "+f"(d[50]), "+f"(d[51]), "+f"(d[52]), "+f"(d[53]), "+f"(d[54]), "+f"(d[55]), "+f"(d[56]), "+f"(d[57]), "+f"(d[58]), "+f"(d[59]), "+f"(d[60]), "+f"(d[61]), "+f"(d[62]), "+f"(d[63]), "+f"(d[64]), "+f"(d[65]), "+f"(d[66]), "+f"(d[67]), "+f"(d[68]), "+f"(d[69]), "+f"(d[70]), "+f"(d[71]), "+f"(d[72]), "+f"(d[73]), "+f"(d[74]), "+f"(d[75]), "+f"(d[76]), "+f"(d[77]), "+f"(d[78]), "+f"(d[79]), "+f"(d[80]), "+f"(d[81]), "+f"(d[82]), "+f"(d[83]), "+f"(d[84]), "+f"(d[85]), "+f"(d[86]), "+f"(d[87]), "+f"(d[88]), "+f"(d[89]), "+f"(d[90]), "+f"(d[91]), "+f"(d[92]), "+f"(d[93]), "+f"(d[94]), "+f"(d[95]), "+f"(d[96]), "+f"(d[97]), "+f"(d[98]), "+f"(d[99]), "+f"(d[100]), "+f"(d[101]), "+f"(d[102]), "+f"(d[103]), "+f"(d[104]), "+f"(d[105]), "+f"(d[106]), "+f"(d[107]), "+f"(d[108]), "+f"(d[109]), "+f"(d[110]), "+f"(d[111])
        : "l"(da), "l"(db), "r"(scale_d));
}
template <int N> __device__ __forceinline__ void fence_acc(float (&d)[N]) {
#pragma unroll
    for (int i = 0; i < N; i++) asm volatile("" : "+f"(d[i]) :: "memory");
}

__device__ __forceinline__ void bulk_s2g(void* dst, uint32_t src, uint32_t bytes) {
    asm volatile("cp.async.bulk.global.shared::cta.bulk_group [%0], [%1], %2;" :: "l"(dst), "r"(src), "r"(bytes) : "memory");
}
__device__ __forceinline__ void sts128(uint32_t addr, uint4 v) {
    asm volatile("st.shared.v4.b32 [%0], {%1, %2, %3, %4};" :: "r"(addr), "r"(v.x), "r"(v.y), "r"(v.z), "r"(v.w) : "memory");
}
__device__ __forceinline__ void sum_partials(uint32_t sb, int ti, int tj, int lane) {
    for (;;) {
        uint32_t item = 0;
        if (lane == 0) asm volatile("atom.shared.add.u32 %0, [%1], 1;" : "=r"(item) : "r"(sb + ITEM_OFF) : "memory");
        item = __shfl_sync(0xffffffffu, item, 0);
        if (item >= 8) break;
        const uint4* p = g_part + (size_t)((ti * 8 + tj) * 8) * 1024 + item * 128 + lane;
        uint4 v[4][4];
#pragma unroll
        for (int s = 0; s < 4; s++)
#pragma unroll
            for (int n = 0; n < 4; n++) v[n][s] = ldg_weak(p + s * 1024 + n * 32);
#pragma unroll
        for (int n = 0; n < 4; n++) {
            float a[8];
#pragma unroll
            for (int e = 0; e < 8; e++) a[e] = 0.f;
#pragma unroll
            for (int s = 0; s < 4; s++) {
                a[0] += bf_lo(v[n][s].x); a[1] += bf_hi(v[n][s].x); a[2] += bf_lo(v[n][s].y); a[3] += bf_hi(v[n][s].y);
                a[4] += bf_lo(v[n][s].z); a[5] += bf_hi(v[n][s].z); a[6] += bf_lo(v[n][s].w); a[7] += bf_hi(v[n][s].w);
            }
            const uint32_t d = sb + STG_OFF + (item * 8 + n * 2) * 512 + lane * 16;
            sts128(d, make_uint4(__float_as_uint(a[0]), __float_as_uint(a[1]), __float_as_uint(a[2]), __float_as_uint(a[3])));
            sts128(d + 512, make_uint4(__float_as_uint(a[4]), __float_as_uint(a[5]), __float_as_uint(a[6]), __float_as_uint(a[7])));
        }
    }
    __syncwarp();
    if (lane == 0) mbar_arrive(sb + B_HSUM);
}

#define PWAIT() mbar_wait(sb + B_EMPTY + 8 * r.slot, r.phase)
#define CWAIT() do { if (!dry) mbar_wait(sb + B_FULL + 8 * r.slot, r.phase); } while (0)
template <bool B> struct BoolTag { static constexpr bool value = B; };
struct Ring {
    int slot; uint32_t phase;
    __device__ __forceinline__ void next() { if (++slot == RING) { slot = 0; phase ^= 1; } }
};

__global__ void __launch_bounds__(384, 1)
fused_kernel(const __grid_constant__ CUtensorMap map_x, const __grid_constant__ CUtensorMap map_qkv,
             const __grid_constant__ CUtensorMap map_w1, const __grid_constant__ CUtensorMap map_w2,
             const __grid_constant__ CUtensorMap map_wo, const __grid_constant__ CUtensorMap map_w1a,
             const __grid_constant__ CUtensorMap map_o,
             const __nv_bfloat16* __restrict__ gate_w, __nv_bfloat16* __restrict__ out,
             const uint8_t* __restrict__ w1p, const uint8_t* __restrict__ w2p, const uint8_t* __restrict__ wop)
{
    extern __shared__ __align__(1024) uint8_t smem_raw[];
    const uint32_t sb = smem_u32(smem_raw);
    const int tid = threadIdx.x, warp = tid >> 5, lane = tid & 31;
    const bool dry = blockIdx.x >= 128;
    const int ti = dry ? (int)(blockIdx.x & 1) * 2 : blockIdx.x >> 3, tj = blockIdx.x & 7;
    if (dry && warp >= 8) {
        asm volatile("setmaxnreg.dec.sync.aligned.u32 88;");
        return;
    }

    if (tid == 0 && !dry) { TSG(31); TSX(0); }
    if (tid == 320) {
        asm volatile("prefetch.tensormap [%0];" :: "l"(&map_x) : "memory");
        asm volatile("prefetch.tensormap [%0];" :: "l"(&map_qkv) : "memory");
        asm volatile("prefetch.tensormap [%0];" :: "l"(&map_w1) : "memory");
        asm volatile("prefetch.tensormap [%0];" :: "l"(&map_w1a) : "memory");
        asm volatile("prefetch.tensormap [%0];" :: "l"(&map_w2) : "memory");
        asm volatile("prefetch.tensormap [%0];" :: "l"(&map_wo) : "memory");
        asm volatile("prefetch.tensormap [%0];" :: "l"(&map_o) : "memory");
    }
    uint32_t gwv[N_QKV / 2];
    if (warp == 8) {
        const unsigned short* gws = reinterpret_cast<const unsigned short*>(gate_w);
#pragma unroll
        for (int n = 0; n < N_QKV / 2; n++) gwv[n] = (uint32_t)__ldg(gws + 64 * n + lane) | ((uint32_t)__ldg(gws + 64 * n + 32 + lane) << 16);
    }
    if (tid == 256) {
        for (int s = 0; s < RING; s++) { mbar_init(sb + B_FULL + 8 * s, 1); mbar_init(sb + B_EMPTY + 8 * s, 8); }
        for (int s = 0; s < 8; s++) mbar_init(sb + B_XFULL + 8 * s, 1);
        mbar_init(sb + B_HDEAD, 8); mbar_init(sb + B_EREADY, 1); mbar_init(sb + B_KVDONE, 8); mbar_init(sb + B_KVREADY, 1);
        mbar_init(sb + B_ODONE, 8); mbar_init(sb + B_WOFULL, 1); mbar_init(sb + B_HSUM, 3);
        mbar_init(sb + B_PREADY, 1); mbar_init(sb + B_SF, 1); mbar_init(sb + B_SF + 8, 1);
        for (int s = 0; s < 4; s++) mbar_init(sb + B_SQ + 8 * s, 8);
        asm volatile("st.shared.u32 [%0], %1;" :: "r"(sb + ITEM_OFF), "r"(0) : "memory");
        asm volatile("fence.mbarrier_init.release.cluster;" ::: "memory");
        fence_async_smem();
        mbar_expect_tx(sb + B_XFULL, 16384);
        tma_2d(sb + X_OFF, &map_x, sb + B_XFULL, 0, ti * 128);
        mbar_expect_only(sb + B_FULL, 12288);
        tma_4d(sb + RING_OFF, &map_qkv, sb + B_FULL, 0, 0, tj, 0);
    }
    if (!dry) __syncthreads();

    if (warp >= 8) {
        asm volatile("setmaxnreg.dec.sync.aligned.u32 88;");
        if (warp == 8) {
            Ring r{0, 1};
            const bool leader = elect_one();
#pragma unroll
            for (int n = 0; n < N_QKV; n++) {
                const uint32_t full = sb + B_FULL + 8 * r.slot, dst = sb + RING_OFF + r.slot * SLOT;
                if (n > 0) {
                    if (!(n & 1) && leader) {
                        mbar_expect_tx(sb + B_XFULL + 8 * (n >> 1), 16384);
                        tma_2d(sb + X_OFF + (n >> 1) * 16384, &map_x, sb + B_XFULL + 8 * (n >> 1), (n >> 1) * 64, ti * 128);
                    }
                    if (n >= RING) PWAIT();
                    if (leader) {
                        mbar_expect_only(full, 12288);
                        tma_4d(dst, &map_qkv, full, 0, 32 * n, tj, 0);
                    }
                }
                const uint32_t gv = (n & 1) ? (gwv[n >> 1] >> 16) : (gwv[n >> 1] & 0xFFFFu);
                asm volatile("st.shared.v4.b32 [%0], {%1, %2, %2, %2};" :: "r"(dst + 12288 + lane * 128 + ((lane & 7) << 4)), "r"(gv), "r"(0) : "memory");
                fence_async_smem();
                __syncwarp();
                if (leader) mbar_arrive(full);
                r.next();
            }
#pragma unroll 1
            for (int n = 0; n < N_FFN1; n++) {
                const uint32_t full = sb + B_FULL + 8 * r.slot, dst = sb + RING_OFF + r.slot * SLOT;
                PWAIT();
                if (leader) {
                    mbar_expect_tx(full, 16384);
                    tma_4d(dst, &map_w1a, full, 0, 32 * n, 0, tj);
                    tma_2d(dst + 3 * 4096, &map_w1, full, 224 * tj + 192, 32 * n);
                }
                r.next();
            }
            {
                int q = 0, rr = 0;
#pragma unroll 1
                for (int n = 0; n < N_FFN2; n++) {
                    const uint32_t full = sb + B_FULL + 8 * r.slot, dst = sb + RING_OFF + r.slot * SLOT;
                    PWAIT();
                    if (leader) mbar_expect_tx(full, 16384);
#pragma unroll
                    for (int h = 0; h < 2; h++) {
                        if (leader) tma_3d(dst + h * 8192, &map_w2, full, 0, 224 * tj + 32 * rr, 2 * q);
                        if (++rr == 7) { rr = 0; q++; }
                    }
                    r.next();
                }
            }
            mbar_wait(sb + B_KVREADY, 0);
            asm volatile("fence.proxy.async.global;" ::: "memory");
            {
                const int bbase = 8 * ti - 16, b0 = bbase < 0 ? 0 : bbase;
                const uint32_t bytes = (uint32_t)(8 * ti + 8 - b0) * 512;
#pragma unroll 1
                for (int m = 0; m < N_KV; m++) {
                    const uint32_t full = sb + B_FULL + 8 * r.slot, dst = sb + RING_OFF + r.slot * SLOT;
                    if (m == RING) {
                        mbar_wait(sb + B_HDEAD, 0);
                        if (leader) {
                            mbar_expect_tx(sb + B_WOFULL, 65536);
#pragma unroll
                            for (int e = 0; e < 2; e++) tma_2d(sb + X_OFF + e * 32768, &map_wo, sb + B_WOFULL, 64 * tj, 256 * e);
                        }
                    }
                    PWAIT();
                    if (leader) {
                        const uint4* src = ((m & 1) ? g_vf : g_kf) + ((tj * 4 + (m >> 1)) * 128 + b0) * 32;
                        mbar_expect_tx(full, bytes);
                        bulk_g2s(dst + (b0 - bbase) * 512, src, bytes, full);
                    }
                    r.next();
                }
            }
            {
                mbar_wait(sb + B_EREADY, 0);
                unsigned epoch; asm volatile("ld.shared.u32 %0, [%1];" : "=r"(epoch) : "r"(sb + EPOCH_OFF) : "memory");
                uint32_t pending = 0xFFu & ~(1u << tj), ready = 0;
                mbar_wait(sb + B_HSUM, 0);
#pragma unroll 1
                for (int m = 0; m < N_O; m++) {
                    const uint32_t full = sb + B_FULL + 8 * r.slot, dst = sb + RING_OFF + r.slot * SLOT;
                    PWAIT();
                    for (int it = 0; it < (1 << 20) && !ready; it++) {
                        bool ok = false;
                        if (lane < 8 && ((pending >> lane) & 1)) ok = (int)(ld_acquire(&g_ocnt[(ti * 8 + lane) * 32]) - 8 * (epoch + 1)) >= 0;
                        ready = __ballot_sync(0xffffffffu, ok);
                        if (!ready) __nanosleep(100);
                    }
                    const int js = ready ? __ffs(ready) - 1 : __ffs(pending) - 1;
                    pending &= ~(1u << js); ready &= ~(1u << js);
                    asm volatile("fence.proxy.async.global;" ::: "memory");
                    if (leader) {
                        asm volatile("st.shared.u32 [%0], %1;" :: "r"(sb + OSRC_OFF + 4 * m), "r"(js) : "memory");
                        mbar_expect_tx(full, 16384);
                        tma_2d(dst, &map_o, full, 64 * js, ti * 128);
                    }
                    r.next();
                }
            }
        } else if (warp == 9) {
            unsigned epoch = 0;
            if (lane == 0) {
                epoch = atomicAdd(&g_ticket, 1u) >> 7;
                asm volatile("st.shared.u32 [%0], %1;" :: "r"(sb + EPOCH_OFF), "r"(epoch) : "memory");
                mbar_arrive(sb + B_EREADY);
                mbar_wait(sb + B_XFULL + 8 * PF1_AT, 0);
                prefetch_l2(w1p + (size_t)blockIdx.x * 14336, 14336);
                mbar_wait(sb + B_XFULL + 8 * PF2_AT, 0);
                prefetch_l2(w2p + (size_t)blockIdx.x * 14336, 14336);
                prefetch_l2(wop + (size_t)blockIdx.x * 4096, 4096);
                mbar_wait(sb + B_KVDONE, 0);
                red_release(&g_kvcnt[blockIdx.x * 32], 1u);
            }
            epoch = __shfl_sync(0xffffffffu, epoch, 0);
            if (lane < 3 && ti - lane >= 0) wait_counter(&g_kvcnt[((ti - lane) * 8 + tj) * 32], epoch + 1);
            __syncwarp();
            if (lane == 0) mbar_arrive(sb + B_KVREADY);
            mbar_wait(sb + B_SQ + 24, 0);
            if (lane < 8) wait_counter(&g_pcnt[(ti * 8 + lane) * 32], epoch + 1);
            __syncwarp();
            if (lane == 0) { mbar_arrive(sb + B_PREADY); TSX(13); }
            sum_partials(sb, ti, tj, lane);
            if (lane == 0) TSX(14);
        } else {
            if (warp == 10) {
#pragma unroll 1
                for (int q = 0; q < 4; q++) {
                    mbar_wait(sb + B_SQ + 8 * q, 0);
                    if (lane < 16) {
                        uint4* d = g_part + (size_t)(((ti * 8 + 2 * q + (lane & 1)) * 8 + tj) * 8 + (lane >> 1)) * 128;
                        bulk_s2g(d, sb + STG_OFF + (q & 1) * 32768 + lane * 2048, 2048);
                        asm volatile("cp.async.bulk.commit_group;" ::: "memory");
                        asm volatile("cp.async.bulk.wait_group.read 0;" ::: "memory");
                    }
                    __syncwarp();
                    if (lane == 0) mbar_arrive(sb + B_SF + 8 * (q & 1));
                }
                asm volatile("cp.async.bulk.wait_group 0;" ::: "memory");
                asm volatile("fence.proxy.async.global;" ::: "memory");
                __syncwarp();
                if (lane == 0) { red_release(&g_pcnt[blockIdx.x * 32], 1u); TSX(12); }
            }
            mbar_wait(sb + B_PREADY, 0);
            sum_partials(sb, ti, tj, lane);
        }
    } else {
        asm volatile("setmaxnreg.inc.sync.aligned.u32 208;");
        const int wg = warp >> 2, g = lane >> 2, c = lane & 3;
        const uint32_t xa = sb + X_OFF + wg * 8192;
        Ring r{0, 0};
        const bool lane0 = lane == 0 && !dry;
        uint32_t qf[4][4];
        float g0, g1;
        TS(9);
        {
            float acc[100];
            int prev = 0;
            if (wg == 1) asm volatile("bar.sync 3, 256;" ::: "memory");
            for (int s = 0; s < (dry ? 4 : N_QKV); s++) {
                if (!(s & 1) && !dry) mbar_wait(sb + B_XFULL + 8 * (s >> 1), 0);
                CWAIT();
                if (s == 0) TS(1);
                if (s == 2) TS(28);
                if (s == 6) TS(29);
                if (s == 10) TS(20);
                const uint32_t bs = sb + RING_OFF + r.slot * SLOT, as = xa + (s >> 1) * 16384 + (s & 1) * 64;
                wgmma_fence();
                wgmma_ss_n200(acc, desc_a(as), desc_b(bs), s);
                wgmma_ss_n200(acc, desc_a(as + 32), desc_b(bs + 2048), 1);
                wgmma_commit();
                if (wg == 0 && s == LEAD1) asm volatile("bar.arrive 3, 256;" ::: "memory");
                if (s > 0) { wgmma_wait<1>(); if (lane0) mbar_arrive(sb + B_EMPTY + 8 * prev); }
                prev = r.slot; r.next();
            }
            wgmma_wait<0>();
            fence_acc(acc);
            if (lane0) mbar_arrive(sb + B_EMPTY + 8 * prev);
            TS(2);
            const int blk = ti * 8 + warp;
#pragma unroll
            for (int hh = 0; hh < 4; hh++) {
                const float* t0 = &acc[8 * hh]; const float* t1 = &acc[8 * hh + 4];
                qf[hh][0] = pack_bf16(t0[0], t0[1]); qf[hh][1] = pack_bf16(t0[2], t0[3]);
                qf[hh][2] = pack_bf16(t1[0], t1[1]); qf[hh][3] = pack_bf16(t1[2], t1[3]);
                const float* k0 = &acc[32 + 8 * hh]; const float* k1 = &acc[32 + 8 * hh + 4];
                uint4 kv;
                kv.x = pack_bf16(k0[0], k0[1]); kv.y = pack_bf16(k1[0], k1[1]);
                kv.z = pack_bf16(k0[2], k0[3]); kv.w = pack_bf16(k1[2], k1[3]);
                if (!dry) g_kf[((tj * 4 + hh) * 128 + blk) * 32 + lane] = kv;
                const float* v0 = &acc[64 + 8 * hh]; const float* v1 = &acc[64 + 8 * hh + 4];
                uint4 vv;
                vv.x = movmatrix(pack_bf16(v0[0], v0[1])); vv.y = movmatrix(pack_bf16(v0[2], v0[3]));
                vv.z = movmatrix(pack_bf16(v1[0], v1[1])); vv.w = movmatrix(pack_bf16(v1[2], v1[3]));
                if (!dry) g_vf[((tj * 4 + hh) * 128 + blk) * 32 + lane] = vv;
            }
            __syncwarp();
            if (lane0) mbar_arrive(sb + B_KVDONE);
            const float z0 = __shfl_sync(0xffffffffu, acc[96], lane & ~3), z1 = __shfl_sync(0xffffffffu, acc[98], lane & ~3);
            g0 = 1.f / (1.f + __expf(-z0)); g1 = 1.f / (1.f + __expf(-z1));
        }
        TS(3);
        const int wrow = (warp & 3) * 16;
        {
            float acc[112];
            int prev = 0;
            for (int s = 0; s < (dry ? 4 : N_FFN1); s++) {
                CWAIT();
                const uint32_t bs = sb + RING_OFF + r.slot * SLOT, as = xa + (s >> 1) * 16384 + (s & 1) * 64;
                wgmma_fence();
                wgmma_ss_n224(acc, desc_a(as), desc_b(bs), s);
                wgmma_ss_n224(acc, desc_a(as + 32), desc_b(bs + 2048), 1);
                wgmma_commit();
                if (s > 0) { wgmma_wait<1>(); if (lane0) mbar_arrive(sb + B_EMPTY + 8 * prev); }
                prev = r.slot; r.next();
            }
            wgmma_wait<0>();
            fence_acc(acc);
            if (lane0) mbar_arrive(sb + B_EMPTY + 8 * prev);
            TS(4);
            const float s0 = 1.f - g0, s1 = 1.f - g1;
            asm volatile("bar.sync %0, 128;" :: "r"(1 + wg) : "memory");
            const uint32_t strow = xa + (wrow + ((lane >> 3) & 1) * 8 + (lane & 7)) * 128;
#pragma unroll
            for (int p = 0; p < 14; p++) {
                const int nt = 2 * p + (lane >> 4);
                const float* a = &acc[8 * p];
                stmatrix_x4(strow + (p >> 2) * 16384 + (((nt & 7) ^ (lane & 7)) << 4),
                            pack_bf16_relu(a[0] * s0, a[1] * s0), pack_bf16_relu(a[2] * s1, a[3] * s1),
                            pack_bf16_relu(a[4] * s0, a[5] * s0), pack_bf16_relu(a[6] * s1, a[7] * s1));
            }
        }
        TS(5);
        {
            fence_async_smem();
            asm volatile("bar.sync 4, 256;" ::: "memory");
            float accA[64], accB[64];
            auto epilogue = [&](float (&acc)[64], int q) {
                fence_acc(acc);
                const uint32_t st = sb + STG_OFF + (q & 1) * 32768 + warp * 4096;
                if (q >= 2 && !dry) mbar_wait(sb + B_SF + 8 * (q & 1), 0);
#pragma unroll
                for (int t2 = 0; t2 < 8; t2++) {
                    uint4 v;
                    v.x = pack_bf16(acc[8 * t2 + 0], acc[8 * t2 + 1]); v.y = pack_bf16(acc[8 * t2 + 2], acc[8 * t2 + 3]);
                    v.z = pack_bf16(acc[8 * t2 + 4], acc[8 * t2 + 5]); v.w = pack_bf16(acc[8 * t2 + 6], acc[8 * t2 + 7]);
                    sts128(st + t2 * 512 + lane * 16, v);
                }
                fence_async_smem();
                __syncwarp();
                if (lane0) mbar_arrive(sb + B_SQ + 8 * q);
            };
            int rel = r.slot;
#pragma unroll
            for (int m = 0; m < N_FFN2; m++) {
                CWAIT();
                wgmma_fence();
#pragma unroll
                for (int h = 0; h < 2; h++) {
                    const int u = 2 * m + h, q = u / 7, rr = u % 7;
                    const uint32_t bs = sb + RING_OFF + r.slot * SLOT + h * 8192;
                    const uint32_t as = xa + (rr >> 1) * 16384 + (rr & 1) * 64;
                    if (!(q & 1)) {
                        wgmma_ss_n128(accA, desc_a(as), desc_b(bs), rr);
                        wgmma_ss_n128(accA, desc_a(as + 32), desc_b(bs + 2048), 1);
                    } else {
                        wgmma_ss_n128(accB, desc_a(as), desc_b(bs), rr);
                        wgmma_ss_n128(accB, desc_a(as + 32), desc_b(bs + 2048), 1);
                    }
                }
                wgmma_commit();
                r.next();
                wgmma_wait<1>();
                if (m > 0) {
                    if (lane0) mbar_arrive(sb + B_EMPTY + 8 * rel);
                    if (++rel == RING) rel = 0;
                }
                if (m == 4) { TS(25); epilogue(accA, 0); }
                if (m == 7) { TS(26); epilogue(accB, 1); }
                if (m == 11) { TS(27); epilogue(accA, 2); }
            }
            wgmma_wait<0>();
            if (lane0) { mbar_arrive(sb + B_EMPTY + 8 * rel); mbar_arrive(sb + B_HDEAD); }
            epilogue(accB, 3);
        }
        TS(6);
        {
            const float SC = 0.25f * 1.4426950408889634f;
            const int gb0 = 8 * ti - 16 + warp;
            int slotK = 0, slotV = 0;
            const uint32_t ostore = sb + OWN_OFF + (warp * 16 + ((lane >> 3) & 1) * 8 + (lane & 7)) * 128;
            uint32_t* odst = reinterpret_cast<uint32_t*>(g_o + (size_t)(ti * 128 + warp * 16 + g) * 512 + tj * 64 + ((lane & 1) ? 8 : 0) + (lane & 2) * 2);
#define NHEADS (dry ? 2 : 4)
#define ATT_KWAIT(kb) do { slotK = r.slot; CWAIT(); kb = sb + RING_OFF + slotK * SLOT + warp * 512 + lane * 16; r.next(); } while (0)
#define ATT_VWAIT(vb) do { slotV = r.slot; CWAIT(); vb = sb + RING_OFF + slotV * SLOT + warp * 512 + lane * 16; r.next(); TS(21 + hh); } while (0)
#define ATT_KREL() do { __syncwarp(); if (lane0) mbar_arrive(sb + B_EMPTY + 8 * slotK); } while (0)
#define ATT_VREL() do { __syncwarp(); if (lane0) mbar_arrive(sb + B_EMPTY + 8 * slotV); } while (0)
#define ATT_NEXTQ(h) do { \
                if ((h) == 1) { q0 = qf[1][0]; q1 = qf[1][1]; q2 = qf[1][2]; q3 = qf[1][3]; } \
                else if ((h) == 2) { q0 = qf[2][0]; q1 = qf[2][1]; q2 = qf[2][2]; q3 = qf[2][3]; } \
                else { q0 = qf[3][0]; q1 = qf[3][1]; q2 = qf[3][2]; q3 = qf[3][3]; } } while (0)
#define ATT_STORE(h, r0, r1, r2, r3) do { \
                if ((h) == 0 && !dry) mbar_wait(sb + B_SF + 8, 1);        \
                stmatrix_x4(ostore + (((2 * (h) + (lane >> 4)) ^ (lane & 7)) << 4), r0, r1, r2, r3); \
                const bool odd = lane & 1; \
                const uint32_t sl = __shfl_xor_sync(0xffffffffu, odd ? (r0) : (r2), 1), sh = __shfl_xor_sync(0xffffffffu, odd ? (r1) : (r3), 1); \
                if (!dry) *reinterpret_cast<uint2*>(odst + 8 * (h)) = odd ? make_uint2(sl, r2) : make_uint2(r0, sl); \
                if (!dry) *reinterpret_cast<uint2*>(odst + 8 * (h) + 8 * 256) = odd ? make_uint2(sh, r3) : make_uint2(r1, sh); \
                } while (0)
            auto attention = [&](auto masked_tag) {
            constexpr bool MASKED = decltype(masked_tag)::value;
            const float NEG = -INFINITY;
            const uint32_t ONES = 0x3F803F80u;
            float sa[8][2][4], sb2[8][2][4];
            float o[2][4], ls[4];
            float m0, m1;
            uint32_t q0 = qf[0][0], q1 = qf[0][1], q2 = qf[0][2], q3 = qf[0][3];
            auto qk = [&](float (&s)[8][2][4], int ps, int t, uint32_t kbase) {
                if (ps == 0 && t == 0) {
                    const uint4 kd = lds128(kbase + 16 * 512);
                    const uint4 kf = lds128(kbase);
                    float f[2][4];
                    const float ci = (!MASKED || opaque(gb0) >= 0) ? 0.f : NEG;
                    mma16816_c(s[0][0], q0, q1, q2, q3, kd.x, kd.y, 0.f);
                    mma16816_c(s[0][1], q0, q1, q2, q3, kd.z, kd.w, 0.f);
                    mma16816_c(f[0], q0, q1, q2, q3, kf.x, kf.y, ci);
                    mma16816_c(f[1], q0, q1, q2, q3, kf.z, kf.w, ci);
#pragma unroll
                    for (int u = 0; u < 2; u++)
#pragma unroll
                        for (int e = 0; e < 4; e++) {
                            const int row = g + 8 * (e >> 1), col = 8 * u + 2 * c + (e & 1);
                            s[0][u][e] = (col > row) ? f[u][e] : s[0][u][e];
                        }
                } else {
                    const uint4 kf = lds128(kbase + (8 * ps + t) * 512);
                    const float ci = (!MASKED || opaque(gb0) + 8 * ps + t >= 0) ? 0.f : NEG;
                    mma16816_c(s[t][0], q0, q1, q2, q3, kf.x, kf.y, ci);
                    mma16816_c(s[t][1], q0, q1, q2, q3, kf.z, kf.w, ci);
                }
            };
            auto rowmax = [&](float (&s)[8][2][4], float b0, float b1, float& n0, float& n1) {
                int i0 = __float_as_int(b0), i1 = __float_as_int(b1);
#pragma unroll
                for (int t = 0; t < 8; t++)
#pragma unroll
                    for (int u = 0; u < 2; u++) {
                        i0 = __vimax3_s32(i0, __float_as_int(s[t][u][0]), __float_as_int(s[t][u][1]));
                        i1 = __vimax3_s32(i1, __float_as_int(s[t][u][2]), __float_as_int(s[t][u][3]));
                    }
                i0 = max(i0, __shfl_xor_sync(0xffffffffu, i0, 1)); i1 = max(i1, __shfl_xor_sync(0xffffffffu, i1, 1));
                i0 = max(i0, __shfl_xor_sync(0xffffffffu, i0, 2)); i1 = max(i1, __shfl_xor_sync(0xffffffffu, i1, 2));
                n0 = __int_as_float(i0); n1 = __int_as_float(i1);
                if (__any_sync(0xffffffffu, (i0 | i1) < 0)) {
                    asm volatile("" ::: "memory");
                    n0 = b0; n1 = b1;
#pragma unroll
                    for (int t = 0; t < 8; t++)
#pragma unroll
                        for (int u = 0; u < 2; u++) {
                            n0 = fmaxf(n0, fmaxf(s[t][u][0], s[t][u][1]));
                            n1 = fmaxf(n1, fmaxf(s[t][u][2], s[t][u][3]));
                        }
                    n0 = fmaxf(n0, __shfl_xor_sync(0xffffffffu, n0, 1)); n1 = fmaxf(n1, __shfl_xor_sync(0xffffffffu, n1, 1));
                    n0 = fmaxf(n0, __shfl_xor_sync(0xffffffffu, n0, 2)); n1 = fmaxf(n1, __shfl_xor_sync(0xffffffffu, n1, 2));
                }
            };
            auto pv = [&](const float (&p)[2][4], uint32_t vaddr) {
                const uint4 vf = lds128(vaddr);
                const uint32_t a0 = pack_bf16(p[0][0], p[0][1]), a1 = pack_bf16(p[0][2], p[0][3]);
                const uint32_t a2 = pack_bf16(p[1][0], p[1][1]), a3 = pack_bf16(p[1][2], p[1][3]);
                mma16816(o[0], a0, a1, a2, a3, vf.x, vf.y);
                mma16816(o[1], a0, a1, a2, a3, vf.z, vf.w);
                mma16816(ls, a0, a1, a2, a3, ONES, ONES);
            };
            auto expv = [&](float (&s)[8][2][4], int ps, int t, float mc0, float mc1, uint32_t vbase) {
                float p[2][4];
#pragma unroll
                for (int u = 0; u < 2; u++) {
                    p[u][0] = ex2(fmaf(s[t][u][0], SC, -mc0)); p[u][1] = ex2(fmaf(s[t][u][1], SC, -mc0));
                    p[u][2] = ex2(fmaf(s[t][u][2], SC, -mc1)); p[u][3] = ex2(fmaf(s[t][u][3], SC, -mc1));
                }
                if (ps == 0 && t == 0) {
                    float pd[2][4], pf[2][4];
#pragma unroll
                    for (int u = 0; u < 2; u++)
#pragma unroll
                        for (int e = 0; e < 4; e++) {
                            const int row = g + 8 * (e >> 1), col = 8 * u + 2 * c + (e & 1);
                            pf[u][e] = (col > row) ? p[u][e] : 0.f;
                            pd[u][e] = (col > row) ? 0.f : p[u][e];
                        }
                    pv(pd, vbase + 16 * 512);
                    pv(pf, vbase);
                } else {
                    pv(p, vbase + (8 * ps + t) * 512);
                }
            };
            uint32_t kbase, vbase;
            ATT_KWAIT(kbase);
#pragma unroll
            for (int t = 0; t < 8; t++) qk(sa, 0, t, kbase);
            rowmax(sa, NEG, NEG, m0, m1);
#pragma unroll 1
            for (int hh = 0; hh < NHEADS; hh++) {
                ATT_VWAIT(vbase);
#pragma unroll
                for (int e = 0; e < 4; e++) { o[0][e] = 0.f; o[1][e] = 0.f; ls[e] = 0.f; }
                {
                    const float mc0 = m0 * SC, mc1 = m1 * SC;
#pragma unroll
                    for (int t = 0; t < 8; t++) { qk(sb2, 1, t, kbase); expv(sa, 0, t, mc0, mc1, vbase); }
                    ATT_KREL();
                    float n0, n1;
                    rowmax(sb2, m0, m1, n0, n1);
                    const float a0 = ex2((m0 - n0) * SC), a1 = ex2((m1 - n1) * SC);
                    ls[0] *= a0; ls[2] *= a1;
                    o[0][0] *= a0; o[0][1] *= a0; o[1][0] *= a0; o[1][1] *= a0;
                    o[0][2] *= a1; o[0][3] *= a1; o[1][2] *= a1; o[1][3] *= a1;
                    m0 = n0; m1 = n1;
                }
                {
                    const float mc0 = m0 * SC, mc1 = m1 * SC;
                    const bool more = hh + 1 < NHEADS;
                    if (more) {
                        ATT_KWAIT(kbase);
                        ATT_NEXTQ(hh + 1);
#pragma unroll
                        for (int t = 0; t < 8; t++) { qk(sa, 0, t, kbase); expv(sb2, 1, t, mc0, mc1, vbase); }
                        rowmax(sa, NEG, NEG, m0, m1);
                    } else {
#pragma unroll
                        for (int t = 0; t < 8; t++) expv(sb2, 1, t, mc0, mc1, vbase);
                    }
                    ATT_VREL();
                }
                const float f0 = __fdividef(g0, ls[0]), f1 = __fdividef(g1, ls[2]);
                ATT_STORE(hh, pack_bf16(o[0][0] * f0, o[0][1] * f0), pack_bf16(o[0][2] * f1, o[0][3] * f1),
                              pack_bf16(o[1][0] * f0, o[1][1] * f0), pack_bf16(o[1][2] * f1, o[1][3] * f1));
            }
            };
            if (ti >= 2) attention(BoolTag<false>{}); else attention(BoolTag<true>{});
            fence_async_smem();
            __syncwarp();
            if (lane0) { mbar_arrive(sb + B_ODONE); red_release(&g_ocnt[blockIdx.x * 32], 1u); }
        }
        TS(7);
        {
            float acc[32];
            uint4 pv[4][4];
            if (!dry) mbar_wait(sb + B_PREADY, 0);
            {
                const uint4* p = g_part + (size_t)((ti * 8 + tj) * 8 + 4) * 1024 + warp * 128 + lane;
#pragma unroll
                for (int s = 0; s < 4; s++)
#pragma unroll
                    for (int n = 0; n < 4; n++) pv[n][s] = dry ? make_uint4(0u, 0u, 0u, 0u) : ldg_weak(p + s * 1024 + n * 32);
            }
            if (!dry) mbar_wait(sb + B_WOFULL, 0);
            if (!dry) mbar_wait(sb + B_ODONE, 0);
            TS(15);
            wgmma_fence();
#pragma unroll
            for (int k = 0; k < 4; k++) wgmma_ss_n64(acc, desc_a(sb + OWN_OFF + wg * 8192 + 32 * k), desc_b(sb + X_OFF + tj * 8192 + 2048 * k), k);
            wgmma_commit();
            float base[32];
            if (!dry) mbar_wait(sb + B_HSUM, 0);
#pragma unroll
            for (int n = 0; n < 4; n++) {
                const uint4 u0 = lds128(sb + STG_OFF + (warp * 8 + 2 * n) * 512 + lane * 16), u1 = lds128(sb + STG_OFF + (warp * 8 + 2 * n + 1) * 512 + lane * 16);
                float* a = &base[8 * n];
                a[0] = __uint_as_float(u0.x); a[1] = __uint_as_float(u0.y); a[2] = __uint_as_float(u0.z); a[3] = __uint_as_float(u0.w);
                a[4] = __uint_as_float(u1.x); a[5] = __uint_as_float(u1.y); a[6] = __uint_as_float(u1.z); a[7] = __uint_as_float(u1.w);
#pragma unroll
                for (int s = 0; s < 4; s++) {
                    a[0] += bf_lo(pv[n][s].x); a[1] += bf_hi(pv[n][s].x); a[2] += bf_lo(pv[n][s].y); a[3] += bf_hi(pv[n][s].y);
                    a[4] += bf_lo(pv[n][s].z); a[5] += bf_hi(pv[n][s].z); a[6] += bf_lo(pv[n][s].w); a[7] += bf_hi(pv[n][s].w);
                }
            }
            fence_acc(base);
            TS(16);
#pragma unroll 1
            for (int m = 0; m < N_O; m++) {
                CWAIT();
                uint32_t js; asm volatile("ld.shared.u32 %0, [%1];" : "=r"(js) : "r"(sb + OSRC_OFF + 4 * m) : "memory");
                const uint32_t as = sb + RING_OFF + r.slot * SLOT + wg * 8192;
                const uint32_t bs = sb + X_OFF + (js & 7) * 8192;
                wgmma_fence();
#pragma unroll
                for (int k = 0; k < 4; k++) wgmma_ss_n64(acc, desc_a(as + 32 * k), desc_b(bs + 2048 * k), 1);
                wgmma_commit();
                if (m == 0) { wgmma_wait<0>(); if (lane0) mbar_arrive(sb + B_EMPTY + 8 * r.slot); }
                r.next();
            }
            wgmma_wait<0>();
            fence_acc(acc);
            TS(17);
#pragma unroll
            for (int k = 0; k < 32; k++) acc[k] += base[k];
            __nv_bfloat16* o = out + (size_t)(ti * 128 + warp * 16 + g) * 512 + tj * 64 + ((lane & 1) ? 8 : 0) + (lane & 2) * 2;
            const bool odd = lane & 1;
#pragma unroll
            for (int t2 = 0; t2 < 4; t2++) {
                const uint32_t lo0 = pack_bf16(acc[8 * t2 + 0], acc[8 * t2 + 1]), hi0 = pack_bf16(acc[8 * t2 + 2], acc[8 * t2 + 3]);
                const uint32_t lo1 = pack_bf16(acc[8 * t2 + 4], acc[8 * t2 + 5]), hi1 = pack_bf16(acc[8 * t2 + 6], acc[8 * t2 + 7]);
                const uint32_t sl = __shfl_xor_sync(0xffffffffu, odd ? lo0 : lo1, 1), sh = __shfl_xor_sync(0xffffffffu, odd ? hi0 : hi1, 1);
                if (!dry) *reinterpret_cast<uint2*>(o + 16 * t2) = odd ? make_uint2(sl, lo1) : make_uint2(lo0, sl);
                if (!dry) *reinterpret_cast<uint2*>(o + 16 * t2 + 8 * 512) = odd ? make_uint2(sh, hi1) : make_uint2(hi0, sh);
            }
            if (tid == 0 && !dry) TSG(30);
        }
        TS(8);
    }
}

typedef CUresult (*PFN_encodeTiled)(CUtensorMap*, CUtensorMapDataType, cuuint32_t, void*, const cuuint64_t*, const cuuint64_t*,
                                    const cuuint32_t*, const cuuint32_t*, CUtensorMapInterleave, CUtensorMapSwizzle,
                                    CUtensorMapL2promotion, CUtensorMapFloatOOBfill);

void make_map(PFN_encodeTiled enc, CUtensorMap* m, const void* base, int rank, const cuuint64_t* dims, const cuuint64_t* strides, const cuuint32_t* box) {
    cuuint32_t es[5] = {1, 1, 1, 1, 1};
    enc(m, CU_TENSOR_MAP_DATA_TYPE_BFLOAT16, (cuuint32_t)rank, const_cast<void*>(base), dims, strides, box, es,
        CU_TENSOR_MAP_INTERLEAVE_NONE, CU_TENSOR_MAP_SWIZZLE_128B, CU_TENSOR_MAP_L2_PROMOTION_L2_256B, CU_TENSOR_MAP_FLOAT_OOB_FILL_NONE);
}

}

extern "C" void kernel_launch(void* const* d_in, const int* in_sizes, int n_in, void* d_out, int out_size) {
    (void)in_sizes; (void)n_in; (void)out_size;
    const void* x = d_in[0]; const void* wqkv = d_in[1]; const void* wo = d_in[2];
    const void* w1 = d_in[4]; const void* w2 = d_in[5]; const void* gate_w = d_in[6];
    static PFN_encodeTiled enc = nullptr;
    if (!enc) {
        void* fn = nullptr; cudaDriverEntryPointQueryResult st;
        cudaGetDriverEntryPoint("cuTensorMapEncodeTiled", &fn, cudaEnableDefault, &st);
        enc = (PFN_encodeTiled)fn;
        cudaFuncSetAttribute(fused_kernel, cudaFuncAttributeMaxDynamicSharedMemorySize, SMEM_BYTES);
    }
    CUtensorMap mx, mqkv, mw1, mw2, mwo, mw1a, mo;
    void* optr = nullptr;
    cudaGetSymbolAddress(&optr, g_o);
    { cuuint64_t d[2] = {512, 2048}, s[1] = {1024}; cuuint32_t b[2] = {64, 128}; make_map(enc, &mo, optr, 2, d, s, b); }
    { cuuint64_t d[4] = {64, 512, 3, 8}, s[3] = {3584, 128, 448}; cuuint32_t b[4] = {64, 32, 3, 1}; make_map(enc, &mw1a, w1, 4, d, s, b); }
    { cuuint64_t d[2] = {512, 2048}, s[1] = {1024}; cuuint32_t b[2] = {64, 128}; make_map(enc, &mx, x, 2, d, s, b); }
    { cuuint64_t d[4] = {64, 512, 8, 3}, s[3] = {3072, 128, 1024}; cuuint32_t b[4] = {64, 32, 1, 3}; make_map(enc, &mqkv, wqkv, 4, d, s, b); }
    { cuuint64_t d[2] = {1792, 512}, s[1] = {3584}; cuuint32_t b[2] = {64, 32}; make_map(enc, &mw1, w1, 2, d, s, b); }
    { cuuint64_t d[3] = {64, 1792, 8}, s[2] = {1024, 128}; cuuint32_t b[3] = {64, 32, 2}; make_map(enc, &mw2, w2, 3, d, s, b); }
    { cuuint64_t d[2] = {512, 512}, s[1] = {1024}; cuuint32_t b[2] = {64, 256}; make_map(enc, &mwo, wo, 2, d, s, b); }
    fused_kernel<<<NCTA, 384, SMEM_BYTES, cudaStreamPerThread>>>(mx, mqkv, mw1, mw2, mwo, mw1a, mo, (const __nv_bfloat16*)gate_w, (__nv_bfloat16*)d_out,
                                           (const uint8_t*)w1, (const uint8_t*)w2, (const uint8_t*)wo);
}
```

```cpp
#include <cuda_runtime.h>
#include <cuda_bf16.h>
#include <cuda.h>
#include <stdint.h>

namespace {

#define PF1_AT 1
#define PF2_AT 5
#define LEAD1 2
#define NCTA 132
constexpr int RING = 6;
constexpr int SLOT = 16384;
constexpr uint32_t X_OFF = 0;
constexpr uint32_t STG_OFF = X_OFF + 4 * 16384;
constexpr uint32_t RING_OFF = 131072;
constexpr uint32_t BAR_OFF = RING_OFF + RING * SLOT;
constexpr uint32_t B_FULL = BAR_OFF, B_EMPTY = BAR_OFF + 64, B_XFULL = BAR_OFF + 128, B_HDEAD = BAR_OFF + 192,
                   B_EREADY = BAR_OFF + 200, B_KVDONE = BAR_OFF + 208, B_ODONE = BAR_OFF + 224,
                   B_KVREADY = BAR_OFF + 232, B_WOFULL = BAR_OFF + 240, B_HSUM = BAR_OFF + 248, B_PREADY = BAR_OFF + 264,
                   B_SQ = BAR_OFF + 272, B_SF = BAR_OFF + 304;
constexpr uint32_t EPOCH_OFF = BAR_OFF + 256, ITEM_OFF = BAR_OFF + 260, OSRC_OFF = BAR_OFF + 384;
constexpr uint32_t OWN_OFF = X_OFF + 6 * 16384;
constexpr uint32_t SMEM_BYTES = BAR_OFF + 1024;

constexpr int N_QKV = 16, N_FFN1 = 16, N_FFN2 = 14, N_KV = 8, N_O = 7;

__device__ uint4 g_kf[32 * 128 * 32];
__device__ uint4 g_vf[32 * 128 * 32];
__device__ uint4 g_part[16 * 8 * 8 * 8 * 4 * 32];
__device__ __nv_bfloat16 g_o[2048 * 512];
__device__ unsigned g_ticket;
__device__ unsigned g_kvcnt[128 * 32];
__device__ unsigned g_pcnt[128 * 32];
__device__ unsigned g_ocnt[128 * 32];
#define TS(k) do {} while (0)
#define TS2(k) do {} while (0)
#define TS2X(k) do {} while (0)
#define TSX(k) do {} while (0)
#define TSG(k) do {} while (0)

__device__ __forceinline__ uint32_t smem_u32(const void* p) { return (uint32_t)__cvta_generic_to_shared(p); }
__device__ __forceinline__ void mbar_init(uint32_t bar, uint32_t cnt) { asm volatile("mbarrier.init.shared::cta.b64 [%0], %1;" :: "r"(bar), "r"(cnt) : "memory"); }
__device__ __forceinline__ void mbar_expect_tx(uint32_t bar, uint32_t bytes) { asm volatile("mbarrier.arrive.expect_tx.shared::cta.b64 _, [%0], %1;" :: "r"(bar), "r"(bytes) : "memory"); }
__device__ __forceinline__ void mbar_expect_only(uint32_t bar, uint32_t bytes) { asm volatile("mbarrier.expect_tx.relaxed.cta.shared::cta.b64 [%0], %1;" :: "r"(bar), "r"(bytes) : "memory"); }
__device__ __forceinline__ void mbar_arrive(uint32_t bar) { asm volatile("mbarrier.arrive.shared::cta.b64 _, [%0];" :: "r"(bar) : "memory"); }
__device__ __forceinline__ void mbar_wait(uint32_t bar, uint32_t parity) {
    asm volatile("{\n.reg .pred P1, P2;\n.reg .u32 n;\nmov.u32 n, 0;\n"
                 "WAIT_LOOP:\n"
                 "mbarrier.try_wait.parity.shared::cta.b64 P1, [%0], %1;\n"
                 "@P1 bra WAIT_DONE;\n"
                 "add.u32 n, n, 1;\n"
                 "setp.lt.u32 P2, n, 0x400000;\n"
                 "@P2 bra WAIT_LOOP;\n"
                 "WAIT_DONE:\n}" :: "r"(bar), "r"(parity) : "memory");
}
__device__ __forceinline__ void tma_2d(uint32_t dst, const void* map, uint32_t bar, int c0, int c1) {
    asm volatile("cp.async.bulk.tensor.2d.shared::cluster.global.mbarrier::complete_tx::bytes [%0], [%1, {%3, %4}], [%2];"
        :: "r"(dst), "l"(map), "r"(bar), "r"(c0), "r"(c1) : "memory");
}
__device__ __forceinline__ void tma_3d(uint32_t dst, const void* map, uint32_t bar, int c0, int c1, int c2) {
    asm volatile("cp.async.bulk.tensor.3d.shared::cluster.global.mbarrier::complete_tx::bytes [%0], [%1, {%3, %4, %5}], [%2];"
        :: "r"(dst), "l"(map), "r"(bar), "r"(c0), "r"(c1), "r"(c2) : "memory");
}
__device__ __forceinline__ void tma_4d(uint32_t dst, const void* map, uint32_t bar, int c0, int c1, int c2, int c3) {
    asm volatile("cp.async.bulk.tensor.4d.shared::cluster.global.mbarrier::complete_tx::bytes [%0], [%1, {%3, %4, %5, %6}], [%2];"
        :: "r"(dst), "l"(map), "r"(bar), "r"(c0), "r"(c1), "r"(c2), "r"(c3) : "memory");
}
__device__ __forceinline__ void bulk_g2s(uint32_t dst, const void* src, uint32_t bytes, uint32_t bar) {
    asm volatile("cp.async.bulk.shared::cluster.global.mbarrier::complete_tx::bytes [%0], [%1], %2, [%3];"
        :: "r"(dst), "l"(src), "r"(bytes), "r"(bar) : "memory");
}
__device__ __forceinline__ void prefetch_l2(const void* src, uint32_t bytes) {
    asm volatile("cp.async.bulk.prefetch.L2.global [%0], %1;" :: "l"(src), "r"(bytes) : "memory");
}
__device__ __forceinline__ bool elect_one() {
    uint32_t p;
    asm volatile("{\n.reg .pred P;\nelect.sync _|P, 0xffffffff;\nselp.u32 %0, 1, 0, P;\n}" : "=r"(p));
    return p != 0;
}
__device__ __forceinline__ void wgmma_fence() { asm volatile("wgmma.fence.sync.aligned;" ::: "memory"); }
__device__ __forceinline__ void wgmma_commit() { asm volatile("wgmma.commit_group.sync.aligned;" ::: "memory"); }
template <int N> __device__ __forceinline__ void wgmma_wait() { asm volatile("wgmma.wait_group.sync.aligned %0;" :: "n"(N) : "memory"); }
__device__ __forceinline__ void fence_async_smem() { asm volatile("fence.proxy.async.shared::cta;" ::: "memory"); }
__device__ __forceinline__ uint64_t desc_a(uint32_t addr) {
    return (uint64_t)((addr & 0x3FFFF) >> 4) | ((uint64_t)1 << 16) | ((uint64_t)(1024 >> 4) << 32) | ((uint64_t)1 << 62);
}
__device__ __forceinline__ uint64_t desc_b(uint32_t addr) {
    return (uint64_t)((addr & 0x3FFFF) >> 4) | ((uint64_t)(4096 >> 4) << 16) | ((uint64_t)(1024 >> 4) << 32) | ((uint64_t)1 << 62);
}
__device__ __forceinline__ uint32_t pack_bf16(float lo, float hi) {
    uint32_t r; asm("cvt.rn.bf16x2.f32 %0, %1, %2;" : "=r"(r) : "f"(hi), "f"(lo)); return r;
}
__device__ __forceinline__ uint32_t pack_bf16_relu(float lo, float hi) {
    uint32_t r; asm("cvt.rn.relu.bf16x2.f32 %0, %1, %2;" : "=r"(r) : "f"(hi), "f"(lo)); return r;
}
__device__ __forceinline__ uint32_t movmatrix(uint32_t a) {
    uint32_t d; asm volatile("movmatrix.sync.aligned.m8n8.trans.b16 %0, %1;" : "=r"(d) : "r"(a)); return d;
}
__device__ __forceinline__ void stmatrix_x4(uint32_t addr, uint32_t r0, uint32_t r1, uint32_t r2, uint32_t r3) {
    asm volatile("stmatrix.sync.aligned.m8n8.x4.shared.b16 [%0], {%1, %2, %3, %4};" :: "r"(addr), "r"(r0), "r"(r1), "r"(r2), "r"(r3) : "memory");
}
__device__ __forceinline__ uint4 lds128(uint32_t addr) {
    uint4 v; asm volatile("ld.shared.v4.b32 {%0, %1, %2, %3}, [%4];" : "=r"(v.x), "=r"(v.y), "=r"(v.z), "=r"(v.w) : "r"(addr) : "memory"); return v;
}
__device__ __forceinline__ void mma16816(float (&c)[4], uint32_t a0, uint32_t a1, uint32_t a2, uint32_t a3, uint32_t b0, uint32_t b1) {
    asm volatile("mma.sync.aligned.m16n8k16.row.col.f32.bf16.bf16.f32 {%0,%1,%2,%3}, {%4,%5,%6,%7}, {%8,%9}, {%0,%1,%2,%3};"
        : "+f"(c[0]), "+f"(c[1]), "+f"(c[2]), "+f"(c[3]) : "r"(a0), "r"(a1), "r"(a2), "r"(a3), "r"(b0), "r"(b1));
}
__device__ __forceinline__ void mma16816_c(float (&c)[4], uint32_t a0, uint32_t a1, uint32_t a2, uint32_t a3, uint32_t b0, uint32_t b1, float ci) {
    asm volatile("mma.sync.aligned.m16n8k16.row.col.f32.bf16.bf16.f32 {%0,%1,%2,%3}, {%4,%5,%6,%7}, {%8,%9}, {%10,%10,%10,%10};"
        : "=f"(c[0]), "=f"(c[1]), "=f"(c[2]), "=f"(c[3]) : "r"(a0), "r"(a1), "r"(a2), "r"(a3), "r"(b0), "r"(b1), "f"(ci));
}
__device__ __forceinline__ int opaque(int v) { asm volatile("" : "+r"(v)); return v; }
__device__ __forceinline__ float ex2(float x) { float y; asm("ex2.approx.ftz.f32 %0, %1;" : "=f"(y) : "f"(x)); return y; }
__device__ __forceinline__ unsigned ld_acquire(const unsigned* p) {
    unsigned v; asm volatile("ld.acquire.gpu.global.u32 %0, [%1];" : "=r"(v) : "l"(p) : "memory"); return v;
}
__device__ __forceinline__ void red_release(unsigned* p, unsigned v) {
    asm volatile("red.release.gpu.global.add.u32 [%0], %1;" :: "l"(p), "r"(v) : "memory");
}
__device__ __forceinline__ void wait_counter(const unsigned* p, unsigned target) {
    uint32_t n = 0;
    while ((int)(ld_acquire(p) - target) < 0) { if (++n > (1u << 20)) break; }
}
__device__ __forceinline__ uint4 ldg_weak(const uint4* p) {
    uint4 v; asm volatile("ld.global.L1::no_allocate.v4.b32 {%0, %1, %2, %3}, [%4];" : "=r"(v.x), "=r"(v.y), "=r"(v.z), "=r"(v.w) : "l"(p) : "memory"); return v;
}
__device__ __forceinline__ float bf_lo(uint32_t v) { return __uint_as_float(v << 16); }
__device__ __forceinline__ float bf_hi(uint32_t v) { return __uint_as_float(v & 0xFFFF0000u); }

__device__ __forceinline__ void wgmma_ss_n64(float (&d)[32], uint64_t da, uint64_t db, int scale_d) {
    asm volatile("{\n.reg .pred p;\nsetp.ne.b32 p, %34, 0;\n"
        "wgmma.mma_async.sync.aligned.m64n64k16.f32.bf16.bf16 {%0, %1, %2, %3, %4, %5, %6, %7, %8, %9, %10, %11, %12, %13, %14, %15, %16, %17, %18, %19, %20, %21, %22, %23, %24, %25, %26, %27, %28, %29, %30, %31}, %32, %33, p, 1, 1, 0, 1;\n}\n"
        : "+f"(d[0]), "+f"(d[1]), "+f"(d[2]), "+f"(d[3]), "+f"(d[4]), "+f"(d[5]), "+f"(d[6]), "+f"(d[7]), "+f"(d[8]), "+f"(d[9]), "+f"(d[10]), "+f"(d[11]), "+f"(d[12]), "+f"(d[13]), "+f"(d[14]), "+f"(d[15]), "+f"(d[16]), "+f"(d[17]), "+f"(d[18]), "+f"(d[19]), "+f"(d[20]), "+f"(d[21]), "+f"(d[22]), "+f"(d[23]), "+f"(d[24]), "+f"(d[25]), "+f"(d[26]), "+f"(d[27]), "+f"(d[28]), "+f"(d[29]), "+f"(d[30]), "+f"(d[31])
        : "l"(da), "l"(db), "r"(scale_d));
}
__device__ __forceinline__ void wgmma_ss_n128(float (&d)[64], uint64_t da, uint64_t db, int scale_d) {
    asm volatile("{\n.reg .pred p;\nsetp.ne.b32 p, %66, 0;\n"
        "wgmma.mma_async.sync.aligned.m64n128k16.f32.bf16.bf16 {%0, %1, %2, %3, %4, %5, %6, %7, %8, %9, %10, %11, %12, %13, %14, %15, %16, %17, %18, %19, %20, %21, %22, %23, %24, %25, %26, %27, %28, %29, %30, %31, %32, %33, %34, %35, %36, %37, %38, %39, %40, %41, %42, %43, %44, %45, %46, %47, %48, %49, %50, %51, %52, %53, %54, %55, %56, %57, %58, %59, %60, %61, %62, %63}, %64, %65, p, 1, 1, 0, 1;\n}\n"
        : "+f"(d[0]), "+f"(d[1]), "+f"(d[2]), "+f"(d[3]), "+f"(d[4]), "+f"(d[5]), "+f"(d[6]), "+f"(d[7]), "+f"(d[8]), "+f"(d[9]), "+f"(d[10]), "+f"(d[11]), "+f"(d[12]), "+f"(d[13]), "+f"(d[14]), "+f"(d[15]), "+f"(d[16]), "+f"(d[17]), "+f"(d[18]), "+f"(d[19]), "+f"(d[20]), "+f"(d[21]), "+f"(d[22]), "+f"(d[23]), "+f"(d[24]), "+f"(d[25]), "+f"(d[26]), "+f"(d[27]), "+f"(d[28]), "+f"(d[29]), "+f"(d[30]), "+f"(d[31]), "+f"(d[32]), "+f"(d[33]), "+f"(d[34]), "+f"(d[35]), "+f"(d[36]), "+f"(d[37]), "+f"(d[38]), "+f"(d[39]), "+f"(d[40]), "+f"(d[41]), "+f"(d[42]), "+f"(d[43]), "+f"(d[44]), "+f"(d[45]), "+f"(d[46]), "+f"(d[47]), "+f"(d[48]), "+f"(d[49]), "+f"(d[50]), "+f"(d[51]), "+f"(d[52]), "+f"(d[53]), "+f"(d[54]), "+f"(d[55]), "+f"(d[56]), "+f"(d[57]), "+f"(d[58]), "+f"(d[59]), "+f"(d[60]), "+f"(d[61]), "+f"(d[62]), "+f"(d[63])
        : "l"(da), "l"(db), "r"(scale_d));
}
__device__ __forceinline__ void wgmma_ss_n200(float (&d)[100], uint64_t da, uint64_t db, int scale_d) {
    asm volatile("{\n.reg .pred p;\nsetp.ne.b32 p, %102, 0;\n"
        "wgmma.mma_async.sync.aligned.m64n200k16.f32.bf16.bf16 {%0, %1, %2, %3, %4, %5, %6, %7, %8, %9, %10, %11, %12, %13, %14, %15, %16, %17, %18, %19, %20, %21, %22, %23, %24, %25, %26, %27, %28, %29, %30, %31, %32, %33, %34, %35, %36, %37, %38, %39, %40, %41, %42, %43, %44, %45, %46, %47, %48, %49, %50, %51, %52, %53, %54, %55, %56, %57, %58, %59, %60, %61, %62, %63, %64, %65, %66, %67, %68, %69, %70, %71, %72, %73, %74, %75, %76, %77, %78, %79, %80, %81, %82, %83, %84, %85, %86, %87, %88, %89, %90, %91, %92, %93, %94, %95, %96, %97, %98, %99}, %100, %101, p, 1, 1, 0, 1;\n}\n"
        : "+f"(d[0]), "+f"(d[1]), "+f"(d[2]), "+f"(d[3]), "+f"(d[4]), "+f"(d[5]), "+f"(d[6]), "+f"(d[7]), "+f"(d[8]), "+f"(d[9]), "+f"(d[10]), "+f"(d[11]), "+f"(d[12]), "+f"(d[13]), "+f"(d[14]), "+f"(d[15]), "+f"(d[16]), "+f"(d[17]), "+f"(d[18]), "+f"(d[19]), "+f"(d[20]), "+f"(d[21]), "+f"(d[22]), "+f"(d[23]), "+f"(d[24]), "+f"(d[25]), "+f"(d[26]), "+f"(d[27]), "+f"(d[28]), "+f"(d[29]), "+f"(d[30]), "+f"(d[31]), "+f"(d[32]), "+f"(d[33]), "+f"(d[34]), "+f"(d[35]), "+f"(d[36]), "+f"(d[37]), "+f"(d[38]), "+f"(d[39]), "+f"(d[40]), "+f"(d[41]), "+f"(d[42]), "+f"(d[43]), "+f"(d[44]), "+f"(d[45]), "+f"(d[46]), "+f"(d[47]), "+f"(d[48]), "+f"(d[49]), "+f"(d[50]), "+f"(d[51]), "+f"(d[52]), "+f"(d[53]), "+f"(d[54]), "+f"(d[55]), "+f"(d[56]), "+f"(d[57]), "+f"(d[58]), "+f"(d[59]), "+f"(d[60]), "+f"(d[61]), "+f"(d[62]), "+f"(d[63]), "+f"(d[64]), "+f"(d[65]), "+f"(d[66]), "+f"(d[67]), "+f"(d[68]), "+f"(d[69]), "+f"(d[70]), "+f"(d[71]), "+f"(d[72]), "+f"(d[73]), "+f"(d[74]), "+f"(d[75]), "+f"(d[76]), "+f"(d[77]), "+f"(d[78]), "+f"(d[79]), "+f"(d[80]), "+f"(d[81]), "+f"(d[82]), "+f"(d[83]), "+f"(d[84]), "+f"(d[85]), "+f"(d[86]), "+f"(d[87]), "+f"(d[88]), "+f"(d[89]), "+f"(d[90]), "+f"(d[91]), "+f"(d[92]), "+f"(d[93]), "+f"(d[94]), "+f"(d[95]), "+f"(d[96]), "+f"(d[97]), "+f"(d[98]), "+f"(d[99])
        : "l"(da), "l"(db), "r"(scale_d));
}
__device__ __forceinline__ void wgmma_ss_n224(float (&d)[112], uint64_t da, uint64_t db, int scale_d) {
    asm volatile("{\n.reg .pred p;\nsetp.ne.b32 p, %114, 0;\n"
        "wgmma.mma_async.sync.aligned.m64n224k16.f32.bf16.bf16 {%0, %1, %2, %3, %4, %5, %6, %7, %8, %9, %10, %11, %12, %13, %14, %15, %16, %17, %18, %19, %20, %21, %22, %23, %24, %25, %26, %27, %28, %29, %30, %31, %32, %33, %34, %35, %36, %37, %38, %39, %40, %41, %42, %43, %44, %45, %46, %47, %48, %49, %50, %51, %52, %53, %54, %55, %56, %57, %58, %59, %60, %61, %62, %63, %64, %65, %66, %67, %68, %69, %70, %71, %72, %73, %74, %75, %76, %77, %78, %79, %80, %81, %82, %83, %84, %85, %86, %87, %88, %89, %90, %91, %92, %93, %94, %95, %96, %97, %98, %99, %100, %101, %102, %103, %104, %105, %106, %107, %108, %109, %110, %111}, %112, %113, p, 1, 1, 0, 1;\n}\n"
        : "+f"(d[0]), "+f"(d[1]), "+f"(d[2]), "+f"(d[3]), "+f"(d[4]), "+f"(d[5]), "+f"(d[6]), "+f"(d[7]), "+f"(d[8]), "+f"(d[9]), "+f"(d[10]), "+f"(d[11]), "+f"(d[12]), "+f"(d[13]), "+f"(d[14]), "+f"(d[15]), "+f"(d[16]), "+f"(d[17]), "+f"(d[18]), "+f"(d[19]), "+f"(d[20]), "+f"(d[21]), "+f"(d[22]), "+f"(d[23]), "+f"(d[24]), "+f"(d[25]), "+f"(d[26]), "+f"(d[27]), "+f"(d[28]), "+f"(d[29]), "+f"(d[30]), "+f"(d[31]), "+f"(d[32]), "+f"(d[33]), "+f"(d[34]), "+f"(d[35]), "+f"(d[36]), "+f"(d[37]), "+f"(d[38]), "+f"(d[39]), "+f"(d[40]), "+f"(d[41]), "+f"(d[42]), "+f"(d[43]), "+f"(d[44]), "+f"(d[45]), "+f"(d[46]), "+f"(d[47]), "+f"(d[48]), "+f"(d[49]), "+f"(d[50]), "+f"(d[51]), "+f"(d[52]), "+f"(d[53]), "+f"(d[54]), "+f"(d[55]), "+f"(d[56]), "+f"(d[57]), "+f"(d[58]), "+f"(d[59]), "+f"(d[60]), "+f"(d[61]), "+f"(d[62]), "+f"(d[63]), "+f"(d[64]), "+f"(d[65]), "+f"(d[66]), "+f"(d[67]), "+f"(d[68]), "+f"(d[69]), "+f"(d[70]), "+f"(d[71]), "+f"(d[72]), "+f"(d[73]), "+f"(d[74]), "+f"(d[75]), "+f"(d[76]), "+f"(d[77]), "+f"(d[78]), "+f"(d[79]), "+f"(d[80]), "+f"(d[81]), "+f"(d[82]), "+f"(d[83]), "+f"(d[84]), "+f"(d[85]), "+f"(d[86]), "+f"(d[87]), "+f"(d[88]), "+f"(d[89]), "+f"(d[90]), "+f"(d[91]), "+f"(d[92]), "+f"(d[93]), "+f"(d[94]), "+f"(d[95]), "+f"(d[96]), "+f"(d[97]), "+f"(d[98]), "+f"(d[99]), "+f"(d[100]), "+f"(d[101]), "+f"(d[102]), "+f"(d[103]), "+f"(d[104]), "+f"(d[105]), "+f"(d[106]), "+f"(d[107]), "+f"(d[108]), "+f"(d[109]), "+f"(d[110]), "+f"(d[111])
        : "l"(da), "l"(db), "r"(scale_d));
}
template <int N> __device__ __forceinline__ void fence_acc(float (&d)[N]) {
#pragma unroll
    for (int i = 0; i < N; i++) asm volatile("" : "+f"(d[i]) :: "memory");
}

__device__ __forceinline__ void bulk_s2g(void* dst, uint32_t src, uint32_t bytes) {
    asm volatile("cp.async.bulk.global.shared::cta.bulk_group [%0], [%1], %2;" :: "l"(dst), "r"(src), "r"(bytes) : "memory");
}
__device__ __forceinline__ void sts128(uint32_t addr, uint4 v) {
    asm volatile("st.shared.v4.b32 [%0], {%1, %2, %3, %4};" :: "r"(addr), "r"(v.x), "r"(v.y), "r"(v.z), "r"(v.w) : "memory");
}
__device__ __forceinline__ void sum_partials(uint32_t sb, int ti, int tj, int lane) {
    for (;;) {
        uint32_t item = 0;
        if (lane == 0) asm volatile("atom.shared.add.u32 %0, [%1], 1;" : "=r"(item) : "r"(sb + ITEM_OFF) : "memory");
        item = __shfl_sync(0xffffffffu, item, 0);
        if (item >= 8) break;
        const uint4* p = g_part + (size_t)((ti * 8 + tj) * 8) * 1024 + item * 128 + lane;
        uint4 v[4][4];
#pragma unroll
        for (int s = 0; s < 4; s++)
#pragma unroll
            for (int n = 0; n < 4; n++) v[n][s] = ldg_weak(p + s * 1024 + n * 32);
#pragma unroll
        for (int n = 0; n < 4; n++) {
            float a[8];
#pragma unroll
            for (int e = 0; e < 8; e++) a[e] = 0.f;
#pragma unroll
            for (int s = 0; s < 4; s++) {
                a[0] += bf_lo(v[n][s].x); a[1] += bf_hi(v[n][s].x); a[2] += bf_lo(v[n][s].y); a[3] += bf_hi(v[n][s].y);
                a[4] += bf_lo(v[n][s].z); a[5] += bf_hi(v[n][s].z); a[6] += bf_lo(v[n][s].w); a[7] += bf_hi(v[n][s].w);
            }
            const uint32_t d = sb + STG_OFF + (item * 8 + n * 2) * 512 + lane * 16;
            sts128(d, make_uint4(__float_as_uint(a[0]), __float_as_uint(a[1]), __float_as_uint(a[2]), __float_as_uint(a[3])));
            sts128(d + 512, make_uint4(__float_as_uint(a[4]), __float_as_uint(a[5]), __float_as_uint(a[6]), __float_as_uint(a[7])));
        }
    }
    __syncwarp();
    if (lane == 0) mbar_arrive(sb + B_HSUM);
}

#define PWAIT() mbar_wait(sb + B_EMPTY + 8 * r.slot, r.phase)
#define CWAIT() do { if (!dry) mbar_wait(sb + B_FULL + 8 * r.slot, r.phase); } while (0)
template <bool B> struct BoolTag { static constexpr bool value = B; };
struct Ring {
    int slot; uint32_t phase;
    __device__ __forceinline__ void next() { if (++slot == RING) { slot = 0; phase ^= 1; } }
};

__global__ void __launch_bounds__(384, 1)
fused_kernel(const __grid_constant__ CUtensorMap map_x, const __grid_constant__ CUtensorMap map_qkv,
             const __grid_constant__ CUtensorMap map_w1, const __grid_constant__ CUtensorMap map_w2,
             const __grid_constant__ CUtensorMap map_wo, const __grid_constant__ CUtensorMap map_w1a,
             const __grid_constant__ CUtensorMap map_o,
             const __nv_bfloat16* __restrict__ gate_w, __nv_bfloat16* __restrict__ out,
             const uint8_t* __restrict__ w1p, const uint8_t* __restrict__ w2p, const uint8_t* __restrict__ wop)
{
    extern __shared__ __align__(1024) uint8_t smem_raw[];
    const uint32_t sb = smem_u32(smem_raw);
    const int tid = threadIdx.x, warp = tid >> 5, lane = tid & 31;
    const bool dry = blockIdx.x >= 128;
    const int ti = dry ? (int)(blockIdx.x & 1) * 2 : blockIdx.x >> 3, tj = blockIdx.x & 7;
    if (dry && warp >= 8) {
        asm volatile("setmaxnreg.dec.sync.aligned.u32 88;");
        return;
    }

    if (tid == 0 && !dry) { TSG(31); TSX(0); }
    if (tid == 320) {
        asm volatile("prefetch.tensormap [%0];" :: "l"(&map_x) : "memory");
        asm volatile("prefetch.tensormap [%0];" :: "l"(&map_qkv) : "memory");
        asm volatile("prefetch.tensormap [%0];" :: "l"(&map_w1) : "memory");
        asm volatile("prefetch.tensormap [%0];" :: "l"(&map_w1a) : "memory");
        asm volatile("prefetch.tensormap [%0];" :: "l"(&map_w2) : "memory");
        asm volatile("prefetch.tensormap [%0];" :: "l"(&map_wo) : "memory");
        asm volatile("prefetch.tensormap [%0];" :: "l"(&map_o) : "memory");
    }
    if (tid == 256) {
        mbar_init(sb + B_FULL, 1); mbar_init(sb + B_XFULL, 1);
        fence_async_smem();
        mbar_expect_tx(sb + B_XFULL, 16384);
        tma_2d(sb + X_OFF, &map_x, sb + B_XFULL, 0, ti * 128);
        mbar_expect_only(sb + B_FULL, 12288);
        tma_4d(sb + RING_OFF, &map_qkv, sb + B_FULL, 0, 0, tj, 0);
    }
    uint32_t gwv[N_QKV / 2];
    if (warp == 8) {
        const unsigned short* gws = reinterpret_cast<const unsigned short*>(gate_w);
#pragma unroll
        for (int n = 0; n < N_QKV / 2; n++) gwv[n] = (uint32_t)__ldg(gws + 64 * n + lane) | ((uint32_t)__ldg(gws + 64 * n + 32 + lane) << 16);
    }
    if (tid == 288) {
        for (int s = 1; s < RING; s++) mbar_init(sb + B_FULL + 8 * s, 1);
        for (int s = 0; s < RING; s++) mbar_init(sb + B_EMPTY + 8 * s, 8);
        for (int s = 1; s < 8; s++) mbar_init(sb + B_XFULL + 8 * s, 1);
        fence_async_smem();
    }
    if (tid == 352) {
        mbar_init(sb + B_HDEAD, 8); mbar_init(sb + B_EREADY, 1); mbar_init(sb + B_KVDONE, 8); mbar_init(sb + B_KVREADY, 1);
        mbar_init(sb + B_ODONE, 8); mbar_init(sb + B_WOFULL, 1); mbar_init(sb + B_HSUM, 3);
        mbar_init(sb + B_PREADY, 1); mbar_init(sb + B_SF, 1); mbar_init(sb + B_SF + 8, 1);
        for (int s = 0; s < 4; s++) mbar_init(sb + B_SQ + 8 * s, 8);
        asm volatile("st.shared.u32 [%0], %1;" :: "r"(sb + ITEM_OFF), "r"(0) : "memory");
        fence_async_smem();
    }
    if (!dry) __syncthreads();

    if (warp >= 8) {
        asm volatile("setmaxnreg.dec.sync.aligned.u32 88;");
        if (warp == 8) {
            Ring r{0, 1};
            const bool leader = elect_one();
#pragma unroll
            for (int n = 0; n < N_QKV; n++) {
                const uint32_t full = sb + B_FULL + 8 * r.slot, dst = sb + RING_OFF + r.slot * SLOT;
                if (n > 0) {
                    if (!(n & 1) && leader) {
                        mbar_expect_tx(sb + B_XFULL + 8 * (n >> 1), 16384);
                        tma_2d(sb + X_OFF + (n >> 1) * 16384, &map_x, sb + B_XFULL + 8 * (n >> 1), (n >> 1) * 64, ti * 128);
                    }
                    if (n >= RING) PWAIT();
                    if (leader) {
                        mbar_expect_only(full, 12288);
                        tma_4d(dst, &map_qkv, full, 0, 32 * n, tj, 0);
                    }
                }
                const uint32_t gv = (n & 1) ? (gwv[n >> 1] >> 16) : (gwv[n >> 1] & 0xFFFFu);
                asm volatile("st.shared.v4.b32 [%0], {%1, %2, %2, %2};" :: "r"(dst + 12288 + lane * 128 + ((lane & 7) << 4)), "r"(gv), "r"(0) : "memory");
                fence_async_smem();
                __syncwarp();
                if (leader) mbar_arrive(full);
                r.next();
            }
#pragma unroll 1
            for (int n = 0; n < N_FFN1; n++) {
                const uint32_t full = sb + B_FULL + 8 * r.slot, dst = sb + RING_OFF + r.slot * SLOT;
                PWAIT();
                if (leader) {
                    mbar_expect_tx(full, 16384);
                    tma_4d(dst, &map_w1a, full, 0, 32 * n, 0, tj);
                    tma_2d(dst + 3 * 4096, &map_w1, full, 224 * tj + 192, 32 * n);
                }
                r.next();
            }
            {
                int q = 0, rr = 0;
#pragma unroll 1
                for (int n = 0; n < N_FFN2; n++) {
                    const uint32_t full = sb + B_FULL + 8 * r.slot, dst = sb + RING_OFF + r.slot * SLOT;
                    PWAIT();
                    if (leader) mbar_expect_tx(full, 16384);
#pragma unroll
                    for (int h = 0; h < 2; h++) {
                        if (leader) tma_3d(dst + h * 8192, &map_w2, full, 0, 224 * tj + 32 * rr, 2 * q);
                        if (++rr == 7) { rr = 0; q++; }
                    }
                    r.next();
                }
            }
            mbar_wait(sb + B_KVREADY, 0);
            asm volatile("fence.proxy.async.global;" ::: "memory");
            {
                const int bbase = 8 * ti - 16, b0 = bbase < 0 ? 0 : bbase;
                const uint32_t bytes = (uint32_t)(8 * ti + 8 - b0) * 512;
#pragma unroll 1
                for (int m = 0; m < N_KV; m++) {
                    const uint32_t full = sb + B_FULL + 8 * r.slot, dst = sb + RING_OFF + r.slot * SLOT;
                    if (m == RING) {
                        mbar_wait(sb + B_HDEAD, 0);
                        if (leader) {
                            mbar_expect_tx(sb + B_WOFULL, 65536);
#pragma unroll
                            for (int e = 0; e < 2; e++) tma_2d(sb + X_OFF + e * 32768, &map_wo, sb + B_WOFULL, 64 * tj, 256 * e);
                        }
                    }
                    PWAIT();
                    if (leader) {
                        const uint4* src = ((m & 1) ? g_vf : g_kf) + ((tj * 4 + (m >> 1)) * 128 + b0) * 32;
                        mbar_expect_tx(full, bytes);
                        bulk_g2s(dst + (b0 - bbase) * 512, src, bytes, full);
                    }
                    r.next();
                }
            }
            {
                mbar_wait(sb + B_EREADY, 0);
                unsigned epoch; asm volatile("ld.shared.u32 %0, [%1];" : "=r"(epoch) : "r"(sb + EPOCH_OFF) : "memory");
                uint32_t pending = 0xFFu & ~(1u << tj), ready = 0;
                mbar_wait(sb + B_HSUM, 0);
#pragma unroll 1
                for (int m = 0; m < N_O; m++) {
                    const uint32_t full = sb + B_FULL + 8 * r.slot, dst = sb + RING_OFF + r.slot * SLOT;
                    PWAIT();
                    for (int it = 0; it < (1 << 20) && !ready; it++) {
                        bool ok = false;
                        if (lane < 8 && ((pending >> lane) & 1)) ok = (int)(ld_acquire(&g_ocnt[(ti * 8 + lane) * 32]) - 8 * (epoch + 1)) >= 0;
                        ready = __ballot_sync(0xffffffffu, ok);
                        if (!ready) __nanosleep(100);
                    }
                    const int js = ready ? __ffs(ready) - 1 : __ffs(pending) - 1;
                    pending &= ~(1u << js); ready &= ~(1u << js);
                    asm volatile("fence.proxy.async.global;" ::: "memory");
                    if (leader) {
                        asm volatile("st.shared.u32 [%0], %1;" :: "r"(sb + OSRC_OFF + 4 * m), "r"(js) : "memory");
                        mbar_expect_tx(full, 16384);
                        tma_2d(dst, &map_o, full, 64 * js, ti * 128);
                    }
                    r.next();
                }
            }
        } else if (warp == 9) {
            unsigned epoch = 0;
            if (lane == 0) {
                epoch = atomicAdd(&g_ticket, 1u) >> 7;
                asm volatile("st.shared.u32 [%0], %1;" :: "r"(sb + EPOCH_OFF), "r"(epoch) : "memory");
                mbar_arrive(sb + B_EREADY);
                mbar_wait(sb + B_XFULL + 8 * PF1_AT, 0);
                prefetch_l2(w1p + (size_t)blockIdx.x * 14336, 14336);
                mbar_wait(sb + B_XFULL + 8 * PF2_AT, 0);
                prefetch_l2(w2p + (size_t)blockIdx.x * 14336, 14336);
                prefetch_l2(wop + (size_t)blockIdx.x * 4096, 4096);
                mbar_wait(sb + B_KVDONE, 0);
                red_release(&g_kvcnt[blockIdx.x * 32], 1u);
            }
            epoch = __shfl_sync(0xffffffffu, epoch, 0);
            if (lane < 3 && ti - lane >= 0) wait_counter(&g_kvcnt[((ti - lane) * 8 + tj) * 32], epoch + 1);
            __syncwarp();
            if (lane == 0) mbar_arrive(sb + B_KVREADY);
            mbar_wait(sb + B_SQ + 24, 0);
            if (lane < 8) wait_counter(&g_pcnt[(ti * 8 + lane) * 32], epoch + 1);
            __syncwarp();
            if (lane == 0) { mbar_arrive(sb + B_PREADY); TSX(13); }
            sum_partials(sb, ti, tj, lane);
            if (lane == 0) TSX(14);
        } else {
            if (warp == 10) {
#pragma unroll 1
                for (int q = 0; q < 4; q++) {
                    mbar_wait(sb + B_SQ + 8 * q, 0);
                    if (lane < 16) {
                        uint4* d = g_part + (size_t)(((ti * 8 + 2 * q + (lane & 1)) * 8 + tj) * 8 + (lane >> 1)) * 128;
                        bulk_s2g(d, sb + STG_OFF + (q & 1) * 32768 + lane * 2048, 2048);
                        asm volatile("cp.async.bulk.commit_group;" ::: "memory");
                        asm volatile("cp.async.bulk.wait_group.read 0;" ::: "memory");
                    }
                    __syncwarp();
                    if (lane == 0) mbar_arrive(sb + B_SF + 8 * (q & 1));
                }
                asm volatile("cp.async.bulk.wait_group 0;" ::: "memory");
                asm volatile("fence.proxy.async.global;" ::: "memory");
                __syncwarp();
                if (lane == 0) { red_release(&g_pcnt[blockIdx.x * 32], 1u); TSX(12); }
            }
            mbar_wait(sb + B_PREADY, 0);
            sum_partials(sb, ti, tj, lane);
        }
    } else {
        asm volatile("setmaxnreg.inc.sync.aligned.u32 208;");
        const int wg = warp >> 2, g = lane >> 2, c = lane & 3;
        const uint32_t xa = sb + X_OFF + wg * 8192;
        Ring r{0, 0};
        const bool lane0 = lane == 0 && !dry;
        uint32_t qf[4][4];
        float g0, g1;
        TS(9);
        {
            float acc[100];
            int prev = 0;
            if (wg == 1) asm volatile("bar.sync 3, 256;" ::: "memory");
            for (int s = 0; s < (dry ? 4 : N_QKV); s++) {
                if (!(s & 1) && !dry) mbar_wait(sb + B_XFULL + 8 * (s >> 1), 0);
                CWAIT();
                if (s == 0) TS(1);
                if (s == 2) TS(28);
                if (s == 6) TS(29);
                if (s == 10) TS(20);
                const uint32_t bs = sb + RING_OFF + r.slot * SLOT, as = xa + (s >> 1) * 16384 + (s & 1) * 64;
                wgmma_fence();
                wgmma_ss_n200(acc, desc_a(as), desc_b(bs), s);
                wgmma_ss_n200(acc, desc_a(as + 32), desc_b(bs + 2048), 1);
                wgmma_commit();
                if (wg == 0 && s == LEAD1) asm volatile("bar.arrive 3, 256;" ::: "memory");
                if (s > 0) { wgmma_wait<1>(); if (lane0) mbar_arrive(sb + B_EMPTY + 8 * prev); }
                prev = r.slot; r.next();
            }
            wgmma_wait<0>();
            fence_acc(acc);
            if (lane0) mbar_arrive(sb + B_EMPTY + 8 * prev);
            TS(2);
            const int blk = ti * 8 + warp;
#pragma unroll
            for (int hh = 0; hh < 4; hh++) {
                const float* t0 = &acc[8 * hh]; const float* t1 = &acc[8 * hh + 4];
                qf[hh][0] = pack_bf16(t0[0], t0[1]); qf[hh][1] = pack_bf16(t0[2], t0[3]);
                qf[hh][2] = pack_bf16(t1[0], t1[1]); qf[hh][3] = pack_bf16(t1[2], t1[3]);
                const float* k0 = &acc[32 + 8 * hh]; const float* k1 = &acc[32 + 8 * hh + 4];
                uint4 kv;
                kv.x = pack_bf16(k0[0], k0[1]); kv.y = pack_bf16(k1[0], k1[1]);
                kv.z = pack_bf16(k0[2], k0[3]); kv.w = pack_bf16(k1[2], k1[3]);
                if (!dry) g_kf[((tj * 4 + hh) * 128 + blk) * 32 + lane] = kv;
                const float* v0 = &acc[64 + 8 * hh]; const float* v1 = &acc[64 + 8 * hh + 4];
                uint4 vv;
                vv.x = movmatrix(pack_bf16(v0[0], v0[1])); vv.y = movmatrix(pack_bf16(v0[2], v0[3]));
                vv.z = movmatrix(pack_bf16(v1[0], v1[1])); vv.w = movmatrix(pack_bf16(v1[2], v1[3]));
                if (!dry) g_vf[((tj * 4 + hh) * 128 + blk) * 32 + lane] = vv;
            }
            __syncwarp();
            if (lane0) mbar_arrive(sb + B_KVDONE);
            const float z0 = __shfl_sync(0xffffffffu, acc[96], lane & ~3), z1 = __shfl_sync(0xffffffffu, acc[98], lane & ~3);
            g0 = 1.f / (1.f + __expf(-z0)); g1 = 1.f / (1.f + __expf(-z1));
        }
        TS(3);
        const int wrow = (warp & 3) * 16;
        {
            float acc[112];
            int prev = 0;
            for (int s = 0; s < (dry ? 4 : N_FFN1); s++) {
                CWAIT();
                const uint32_t bs = sb + RING_OFF + r.slot * SLOT, as = xa + (s >> 1) * 16384 + (s & 1) * 64;
                wgmma_fence();
                wgmma_ss_n224(acc, desc_a(as), desc_b(bs), s);
                wgmma_ss_n224(acc, desc_a(as + 32), desc_b(bs + 2048), 1);
                wgmma_commit();
                if (s > 0) { wgmma_wait<1>(); if (lane0) mbar_arrive(sb + B_EMPTY + 8 * prev); }
                prev = r.slot; r.next();
            }
            wgmma_wait<0>();
            fence_acc(acc);
            if (lane0) mbar_arrive(sb + B_EMPTY + 8 * prev);
            TS(4);
            const float s0 = 1.f - g0, s1 = 1.f - g1;
            asm volatile("bar.sync %0, 128;" :: "r"(1 + wg) : "memory");
            const uint32_t strow = xa + (wrow + ((lane >> 3) & 1) * 8 + (lane & 7)) * 128;
#pragma unroll
            for (int p = 0; p < 14; p++) {
                const int nt = 2 * p + (lane >> 4);
                const float* a = &acc[8 * p];
                stmatrix_x4(strow + (p >> 2) * 16384 + (((nt & 7) ^ (lane & 7)) << 4),
                            pack_bf16_relu(a[0] * s0, a[1] * s0), pack_bf16_relu(a[2] * s1, a[3] * s1),
                            pack_bf16_relu(a[4] * s0, a[5] * s0), pack_bf16_relu(a[6] * s1, a[7] * s1));
            }
        }
        TS(5);
        {
            fence_async_smem();
            asm volatile("bar.sync 4, 256;" ::: "memory");
            float accA[64], accB[64];
            auto epilogue = [&](float (&acc)[64], int q) {
                fence_acc(acc);
                const uint32_t st = sb + STG_OFF + (q & 1) * 32768 + warp * 4096;
                if (q >= 2 && !dry) mbar_wait(sb + B_SF + 8 * (q & 1), 0);
#pragma unroll
                for (int t2 = 0; t2 < 8; t2++) {
                    uint4 v;
                    v.x = pack_bf16(acc[8 * t2 + 0], acc[8 * t2 + 1]); v.y = pack_bf16(acc[8 * t2 + 2], acc[8 * t2 + 3]);
                    v.z = pack_bf16(acc[8 * t2 + 4], acc[8 * t2 + 5]); v.w = pack_bf16(acc[8 * t2 + 6], acc[8 * t2 + 7]);
                    sts128(st + t2 * 512 + lane * 16, v);
                }
                fence_async_smem();
                __syncwarp();
                if (lane0) mbar_arrive(sb + B_SQ + 8 * q);
            };
            int rel = r.slot;
#pragma unroll
            for (int m = 0; m < N_FFN2; m++) {
                CWAIT();
                wgmma_fence();
#pragma unroll
                for (int h = 0; h < 2; h++) {
                    const int u = 2 * m + h, q = u / 7, rr = u % 7;
                    const uint32_t bs = sb + RING_OFF + r.slot * SLOT + h * 8192;
                    const uint32_t as = xa + (rr >> 1) * 16384 + (rr & 1) * 64;
                    if (!(q & 1)) {
                        wgmma_ss_n128(accA, desc_a(as), desc_b(bs), rr);
                        wgmma_ss_n128(accA, desc_a(as + 32), desc_b(bs + 2048), 1);
                    } else {
                        wgmma_ss_n128(accB, desc_a(as), desc_b(bs), rr);
                        wgmma_ss_n128(accB, desc_a(as + 32), desc_b(bs + 2048), 1);
                    }
                }
                wgmma_commit();
                r.next();
                wgmma_wait<1>();
                if (m > 0) {
                    if (lane0) mbar_arrive(sb + B_EMPTY + 8 * rel);
                    if (++rel == RING) rel = 0;
                }
                if (m == 4) { TS(25); epilogue(accA, 0); }
                if (m == 7) { TS(26); epilogue(accB, 1); }
                if (m == 11) { TS(27); epilogue(accA, 2); }
            }
            wgmma_wait<0>();
            if (lane0) { mbar_arrive(sb + B_EMPTY + 8 * rel); mbar_arrive(sb + B_HDEAD); }
            epilogue(accB, 3);
        }
        TS(6);
        {
            const float SC = 0.25f * 1.4426950408889634f;
            const int gb0 = 8 * ti - 16 + warp;
            int slotK = 0, slotV = 0;
            const uint32_t ostore = sb + OWN_OFF + (warp * 16 + ((lane >> 3) & 1) * 8 + (lane & 7)) * 128;
            uint32_t* odst = reinterpret_cast<uint32_t*>(g_o + (size_t)(ti * 128 + warp * 16 + g) * 512 + tj * 64 + ((lane & 1) ? 8 : 0) + (lane & 2) * 2);
#define NHEADS (dry ? 2 : 4)
#define ATT_KWAIT(kb) do { slotK = r.slot; CWAIT(); kb = sb + RING_OFF + slotK * SLOT + warp * 512 + lane * 16; r.next(); } while (0)
#define ATT_VWAIT(vb) do { slotV = r.slot; CWAIT(); vb = sb + RING_OFF + slotV * SLOT + warp * 512 + lane * 16; r.next(); TS(21 + hh); } while (0)
#define ATT_KREL() do { __syncwarp(); if (lane0) mbar_arrive(sb + B_EMPTY + 8 * slotK); } while (0)
#define ATT_VREL() do { __syncwarp(); if (lane0) mbar_arrive(sb + B_EMPTY + 8 * slotV); } while (0)
#define ATT_NEXTQ(h) do { \
                if ((h) == 1) { q0 = qf[1][0]; q1 = qf[1][1]; q2 = qf[1][2]; q3 = qf[1][3]; } \
                else if ((h) == 2) { q0 = qf[2][0]; q1 = qf[2][1]; q2 = qf[2][2]; q3 = qf[2][3]; } \
                else { q0 = qf[3][0]; q1 = qf[3][1]; q2 = qf[3][2]; q3 = qf[3][3]; } } while (0)
#define ATT_STORE(h, r0, r1, r2, r3) do { \
                if ((h) == 0 && !dry) mbar_wait(sb + B_SF + 8, 1);        \
                stmatrix_x4(ostore + (((2 * (h) + (lane >> 4)) ^ (lane & 7)) << 4), r0, r1, r2, r3); \
                const bool odd = lane & 1; \
                const uint32_t sl = __shfl_xor_sync(0xffffffffu, odd ? (r0) : (r2), 1), sh = __shfl_xor_sync(0xffffffffu, odd ? (r1) : (r3), 1); \
                if (!dry) *reinterpret_cast<uint2*>(odst + 8 * (h)) = odd ? make_uint2(sl, r2) : make_uint2(r0, sl); \
                if (!dry) *reinterpret_cast<uint2*>(odst + 8 * (h) + 8 * 256) = odd ? make_uint2(sh, r3) : make_uint2(r1, sh); \
                } while (0)
            auto attention = [&](auto masked_tag) {
            constexpr bool MASKED = decltype(masked_tag)::value;
            const float NEG = -INFINITY;
            const uint32_t ONES = 0x3F803F80u;
            float sa[8][2][4], sb2[8][2][4];
            float o[2][4], ls[4];
            float m0, m1;
            uint32_t q0 = qf[0][0], q1 = qf[0][1], q2 = qf[0][2], q3 = qf[0][3];
            auto qk = [&](float (&s)[8][2][4], int ps, int t, uint32_t kbase) {
                if (ps == 0 && t == 0) {
                    const uint4 kd = lds128(kbase + 16 * 512);
                    const uint4 kf = lds128(kbase);
                    float f[2][4];
                    const float ci = (!MASKED || opaque(gb0) >= 0) ? 0.f : NEG;
                    mma16816_c(s[0][0], q0, q1, q2, q3, kd.x, kd.y, 0.f);
                    mma16816_c(s[0][1], q0, q1, q2, q3, kd.z, kd.w, 0.f);
                    mma16816_c(f[0], q0, q1, q2, q3, kf.x, kf.y, ci);
                    mma16816_c(f[1], q0, q1, q2, q3, kf.z, kf.w, ci);
#pragma unroll
                    for (int u = 0; u < 2; u++)
#pragma unroll
                        for (int e = 0; e < 4; e++) {
                            const int row = g + 8 * (e >> 1), col = 8 * u + 2 * c + (e & 1);
                            s[0][u][e] = (col > row) ? f[u][e] : s[0][u][e];
                        }
                } else {
                    const uint4 kf = lds128(kbase + (8 * ps + t) * 512);
                    const float ci = (!MASKED || opaque(gb0) + 8 * ps + t >= 0) ? 0.f : NEG;
                    mma16816_c(s[t][0], q0, q1, q2, q3, kf.x, kf.y, ci);
                    mma16816_c(s[t][1], q0, q1, q2, q3, kf.z, kf.w, ci);
                }
            };
            auto rowmax = [&](float (&s)[8][2][4], float b0, float b1, float& n0, float& n1) {
                int i0 = __float_as_int(b0), i1 = __float_as_int(b1);
#pragma unroll
                for (int t = 0; t < 8; t++)
#pragma unroll
                    for (int u = 0; u < 2; u++) {
                        i0 = __vimax3_s32(i0, __float_as_int(s[t][u][0]), __float_as_int(s[t][u][1]));
                        i1 = __vimax3_s32(i1, __float_as_int(s[t][u][2]), __float_as_int(s[t][u][3]));
                    }
                i0 = max(i0, __shfl_xor_sync(0xffffffffu, i0, 1)); i1 = max(i1, __shfl_xor_sync(0xffffffffu, i1, 1));
                i0 = max(i0, __shfl_xor_sync(0xffffffffu, i0, 2)); i1 = max(i1, __shfl_xor_sync(0xffffffffu, i1, 2));
                n0 = __int_as_float(i0); n1 = __int_as_float(i1);
                if (__any_sync(0xffffffffu, (i0 | i1) < 0)) {
                    asm volatile("" ::: "memory");
                    n0 = b0; n1 = b1;
#pragma unroll
                    for (int t = 0; t < 8; t++)
#pragma unroll
                        for (int u = 0; u < 2; u++) {
                            n0 = fmaxf(n0, fmaxf(s[t][u][0], s[t][u][1]));
                            n1 = fmaxf(n1, fmaxf(s[t][u][2], s[t][u][3]));
                        }
                    n0 = fmaxf(n0, __shfl_xor_sync(0xffffffffu, n0, 1)); n1 = fmaxf(n1, __shfl_xor_sync(0xffffffffu, n1, 1));
                    n0 = fmaxf(n0, __shfl_xor_sync(0xffffffffu, n0, 2)); n1 = fmaxf(n1, __shfl_xor_sync(0xffffffffu, n1, 2));
                }
            };
            auto pv = [&](const float (&p)[2][4], uint32_t vaddr) {
                const uint4 vf = lds128(vaddr);
                const uint32_t a0 = pack_bf16(p[0][0], p[0][1]), a1 = pack_bf16(p[0][2], p[0][3]);
                const uint32_t a2 = pack_bf16(p[1][0], p[1][1]), a3 = pack_bf16(p[1][2], p[1][3]);
                mma16816(o[0], a0, a1, a2, a3, vf.x, vf.y);
                mma16816(o[1], a0, a1, a2, a3, vf.z, vf.w);
                mma16816(ls, a0, a1, a2, a3, ONES, ONES);
            };
            auto expv = [&](float (&s)[8][2][4], int ps, int t, float mc0, float mc1, uint32_t vbase) {
                float p[2][4];
#pragma unroll
                for (int u = 0; u < 2; u++) {
                    p[u][0] = ex2(fmaf(s[t][u][0], SC, -mc0)); p[u][1] = ex2(fmaf(s[t][u][1], SC, -mc0));
                    p[u][2] = ex2(fmaf(s[t][u][2], SC, -mc1)); p[u][3] = ex2(fmaf(s[t][u][3], SC, -mc1));
                }
                if (ps == 0 && t == 0) {
                    float pd[2][4], pf[2][4];
#pragma unroll
                    for (int u = 0; u < 2; u++)
#pragma unroll
                        for (int e = 0; e < 4; e++) {
                            const int row = g + 8 * (e >> 1), col = 8 * u + 2 * c + (e & 1);
                            pf[u][e] = (col > row) ? p[u][e] : 0.f;
                            pd[u][e] = (col > row) ? 0.f : p[u][e];
                        }
                    pv(pd, vbase + 16 * 512);
                    pv(pf, vbase);
                } else {
                    pv(p, vbase + (8 * ps + t) * 512);
                }
            };
            uint32_t kbase, vbase;
            ATT_KWAIT(kbase);
#pragma unroll
            for (int t = 0; t < 8; t++) qk(sa, 0, t, kbase);
            rowmax(sa, NEG, NEG, m0, m1);
#pragma unroll 1
            for (int hh = 0; hh < NHEADS; hh++) {
                ATT_VWAIT(vbase);
#pragma unroll
                for (int e = 0; e < 4; e++) { o[0][e] = 0.f; o[1][e] = 0.f; ls[e] = 0.f; }
                {
                    const float mc0 = m0 * SC, mc1 = m1 * SC;
#pragma unroll
                    for (int t = 0; t < 8; t++) { qk(sb2, 1, t, kbase); expv(sa, 0, t, mc0, mc1, vbase); }
                    ATT_KREL();
                    float n0, n1;
                    rowmax(sb2, m0, m1, n0, n1);
                    const float a0 = ex2((m0 - n0) * SC), a1 = ex2((m1 - n1) * SC);
                    ls[0] *= a0; ls[2] *= a1;
                    o[0][0] *= a0; o[0][1] *= a0; o[1][0] *= a0; o[1][1] *= a0;
                    o[0][2] *= a1; o[0][3] *= a1; o[1][2] *= a1; o[1][3] *= a1;
                    m0 = n0; m1 = n1;
                }
                {
                    const float mc0 = m0 * SC, mc1 = m1 * SC;
                    const bool more = hh + 1 < NHEADS;
                    if (more) {
                        ATT_KWAIT(kbase);
                        ATT_NEXTQ(hh + 1);
#pragma unroll
                        for (int t = 0; t < 8; t++) { qk(sa, 0, t, kbase); expv(sb2, 1, t, mc0, mc1, vbase); }
                        rowmax(sa, NEG, NEG, m0, m1);
                    } else {
#pragma unroll
                        for (int t = 0; t < 8; t++) expv(sb2, 1, t, mc0, mc1, vbase);
                    }
                    ATT_VREL();
                }
                const float f0 = __fdividef(g0, ls[0]), f1 = __fdividef(g1, ls[2]);
                ATT_STORE(hh, pack_bf16(o[0][0] * f0, o[0][1] * f0), pack_bf16(o[0][2] * f1, o[0][3] * f1),
                              pack_bf16(o[1][0] * f0, o[1][1] * f0), pack_bf16(o[1][2] * f1, o[1][3] * f1));
            }
            };
            if (ti >= 2) attention(BoolTag<false>{}); else attention(BoolTag<true>{});
            fence_async_smem();
            __syncwarp();
            if (lane0) { mbar_arrive(sb + B_ODONE); red_release(&g_ocnt[blockIdx.x * 32], 1u); }
        }
        TS(7);
        {
            float acc[32];
            uint4 pv[4][4];
            if (!dry) mbar_wait(sb + B_PREADY, 0);
            {
                const uint4* p = g_part + (size_t)((ti * 8 + tj) * 8 + 4) * 1024 + warp * 128 + lane;
#pragma unroll
                for (int s = 0; s < 4; s++)
#pragma unroll
                    for (int n = 0; n < 4; n++) pv[n][s] = dry ? make_uint4(0u, 0u, 0u, 0u) : ldg_weak(p + s * 1024 + n * 32);
            }
            if (!dry) mbar_wait(sb + B_WOFULL, 0);
            if (!dry) mbar_wait(sb + B_ODONE, 0);
            TS(15);
            wgmma_fence();
#pragma unroll
            for (int k = 0; k < 4; k++) wgmma_ss_n64(acc, desc_a(sb + OWN_OFF + wg * 8192 + 32 * k), desc_b(sb + X_OFF + tj * 8192 + 2048 * k), k);
            wgmma_commit();
            TS(16);
#pragma unroll 1
            for (int m = 0; m < N_O; m++) {
                CWAIT();
                uint32_t js; asm volatile("ld.shared.u32 %0, [%1];" : "=r"(js) : "r"(sb + OSRC_OFF + 4 * m) : "memory");
                const uint32_t as = sb + RING_OFF + r.slot * SLOT + wg * 8192;
                const uint32_t bs = sb + X_OFF + (js & 7) * 8192;
                wgmma_fence();
#pragma unroll
                for (int k = 0; k < 4; k++) wgmma_ss_n64(acc, desc_a(as + 32 * k), desc_b(bs + 2048 * k), 1);
                wgmma_commit();
                if (m == 0) { wgmma_wait<0>(); if (lane0) mbar_arrive(sb + B_EMPTY + 8 * r.slot); }
                r.next();
            }
            float base[32];
            if (!dry) mbar_wait(sb + B_HSUM, 0);
#pragma unroll
            for (int n = 0; n < 4; n++) {
                const uint4 u0 = lds128(sb + STG_OFF + (warp * 8 + 2 * n) * 512 + lane * 16), u1 = lds128(sb + STG_OFF + (warp * 8 + 2 * n + 1) * 512 + lane * 16);
                float* a = &base[8 * n];
                a[0] = __uint_as_float(u0.x); a[1] = __uint_as_float(u0.y); a[2] = __uint_as_float(u0.z); a[3] = __uint_as_float(u0.w);
                a[4] = __uint_as_float(u1.x); a[5] = __uint_as_float(u1.y); a[6] = __uint_as_float(u1.z); a[7] = __uint_as_float(u1.w);
#pragma unroll
                for (int s = 0; s < 4; s++) {
                    a[0] += bf_lo(pv[n][s].x); a[1] += bf_hi(pv[n][s].x); a[2] += bf_lo(pv[n][s].y); a[3] += bf_hi(pv[n][s].y);
                    a[4] += bf_lo(pv[n][s].z); a[5] += bf_hi(pv[n][s].z); a[6] += bf_lo(pv[n][s].w); a[7] += bf_hi(pv[n][s].w);
                }
            }
            fence_acc(base);
            wgmma_wait<0>();
            fence_acc(acc);
            TS(17);
#pragma unroll
            for (int k = 0; k < 32; k++) acc[k] += base[k];
            __nv_bfloat16* o = out + (size_t)(ti * 128 + warp * 16 + g) * 512 + tj * 64 + ((lane & 1) ? 8 : 0) + (lane & 2) * 2;
            const bool odd = lane & 1;
#pragma unroll
            for (int t2 = 0; t2 < 4; t2++) {
                const uint32_t lo0 = pack_bf16(acc[8 * t2 + 0], acc[8 * t2 + 1]), hi0 = pack_bf16(acc[8 * t2 + 2], acc[8 * t2 + 3]);
                const uint32_t lo1 = pack_bf16(acc[8 * t2 + 4], acc[8 * t2 + 5]), hi1 = pack_bf16(acc[8 * t2 + 6], acc[8 * t2 + 7]);
                const uint32_t sl = __shfl_xor_sync(0xffffffffu, odd ? lo0 : lo1, 1), sh = __shfl_xor_sync(0xffffffffu, odd ? hi0 : hi1, 1);
                if (!dry) *reinterpret_cast<uint2*>(o + 16 * t2) = odd ? make_uint2(sl, lo1) : make_uint2(lo0, sl);
                if (!dry) *reinterpret_cast<uint2*>(o + 16 * t2 + 8 * 512) = odd ? make_uint2(sh, hi1) : make_uint2(hi0, sh);
            }
            if (tid == 0 && !dry) TSG(30);
        }
        TS(8);
    }
}

typedef CUresult (*PFN_encodeTiled)(CUtensorMap*, CUtensorMapDataType, cuuint32_t, void*, const cuuint64_t*, const cuuint64_t*,
                                    const cuuint32_t*, const cuuint32_t*, CUtensorMapInterleave, CUtensorMapSwizzle,
                                    CUtensorMapL2promotion, CUtensorMapFloatOOBfill);

void make_map(PFN_encodeTiled enc, CUtensorMap* m, const void* base, int rank, const cuuint64_t* dims, const cuuint64_t* strides, const cuuint32_t* box) {
    cuuint32_t es[5] = {1, 1, 1, 1, 1};
    enc(m, CU_TENSOR_MAP_DATA_TYPE_BFLOAT16, (cuuint32_t)rank, const_cast<void*>(base), dims, strides, box, es,
        CU_TENSOR_MAP_INTERLEAVE_NONE, CU_TENSOR_MAP_SWIZZLE_128B, CU_TENSOR_MAP_L2_PROMOTION_L2_256B, CU_TENSOR_MAP_FLOAT_OOB_FILL_NONE);
}

}

extern "C" void kernel_launch(void* const* d_in, const int* in_sizes, int n_in, void* d_out, int out_size) {
    (void)in_sizes; (void)n_in; (void)out_size;
    const void* x = d_in[0]; const void* wqkv = d_in[1]; const void* wo = d_in[2];
    const void* w1 = d_in[4]; const void* w2 = d_in[5]; const void* gate_w = d_in[6];
    static PFN_encodeTiled enc = nullptr;
    if (!enc) {
        void* fn = nullptr; cudaDriverEntryPointQueryResult st;
        cudaGetDriverEntryPoint("cuTensorMapEncodeTiled", &fn, cudaEnableDefault, &st);
        enc = (PFN_encodeTiled)fn;
        cudaFuncSetAttribute(fused_kernel, cudaFuncAttributeMaxDynamicSharedMemorySize, SMEM_BYTES);
    }
    CUtensorMap mx, mqkv, mw1, mw2, mwo, mw1a, mo;
    void* optr = nullptr;
    cudaGetSymbolAddress(&optr, g_o);
    { cuuint64_t d[2] = {512, 2048}, s[1] = {1024}; cuuint32_t b[2] = {64, 128}; make_map(enc, &mo, optr, 2, d, s, b); }
    { cuuint64_t d[4] = {64, 512, 3, 8}, s[3] = {3584, 128, 448}; cuuint32_t b[4] = {64, 32, 3, 1}; make_map(enc, &mw1a, w1, 4, d, s, b); }
    { cuuint64_t d[2] = {512, 2048}, s[1] = {1024}; cuuint32_t b[2] = {64, 128}; make_map(enc, &mx, x, 2, d, s, b); }
    { cuuint64_t d[4] = {64, 512, 8, 3}, s[3] = {3072, 128, 1024}; cuuint32_t b[4] = {64, 32, 1, 3}; make_map(enc, &mqkv, wqkv, 4, d, s, b); }
    { cuuint64_t d[2] = {1792, 512}, s[1] = {3584}; cuuint32_t b[2] = {64, 32}; make_map(enc, &mw1, w1, 2, d, s, b); }
    { cuuint64_t d[3] = {64, 1792, 8}, s[2] = {1024, 128}; cuuint32_t b[3] = {64, 32, 2}; make_map(enc, &mw2, w2, 3, d, s, b); }
    { cuuint64_t d[2] = {512, 512}, s[1] = {1024}; cuuint32_t b[2] = {64, 256}; make_map(enc, &mwo, wo, 2, d, s, b); }
    fused_kernel<<<NCTA, 384, SMEM_BYTES, cudaStreamPerThread>>>(mx, mqkv, mw1, mw2, mwo, mw1a, mo, (const __nv_bfloat16*)gate_w, (__nv_bfloat16*)d_out,
                                           (const uint8_t*)w1, (const uint8_t*)w2, (const uint8_t*)wo);
}
```

```cpp
#include <cuda_runtime.h>
#include <cuda_bf16.h>
#include <cuda.h>
#include <stdint.h>

namespace {

#define PF1_AT 1
#define PF2_AT 5
#define LEAD1 2
#define NCTA 132
constexpr int RING = 6;
constexpr int SLOT = 16384;
constexpr uint32_t X_OFF = 0;
constexpr uint32_t STG_OFF = X_OFF + 4 * 16384;
constexpr uint32_t RING_OFF = 131072;
constexpr uint32_t BAR_OFF = RING_OFF + RING * SLOT;
constexpr uint32_t B_FULL = BAR_OFF, B_EMPTY = BAR_OFF + 64, B_XFULL = BAR_OFF + 128, B_HDEAD = BAR_OFF + 192,
                   B_EREADY = BAR_OFF + 200, B_KVDONE = BAR_OFF + 208, B_ODONE = BAR_OFF + 224,
                   B_KVREADY = BAR_OFF + 232, B_WOFULL = BAR_OFF + 240, B_HSUM = BAR_OFF + 248, B_PREADY = BAR_OFF + 264,
                   B_SQ = BAR_OFF + 272, B_SF = BAR_OFF + 304;
constexpr uint32_t EPOCH_OFF = BAR_OFF + 256, ITEM_OFF = BAR_OFF + 260, OSRC_OFF = BAR_OFF + 384;
constexpr uint32_t OWN_OFF = X_OFF + 6 * 16384;
constexpr uint32_t SMEM_BYTES = BAR_OFF + 1024;

constexpr int N_QKV = 16, N_FFN1 = 16, N_FFN2 = 14, N_KV = 8, N_O = 7;

__device__ uint4 g_kf[32 * 128 * 32];
__device__ uint4 g_vf[32 * 128 * 32];
__device__ uint4 g_part[16 * 8 * 8 * 8 * 4 * 32];
__device__ __nv_bfloat16 g_o[2048 * 512];
__device__ unsigned g_ticket;
__device__ unsigned g_kvcnt[128 * 32];
__device__ unsigned g_pcnt[128 * 32];
__device__ unsigned g_ocnt[128 * 32];
#define TS(k) do {} while (0)
#define TS2(k) do {} while (0)
#define TS2X(k) do {} while (0)
#define TSX(k) do {} while (0)
#define TSG(k) do {} while (0)

__device__ __forceinline__ uint32_t smem_u32(const void* p) { return (uint32_t)__cvta_generic_to_shared(p); }
__device__ __forceinline__ void mbar_init(uint32_t bar, uint32_t cnt) { asm volatile("mbarrier.init.shared::cta.b64 [%0], %1;" :: "r"(bar), "r"(cnt) : "memory"); }
__device__ __forceinline__ void mbar_expect_tx(uint32_t bar, uint32_t bytes) { asm volatile("mbarrier.arrive.expect_tx.shared::cta.b64 _, [%0], %1;" :: "r"(bar), "r"(bytes) : "memory"); }
__device__ __forceinline__ void mbar_expect_only(uint32_t bar, uint32_t bytes) { asm volatile("mbarrier.expect_tx.relaxed.cta.shared::cta.b64 [%0], %1;" :: "r"(bar), "r"(bytes) : "memory"); }
__device__ __forceinline__ void mbar_arrive(uint32_t bar) { asm volatile("mbarrier.arrive.shared::cta.b64 _, [%0];" :: "r"(bar) : "memory"); }
__device__ __forceinline__ void mbar_wait(uint32_t bar, uint32_t parity) {
    asm volatile("{\n.reg .pred P1, P2;\n.reg .u32 n;\nmov.u32 n, 0;\n"
                 "WAIT_LOOP:\n"
                 "mbarrier.try_wait.parity.shared::cta.b64 P1, [%0], %1;\n"
                 "@P1 bra WAIT_DONE;\n"
                 "add.u32 n, n, 1;\n"
                 "setp.lt.u32 P2, n, 0x400000;\n"
                 "@P2 bra WAIT_LOOP;\n"
                 "WAIT_DONE:\n}" :: "r"(bar), "r"(parity) : "memory");
}
__device__ __forceinline__ void tma_2d(uint32_t dst, const void* map, uint32_t bar, int c0, int c1) {
    asm volatile("cp.async.bulk.tensor.2d.shared::cluster.global.mbarrier::complete_tx::bytes [%0], [%1, {%3, %4}], [%2];"
        :: "r"(dst), "l"(map), "r"(bar), "r"(c0), "r"(c1) : "memory");
}
__device__ __forceinline__ void tma_3d(uint32_t dst, const void* map, uint32_t bar, int c0, int c1, int c2) {
    asm volatile("cp.async.bulk.tensor.3d.shared::cluster.global.mbarrier::complete_tx::bytes [%0], [%1, {%3, %4, %5}], [%2];"
        :: "r"(dst), "l"(map), "r"(bar), "r"(c0), "r"(c1), "r"(c2) : "memory");
}
__device__ __forceinline__ void tma_4d(uint32_t dst, const void* map, uint32_t bar, int c0, int c1, int c2, int c3) {
    asm volatile("cp.async.bulk.tensor.4d.shared::cluster.global.mbarrier::complete_tx::bytes [%0], [%1, {%3, %4, %5, %6}], [%2];"
        :: "r"(dst), "l"(map), "r"(bar), "r"(c0), "r"(c1), "r"(c2), "r"(c3) : "memory");
}
__device__ __forceinline__ void bulk_g2s(uint32_t dst, const void* src, uint32_t bytes, uint32_t bar) {
    asm volatile("cp.async.bulk.shared::cluster.global.mbarrier::complete_tx::bytes [%0], [%1], %2, [%3];"
        :: "r"(dst), "l"(src), "r"(bytes), "r"(bar) : "memory");
}
__device__ __forceinline__ void prefetch_l2(const void* src, uint32_t bytes) {
    asm volatile("cp.async.bulk.prefetch.L2.global [%0], %1;" :: "l"(src), "r"(bytes) : "memory");
}
__device__ __forceinline__ bool elect_one() {
    uint32_t p;
    asm volatile("{\n.reg .pred P;\nelect.sync _|P, 0xffffffff;\nselp.u32 %0, 1, 0, P;\n}" : "=r"(p));
    return p != 0;
}
__device__ __forceinline__ void wgmma_fence() { asm volatile("wgmma.fence.sync.aligned;" ::: "memory"); }
__device__ __forceinline__ void wgmma_commit() { asm volatile("wgmma.commit_group.sync.aligned;" ::: "memory"); }
template <int N> __device__ __forceinline__ void wgmma_wait() { asm volatile("wgmma.wait_group.sync.aligned %0;" :: "n"(N) : "memory"); }
__device__ __forceinline__ void fence_async_smem() { asm volatile("fence.proxy.async.shared::cta;" ::: "memory"); }
__device__ __forceinline__ uint64_t desc_a(uint32_t addr) {
    return (uint64_t)((addr & 0x3FFFF) >> 4) | ((uint64_t)1 << 16) | ((uint64_t)(1024 >> 4) << 32) | ((uint64_t)1 << 62);
}
__device__ __forceinline__ uint64_t desc_b(uint32_t addr) {
    return (uint64_t)((addr & 0x3FFFF) >> 4) | ((uint64_t)(4096 >> 4) << 16) | ((uint64_t)(1024 >> 4) << 32) | ((uint64_t)1 << 62);
}
__device__ __forceinline__ uint32_t pack_bf16(float lo, float hi) {
    uint32_t r; asm("cvt.rn.bf16x2.f32 %0, %1, %2;" : "=r"(r) : "f"(hi), "f"(lo)); return r;
}
__device__ __forceinline__ uint32_t pack_bf16_relu(float lo, float hi) {
    uint32_t r; asm("cvt.rn.relu.bf16x2.f32 %0, %1, %2;" : "=r"(r) : "f"(hi), "f"(lo)); return r;
}
__device__ __forceinline__ uint32_t movmatrix(uint32_t a) {
    uint32_t d; asm volatile("movmatrix.sync.aligned.m8n8.trans.b16 %0, %1;" : "=r"(d) : "r"(a)); return d;
}
__device__ __forceinline__ void stmatrix_x4(uint32_t addr, uint32_t r0, uint32_t r1, uint32_t r2, uint32_t r3) {
    asm volatile("stmatrix.sync.aligned.m8n8.x4.shared.b16 [%0], {%1, %2, %3, %4};" :: "r"(addr), "r"(r0), "r"(r1), "r"(r2), "r"(r3) : "memory");
}
__device__ __forceinline__ uint4 lds128(uint32_t addr) {
    uint4 v; asm volatile("ld.shared.v4.b32 {%0, %1, %2, %3}, [%4];" : "=r"(v.x), "=r"(v.y), "=r"(v.z), "=r"(v.w) : "r"(addr) : "memory"); return v;
}
__device__ __forceinline__ void mma16816(float (&c)[4], uint32_t a0, uint32_t a1, uint32_t a2, uint32_t a3, uint32_t b0, uint32_t b1) {
    asm volatile("mma.sync.aligned.m16n8k16.row.col.f32.bf16.bf16.f32 {%0,%1,%2,%3}, {%4,%5,%6,%7}, {%8,%9}, {%0,%1,%2,%3};"
        : "+f"(c[0]), "+f"(c[1]), "+f"(c[2]), "+f"(c[3]) : "r"(a0), "r"(a1), "r"(a2), "r"(a3), "r"(b0), "r"(b1));
}
__device__ __forceinline__ void mma16816_c(float (&c)[4], uint32_t a0, uint32_t a1, uint32_t a2, uint32_t a3, uint32_t b0, uint32_t b1, float ci) {
    asm volatile("mma.sync.aligned.m16n8k16.row.col.f32.bf16.bf16.f32 {%0,%1,%2,%3}, {%4,%5,%6,%7}, {%8,%9}, {%10,%10,%10,%10};"
        : "=f"(c[0]), "=f"(c[1]), "=f"(c[2]), "=f"(c[3]) : "r"(a0), "r"(a1), "r"(a2), "r"(a3), "r"(b0), "r"(b1), "f"(ci));
}
__device__ __forceinline__ int opaque(int v) { asm volatile("" : "+r"(v)); return v; }
__device__ __forceinline__ float ex2(float x) { float y; asm("ex2.approx.ftz.f32 %0, %1;" : "=f"(y) : "f"(x)); return y; }
__device__ __forceinline__ unsigned ld_acquire(const unsigned* p) {
    unsigned v; asm volatile("ld.acquire.gpu.global.u32 %0, [%1];" : "=r"(v) : "l"(p) : "memory"); return v;
}
__device__ __forceinline__ void red_release(unsigned* p, unsigned v) {
    asm volatile("red.release.gpu.global.add.u32 [%0], %1;" :: "l"(p), "r"(v) : "memory");
}
__device__ __forceinline__ void wait_counter(const unsigned* p, unsigned target) {
    uint32_t n = 0;
    while ((int)(ld_acquire(p) - target) < 0) { if (++n > (1u << 20)) break; }
}
__device__ __forceinline__ uint4 ldg_weak(const uint4* p) {
    uint4 v; asm volatile("ld.global.L1::no_allocate.v4.b32 {%0, %1, %2, %3}, [%4];" : "=r"(v.x), "=r"(v.y), "=r"(v.z), "=r"(v.w) : "l"(p) : "memory"); return v;
}
__device__ __forceinline__ float bf_lo(uint32_t v) { return __uint_as_float(v << 16); }
__device__ __forceinline__ float bf_hi(uint32_t v) { return __uint_as_float(v & 0xFFFF0000u); }

__device__ __forceinline__ void wgmma_ss_n64(float (&d)[32], uint64_t da, uint64_t db, int scale_d) {
    asm volatile("{\n.reg .pred p;\nsetp.ne.b32 p, %34, 0;\n"
        "wgmma.mma_async.sync.aligned.m64n64k16.f32.bf16.bf16 {%0, %1, %2, %3, %4, %5, %6, %7, %8, %9, %10, %11, %12, %13, %14, %15, %16, %17, %18, %19, %20, %21, %22, %23, %24, %25, %26, %27, %28, %29, %30, %31}, %32, %33, p, 1, 1, 0, 1;\n}\n"
        : "+f"(d[0]), "+f"(d[1]), "+f"(d[2]), "+f"(d[3]), "+f"(d[4]), "+f"(d[5]), "+f"(d[6]), "+f"(d[7]), "+f"(d[8]), "+f"(d[9]), "+f"(d[10]), "+f"(d[11]), "+f"(d[12]), "+f"(d[13]), "+f"(d[14]), "+f"(d[15]), "+f"(d[16]), "+f"(d[17]), "+f"(d[18]), "+f"(d[19]), "+f"(d[20]), "+f"(d[21]), "+f"(d[22]), "+f"(d[23]), "+f"(d[24]), "+f"(d[25]), "+f"(d[26]), "+f"(d[27]), "+f"(d[28]), "+f"(d[29]), "+f"(d[30]), "+f"(d[31])
        : "l"(da), "l"(db), "r"(scale_d));
}
__device__ __forceinline__ void wgmma_ss_n128(float (&d)[64], uint64_t da, uint64_t db, int scale_d) {
    asm volatile("{\n.reg .pred p;\nsetp.ne.b32 p, %66, 0;\n"
        "wgmma.mma_async.sync.aligned.m64n128k16.f32.bf16.bf16 {%0, %1, %2, %3, %4, %5, %6, %7, %8, %9, %10, %11, %12, %13, %14, %15, %16, %17, %18, %19, %20, %21, %22, %23, %24, %25, %26, %27, %28, %29, %30, %31, %32, %33, %34, %35, %36, %37, %38, %39, %40, %41, %42, %43, %44, %45, %46, %47, %48, %49, %50, %51, %52, %53, %54, %55, %56, %57, %58, %59, %60, %61, %62, %63}, %64, %65, p, 1, 1, 0, 1;\n}\n"
        : "+f"(d[0]), "+f"(d[1]), "+f"(d[2]), "+f"(d[3]), "+f"(d[4]), "+f"(d[5]), "+f"(d[6]), "+f"(d[7]), "+f"(d[8]), "+f"(d[9]), "+f"(d[10]), "+f"(d[11]), "+f"(d[12]), "+f"(d[13]), "+f"(d[14]), "+f"(d[15]), "+f"(d[16]), "+f"(d[17]), "+f"(d[18]), "+f"(d[19]), "+f"(d[20]), "+f"(d[21]), "+f"(d[22]), "+f"(d[23]), "+f"(d[24]), "+f"(d[25]), "+f"(d[26]), "+f"(d[27]), "+f"(d[28]), "+f"(d[29]), "+f"(d[30]), "+f"(d[31]), "+f"(d[32]), "+f"(d[33]), "+f"(d[34]), "+f"(d[35]), "+f"(d[36]), "+f"(d[37]), "+f"(d[38]), "+f"(d[39]), "+f"(d[40]), "+f"(d[41]), "+f"(d[42]), "+f"(d[43]), "+f"(d[44]), "+f"(d[45]), "+f"(d[46]), "+f"(d[47]), "+f"(d[48]), "+f"(d[49]), "+f"(d[50]), "+f"(d[51]), "+f"(d[52]), "+f"(d[53]), "+f"(d[54]), "+f"(d[55]), "+f"(d[56]), "+f"(d[57]), "+f"(d[58]), "+f"(d[59]), "+f"(d[60]), "+f"(d[61]), "+f"(d[62]), "+f"(d[63])
        : "l"(da), "l"(db), "r"(scale_d));
}
__device__ __forceinline__ void wgmma_ss_n200(float (&d)[100], uint64_t da, uint64_t db, int scale_d) {
    asm volatile("{\n.reg .pred p;\nsetp.ne.b32 p, %102, 0;\n"
        "wgmma.mma_async.sync.aligned.m64n200k16.f32.bf16.bf16 {%0, %1, %2, %3, %4, %5, %6, %7, %8, %9, %10, %11, %12, %13, %14, %15, %16, %17, %18, %19, %20, %21, %22, %23, %24, %25, %26, %27, %28, %29, %30, %31, %32, %33, %34, %35, %36, %37, %38, %39, %40, %41, %42, %43, %44, %45, %46, %47, %48, %49, %50, %51, %52, %53, %54, %55, %56, %57, %58, %59, %60, %61, %62, %63, %64, %65, %66, %67, %68, %69, %70, %71, %72, %73, %74, %75, %76, %77, %78, %79, %80, %81, %82, %83, %84, %85, %86, %87, %88, %89, %90, %91, %92, %93, %94, %95, %96, %97, %98, %99}, %100, %101, p, 1, 1, 0, 1;\n}\n"
        : "+f"(d[0]), "+f"(d[1]), "+f"(d[2]), "+f"(d[3]), "+f"(d[4]), "+f"(d[5]), "+f"(d[6]), "+f"(d[7]), "+f"(d[8]), "+f"(d[9]), "+f"(d[10]), "+f"(d[11]), "+f"(d[12]), "+f"(d[13]), "+f"(d[14]), "+f"(d[15]), "+f"(d[16]), "+f"(d[17]), "+f"(d[18]), "+f"(d[19]), "+f"(d[20]), "+f"(d[21]), "+f"(d[22]), "+f"(d[23]), "+f"(d[24]), "+f"(d[25]), "+f"(d[26]), "+f"(d[27]), "+f"(d[28]), "+f"(d[29]), "+f"(d[30]), "+f"(d[31]), "+f"(d[32]), "+f"(d[33]), "+f"(d[34]), "+f"(d[35]), "+f"(d[36]), "+f"(d[37]), "+f"(d[38]), "+f"(d[39]), "+f"(d[40]), "+f"(d[41]), "+f"(d[42]), "+f"(d[43]), "+f"(d[44]), "+f"(d[45]), "+f"(d[46]), "+f"(d[47]), "+f"(d[48]), "+f"(d[49]), "+f"(d[50]), "+f"(d[51]), "+f"(d[52]), "+f"(d[53]), "+f"(d[54]), "+f"(d[55]), "+f"(d[56]), "+f"(d[57]), "+f"(d[58]), "+f"(d[59]), "+f"(d[60]), "+f"(d[61]), "+f"(d[62]), "+f"(d[63]), "+f"(d[64]), "+f"(d[65]), "+f"(d[66]), "+f"(d[67]), "+f"(d[68]), "+f"(d[69]), "+f"(d[70]), "+f"(d[71]), "+f"(d[72]), "+f"(d[73]), "+f"(d[74]), "+f"(d[75]), "+f"(d[76]), "+f"(d[77]), "+f"(d[78]), "+f"(d[79]), "+f"(d[80]), "+f"(d[81]), "+f"(d[82]), "+f"(d[83]), "+f"(d[84]), "+f"(d[85]), "+f"(d[86]), "+f"(d[87]), "+f"(d[88]), "+f"(d[89]), "+f"(d[90]), "+f"(d[91]), "+f"(d[92]), "+f"(d[93]), "+f"(d[94]), "+f"(d[95]), "+f"(d[96]), "+f"(d[97]), "+f"(d[98]), "+f"(d[99])
        : "l"(da), "l"(db), "r"(scale_d));
}
__device__ __forceinline__ void wgmma_ss_n224(float (&d)[112], uint64_t da, uint64_t db, int scale_d) {
    asm volatile("{\n.reg .pred p;\nsetp.ne.b32 p, %114, 0;\n"
        "wgmma.mma_async.sync.aligned.m64n224k16.f32.bf16.bf16 {%0, %1, %2, %3, %4, %5, %6, %7, %8, %9, %10, %11, %12, %13, %14, %15, %16, %17, %18, %19, %20, %21, %22, %23, %24, %25, %26, %27, %28, %29, %30, %31, %32, %33, %34, %35, %36, %37, %38, %39, %40, %41, %42, %43, %44, %45, %46, %47, %48, %49, %50, %51, %52, %53, %54, %55, %56, %57, %58, %59, %60, %61, %62, %63, %64, %65, %66, %67, %68, %69, %70, %71, %72, %73, %74, %75, %76, %77, %78, %79, %80, %81, %82, %83, %84, %85, %86, %87, %88, %89, %90, %91, %92, %93, %94, %95, %96, %97, %98, %99, %100, %101, %102, %103, %104, %105, %106, %107, %108, %109, %110, %111}, %112, %113, p, 1, 1, 0, 1;\n}\n"
        : "+f"(d[0]), "+f"(d[1]), "+f"(d[2]), "+f"(d[3]), "+f"(d[4]), "+f"(d[5]), "+f"(d[6]), "+f"(d[7]), "+f"(d[8]), "+f"(d[9]), "+f"(d[10]), "+f"(d[11]), "+f"(d[12]), "+f"(d[13]), "+f"(d[14]), "+f"(d[15]), "+f"(d[16]), "+f"(d[17]), "+f"(d[18]), "+f"(d[19]), "+f"(d[20]), "+f"(d[21]), "+f"(d[22]), "+f"(d[23]), "+f"(d[24]), "+f"(d[25]), "+f"(d[26]), "+f"(d[27]), "+f"(d[28]), "+f"(d[29]), "+f"(d[30]), "+f"(d[31]), "+f"(d[32]), "+f"(d[33]), "+f"(d[34]), "+f"(d[35]), "+f"(d[36]), "+f"(d[37]), "+f"(d[38]), "+f"(d[39]), "+f"(d[40]), "+f"(d[41]), "+f"(d[42]), "+f"(d[43]), "+f"(d[44]), "+f"(d[45]), "+f"(d[46]), "+f"(d[47]), "+f"(d[48]), "+f"(d[49]), "+f"(d[50]), "+f"(d[51]), "+f"(d[52]), "+f"(d[53]), "+f"(d[54]), "+f"(d[55]), "+f"(d[56]), "+f"(d[57]), "+f"(d[58]), "+f"(d[59]), "+f"(d[60]), "+f"(d[61]), "+f"(d[62]), "+f"(d[63]), "+f"(d[64]), "+f"(d[65]), "+f"(d[66]), "+f"(d[67]), "+f"(d[68]), "+f"(d[69]), "+f"(d[70]), "+f"(d[71]), "+f"(d[72]), "+f"(d[73]), "+f"(d[74]), "+f"(d[75]), "+f"(d[76]), "+f"(d[77]), "+f"(d[78]), "+f"(d[79]), "+f"(d[80]), "+f"(d[81]), "+f"(d[82]), "+f"(d[83]), "+f"(d[84]), "+f"(d[85]), "+f"(d[86]), "+f"(d[87]), "+f"(d[88]), "+f"(d[89]), "+f"(d[90]), "+f"(d[91]), "+f"(d[92]), "+f"(d[93]), "+f"(d[94]), "+f"(d[95]), "+f"(d[96]), "+f"(d[97]), "+f"(d[98]), "+f"(d[99]), "+f"(d[100]), "+f"(d[101]), "+f"(d[102]), "+f"(d[103]), "+f"(d[104]), "+f"(d[105]), "+f"(d[106]), "+f"(d[107]), "+f"(d[108]), "+f"(d[109]), "+f"(d[110]), "+f"(d[111])
        : "l"(da), "l"(db), "r"(scale_d));
}
template <int N> __device__ __forceinline__ void fence_acc(float (&d)[N]) {
#pragma unroll
    for (int i = 0; i < N; i++) asm volatile("" : "+f"(d[i]) :: "memory");
}

__device__ __forceinline__ void bulk_s2g(void* dst, uint32_t src, uint32_t bytes) {
    asm volatile("cp.async.bulk.global.shared::cta.bulk_group [%0], [%1], %2;" :: "l"(dst), "r"(src), "r"(bytes) : "memory");
}
__device__ __forceinline__ void sts128(uint32_t addr, uint4 v) {
    asm volatile("st.shared.v4.b32 [%0], {%1, %2, %3, %4};" :: "r"(addr), "r"(v.x), "r"(v.y), "r"(v.z), "r"(v.w) : "memory");
}
__device__ __forceinline__ void sum_partials(uint32_t sb, int ti, int tj, int lane) {
    for (;;) {
        uint32_t item = 0;
        if (lane == 0) asm volatile("atom.shared.add.u32 %0, [%1], 1;" : "=r"(item) : "r"(sb + ITEM_OFF) : "memory");
        item = __shfl_sync(0xffffffffu, item, 0);
        if (item >= 8) break;
        const uint4* p = g_part + (size_t)((ti * 8 + tj) * 8) * 1024 + item * 128 + lane;
        uint4 v[4][4];
#pragma unroll
        for (int s = 0; s < 4; s++)
#pragma unroll
            for (int n = 0; n < 4; n++) v[n][s] = ldg_weak(p + s * 1024 + n * 32);
#pragma unroll
        for (int n = 0; n < 4; n++) {
            float a[8];
#pragma unroll
            for (int e = 0; e < 8; e++) a[e] = 0.f;
#pragma unroll
            for (int s = 0; s < 4; s++) {
                a[0] += bf_lo(v[n][s].x); a[1] += bf_hi(v[n][s].x); a[2] += bf_lo(v[n][s].y); a[3] += bf_hi(v[n][s].y);
                a[4] += bf_lo(v[n][s].z); a[5] += bf_hi(v[n][s].z); a[6] += bf_lo(v[n][s].w); a[7] += bf_hi(v[n][s].w);
            }
            const uint32_t d = sb + STG_OFF + (item * 8 + n * 2) * 512 + lane * 16;
            sts128(d, make_uint4(__float_as_uint(a[0]), __float_as_uint(a[1]), __float_as_uint(a[2]), __float_as_uint(a[3])));
            sts128(d + 512, make_uint4(__float_as_uint(a[4]), __float_as_uint(a[5]), __float_as_uint(a[6]), __float_as_uint(a[7])));
        }
    }
    __syncwarp();
    if (lane == 0) mbar_arrive(sb + B_HSUM);
}

#define PWAIT() mbar_wait(sb + B_EMPTY + 8 * r.slot, r.phase)
#define CWAIT() do { if (!dry) mbar_wait(sb + B_FULL + 8 * r.slot, r.phase); } while (0)
template <bool B> struct BoolTag { static constexpr bool value = B; };
struct Ring {
    int slot; uint32_t phase;
    __device__ __forceinline__ void next() { if (++slot == RING) { slot = 0; phase ^= 1; } }
};

__global__ void __launch_bounds__(384, 1)
fused_kernel(const __grid_constant__ CUtensorMap map_x, const __grid_constant__ CUtensorMap map_qkv,
             const __grid_constant__ CUtensorMap map_w1, const __grid_constant__ CUtensorMap map_w2,
             const __grid_constant__ CUtensorMap map_wo, const __grid_constant__ CUtensorMap map_w1a,
             const __grid_constant__ CUtensorMap map_o,
             const __nv_bfloat16* __restrict__ gate_w, __nv_bfloat16* __restrict__ out,
             const uint8_t* __restrict__ w1p, const uint8_t* __restrict__ w2p, const uint8_t* __restrict__ wop)
{
    extern __shared__ __align__(1024) uint8_t smem_raw[];
    const uint32_t sb = smem_u32(smem_raw);
    const int tid = threadIdx.x, warp = tid >> 5, lane = tid & 31;
    const bool dry = blockIdx.x >= 128;
    const int ti = dry ? (int)(blockIdx.x & 1) * 2 : blockIdx.x >> 3, tj = blockIdx.x & 7;
    if (dry && warp >= 8) {
        asm volatile("setmaxnreg.dec.sync.aligned.u32 88;");
        return;
    }

    if (tid == 0 && !dry) { TSG(31); TSX(0); }
    if (tid == 320) {
        asm volatile("prefetch.tensormap [%0];" :: "l"(&map_x) : "memory");
        asm volatile("prefetch.tensormap [%0];" :: "l"(&map_qkv) : "memory");
        asm volatile("prefetch.tensormap [%0];" :: "l"(&map_w1) : "memory");
        asm volatile("prefetch.tensormap [%0];" :: "l"(&map_w1a) : "memory");
        asm volatile("prefetch.tensormap [%0];" :: "l"(&map_w2) : "memory");
        asm volatile("prefetch.tensormap [%0];" :: "l"(&map_wo) : "memory");
        asm volatile("prefetch.tensormap [%0];" :: "l"(&map_o) : "memory");
    }
    if (tid == 256) {
        mbar_init(sb + B_FULL, 1); mbar_init(sb + B_XFULL, 1);
        fence_async_smem();
        mbar_expect_tx(sb + B_XFULL, 16384);
        tma_2d(sb + X_OFF, &map_x, sb + B_XFULL, 0, ti * 128);
        mbar_expect_only(sb + B_FULL, 12288);
        tma_4d(sb + RING_OFF, &map_qkv, sb + B_FULL, 0, 0, tj, 0);
    }
    uint32_t gwv[N_QKV / 2];
    if (warp == 8) {
        const unsigned short* gws = reinterpret_cast<const unsigned short*>(gate_w);
#pragma unroll
        for (int n = 0; n < N_QKV / 2; n++) gwv[n] = (uint32_t)__ldg(gws + 64 * n + lane) | ((uint32_t)__ldg(gws + 64 * n + 32 + lane) << 16);
    }
    if (tid == 288) {
        for (int s = 1; s < RING; s++) mbar_init(sb + B_FULL + 8 * s, 1);
        for (int s = 0; s < RING; s++) mbar_init(sb + B_EMPTY + 8 * s, 8);
        for (int s = 1; s < 8; s++) mbar_init(sb + B_XFULL + 8 * s, 1);
        fence_async_smem();
    }
    if (tid == 352) {
        mbar_init(sb + B_HDEAD, 8); mbar_init(sb + B_EREADY, 1); mbar_init(sb + B_KVDONE, 8); mbar_init(sb + B_KVREADY, 1);
        mbar_init(sb + B_ODONE, 8); mbar_init(sb + B_WOFULL, 1); mbar_init(sb + B_HSUM, 3);
        mbar_init(sb + B_PREADY, 1); mbar_init(sb + B_SF, 1); mbar_init(sb + B_SF + 8, 1);
        for (int s = 0; s < 4; s++) mbar_init(sb + B_SQ + 8 * s, 8);
        asm volatile("st.shared.u32 [%0], %1;" :: "r"(sb + ITEM_OFF), "r"(0) : "memory");
        fence_async_smem();
    }
    if (!dry) __syncthreads();

    if (warp >= 8) {
        asm volatile("setmaxnreg.dec.sync.aligned.u32 88;");
        if (warp == 8) {
            Ring r{0, 1};
            const bool leader = elect_one();
#pragma unroll
            for (int n = 0; n < N_QKV; n++) {
                const uint32_t full = sb + B_FULL + 8 * r.slot, dst = sb + RING_OFF + r.slot * SLOT;
                if (n > 0) {
                    if (!(n & 1) && leader) {
                        mbar_expect_tx(sb + B_XFULL + 8 * (n >> 1), 16384);
                        tma_2d(sb + X_OFF + (n >> 1) * 16384, &map_x, sb + B_XFULL + 8 * (n >> 1), (n >> 1) * 64, ti * 128);
                    }
                    if (n >= RING) PWAIT();
                    if (leader) {
                        mbar_expect_only(full, 12288);
                        tma_4d(dst, &map_qkv, full, 0, 32 * n, tj, 0);
                    }
                }
                const uint32_t gv = (n & 1) ? (gwv[n >> 1] >> 16) : (gwv[n >> 1] & 0xFFFFu);
                asm volatile("st.shared.v4.b32 [%0], {%1, %2, %2, %2};" :: "r"(dst + 12288 + lane * 128 + ((lane & 7) << 4)), "r"(gv), "r"(0) : "memory");
                fence_async_smem();
                __syncwarp();
                if (leader) mbar_arrive(full);
                r.next();
            }
#pragma unroll 1
            for (int n = 0; n < N_FFN1; n++) {
                const uint32_t full = sb + B_FULL + 8 * r.slot, dst = sb + RING_OFF + r.slot * SLOT;
                PWAIT();
                if (leader) {
                    mbar_expect_tx(full, 16384);
                    tma_4d(dst, &map_w1a, full, 0, 32 * n, 0, tj);
                    tma_2d(dst + 3 * 4096, &map_w1, full, 224 * tj + 192, 32 * n);
                }
                r.next();
            }
            {
                int q = 0, rr = 0;
#pragma unroll 1
                for (int n = 0; n < N_FFN2; n++) {
                    const uint32_t full = sb + B_FULL + 8 * r.slot, dst = sb + RING_OFF + r.slot * SLOT;
                    PWAIT();
                    if (leader) mbar_expect_tx(full, 16384);
#pragma unroll
                    for (int h = 0; h < 2; h++) {
                        if (leader) tma_3d(dst + h * 8192, &map_w2, full, 0, 224 * tj + 32 * rr, 2 * q);
                        if (++rr == 7) { rr = 0; q++; }
                    }
                    r.next();
                }
            }
            mbar_wait(sb + B_KVREADY, 0);
            asm volatile("fence.proxy.async.global;" ::: "memory");
            {
                const int bbase = 8 * ti - 16, b0 = bbase < 0 ? 0 : bbase;
                const uint32_t bytes = (uint32_t)(8 * ti + 8 - b0) * 512;
#pragma unroll 1
                for (int m = 0; m < N_KV; m++) {
                    const uint32_t full = sb + B_FULL + 8 * r.slot, dst = sb + RING_OFF + r.slot * SLOT;
                    if (m == RING) {
                        mbar_wait(sb + B_HDEAD, 0);
                        if (leader) {
                            mbar_expect_tx(sb + B_WOFULL, 65536);
#pragma unroll
                            for (int e = 0; e < 2; e++) tma_2d(sb + X_OFF + e * 32768, &map_wo, sb + B_WOFULL, 64 * tj, 256 * e);
                        }
                    }
                    PWAIT();
                    if (leader) {
                        const uint4* src = ((m & 1) ? g_vf : g_kf) + ((tj * 4 + (m >> 1)) * 128 + b0) * 32;
                        mbar_expect_tx(full, bytes);
                        bulk_g2s(dst + (b0 - bbase) * 512, src, bytes, full);
                    }
                    r.next();
                }
            }
            {
                mbar_wait(sb + B_EREADY, 0);
                unsigned epoch; asm volatile("ld.shared.u32 %0, [%1];" : "=r"(epoch) : "r"(sb + EPOCH_OFF) : "memory");
                uint32_t pending = 0xFFu & ~(1u << tj), ready = 0;
                mbar_wait(sb + B_HSUM, 0);
#pragma unroll 1
                for (int m = 0; m < N_O; m++) {
                    const uint32_t full = sb + B_FULL + 8 * r.slot, dst = sb + RING_OFF + r.slot * SLOT;
                    PWAIT();
                    for (int it = 0; it < (1 << 20) && !ready; it++) {
                        bool ok = false;
                        if (lane < 8 && ((pending >> lane) & 1)) ok = (int)(ld_acquire(&g_ocnt[(ti * 8 + lane) * 32]) - 8 * (epoch + 1)) >= 0;
                        ready = __ballot_sync(0xffffffffu, ok);
                        if (!ready) __nanosleep(100);
                    }
                    const int js = ready ? __ffs(ready) - 1 : __ffs(pending) - 1;
                    pending &= ~(1u << js); ready &= ~(1u << js);
                    asm volatile("fence.proxy.async.global;" ::: "memory");
                    if (leader) {
                        asm volatile("st.shared.u32 [%0], %1;" :: "r"(sb + OSRC_OFF + 4 * m), "r"(js) : "memory");
                        mbar_expect_tx(full, 16384);
                        tma_2d(dst, &map_o, full, 64 * js, ti * 128);
                    }
                    r.next();
                }
            }
        } else if (warp == 9) {
            unsigned epoch = 0;
            if (lane == 0) {
                epoch = atomicAdd(&g_ticket, 1u) >> 7;
                asm volatile("st.shared.u32 [%0], %1;" :: "r"(sb + EPOCH_OFF), "r"(epoch) : "memory");
                mbar_arrive(sb + B_EREADY);
                mbar_wait(sb + B_XFULL + 8 * PF1_AT, 0);
                prefetch_l2(w1p + (size_t)blockIdx.x * 14336, 14336);
                mbar_wait(sb + B_XFULL + 8 * PF2_AT, 0);
                prefetch_l2(w2p + (size_t)blockIdx.x * 14336, 14336);
                prefetch_l2(wop + (size_t)blockIdx.x * 4096, 4096);
                mbar_wait(sb + B_KVDONE, 0);
                red_release(&g_kvcnt[blockIdx.x * 32], 1u);
            }
            epoch = __shfl_sync(0xffffffffu, epoch, 0);
            if (lane < 3 && ti - lane >= 0) wait_counter(&g_kvcnt[((ti - lane) * 8 + tj) * 32], epoch + 1);
            __syncwarp();
            if (lane == 0) mbar_arrive(sb + B_KVREADY);
            mbar_wait(sb + B_SQ + 24, 0);
            if (lane < 8) wait_counter(&g_pcnt[(ti * 8 + lane) * 32], epoch + 1);
            __syncwarp();
            if (lane == 0) { mbar_arrive(sb + B_PREADY); TSX(13); }
            sum_partials(sb, ti, tj, lane);
            if (lane == 0) TSX(14);
        } else {
            if (warp == 10) {
#pragma unroll 1
                for (int q = 0; q < 4; q++) {
                    mbar_wait(sb + B_SQ + 8 * q, 0);
                    if (lane < 16) {
                        uint4* d = g_part + (size_t)(((ti * 8 + 2 * q + (lane & 1)) * 8 + tj) * 8 + (lane >> 1)) * 128;
                        bulk_s2g(d, sb + STG_OFF + (q & 1) * 32768 + lane * 2048, 2048);
                        asm volatile("cp.async.bulk.commit_group;" ::: "memory");
                        asm volatile("cp.async.bulk.wait_group.read 0;" ::: "memory");
                    }
                    __syncwarp();
                    if (lane == 0) mbar_arrive(sb + B_SF + 8 * (q & 1));
                }
                asm volatile("cp.async.bulk.wait_group 0;" ::: "memory");
                asm volatile("fence.proxy.async.global;" ::: "memory");
                __syncwarp();
                if (lane == 0) { red_release(&g_pcnt[blockIdx.x * 32], 1u); TSX(12); }
            }
            mbar_wait(sb + B_PREADY, 0);
            sum_partials(sb, ti, tj, lane);
        }
    } else {
        asm volatile("setmaxnreg.inc.sync.aligned.u32 208;");
        const int wg = warp >> 2, g = lane >> 2, c = lane & 3;
        const uint32_t xa = sb + X_OFF + wg * 8192;
        Ring r{0, 0};
        const bool lane0 = lane == 0 && !dry;
        uint32_t qf[4][4];
        float g0, g1;
        TS(9);
        {
            float acc[100];
            int prev = 0;
            if (wg == 1) asm volatile("bar.sync 3, 256;" ::: "memory");
            for (int s = 0; s < (dry ? 4 : N_QKV); s++) {
                if (!(s & 1) && !dry) mbar_wait(sb + B_XFULL + 8 * (s >> 1), 0);
                CWAIT();
                if (s == 0) TS(1);
                if (s == 2) TS(28);
                if (s == 6) TS(29);
                if (s == 10) TS(20);
                const uint32_t bs = sb + RING_OFF + r.slot * SLOT, as = xa + (s >> 1) * 16384 + (s & 1) * 64;
                wgmma_fence();
                wgmma_ss_n200(acc, desc_a(as), desc_b(bs), s);
                wgmma_ss_n200(acc, desc_a(as + 32), desc_b(bs + 2048), 1);
                wgmma_commit();
                if (wg == 0 && s == LEAD1) asm volatile("bar.arrive 3, 256;" ::: "memory");
                if (s > 0) { wgmma_wait<1>(); if (lane0) mbar_arrive(sb + B_EMPTY + 8 * prev); }
                prev = r.slot; r.next();
            }
            wgmma_wait<0>();
            fence_acc(acc);
            if (lane0) mbar_arrive(sb + B_EMPTY + 8 * prev);
            TS(2);
            const int blk = ti * 8 + warp;
#pragma unroll
            for (int hh = 0; hh < 4; hh++) {
                const float* t0 = &acc[8 * hh]; const float* t1 = &acc[8 * hh + 4];
                qf[hh][0] = pack_bf16(t0[0], t0[1]); qf[hh][1] = pack_bf16(t0[2], t0[3]);
                qf[hh][2] = pack_bf16(t1[0], t1[1]); qf[hh][3] = pack_bf16(t1[2], t1[3]);
                const float* k0 = &acc[32 + 8 * hh]; const float* k1 = &acc[32 + 8 * hh + 4];
                uint4 kv;
                kv.x = pack_bf16(k0[0], k0[1]); kv.y = pack_bf16(k1[0], k1[1]);
                kv.z = pack_bf16(k0[2], k0[3]); kv.w = pack_bf16(k1[2], k1[3]);
                if (!dry) g_kf[((tj * 4 + hh) * 128 + blk) * 32 + lane] = kv;
                const float* v0 = &acc[64 + 8 * hh]; const float* v1 = &acc[64 + 8 * hh + 4];
                uint4 vv;
                vv.x = movmatrix(pack_bf16(v0[0], v0[1])); vv.y = movmatrix(pack_bf16(v0[2], v0[3]));
                vv.z = movmatrix(pack_bf16(v1[0], v1[1])); vv.w = movmatrix(pack_bf16(v1[2], v1[3]));
                if (!dry) g_vf[((tj * 4 + hh) * 128 + blk) * 32 + lane] = vv;
            }
            __syncwarp();
            if (lane0) mbar_arrive(sb + B_KVDONE);
            const float z0 = __shfl_sync(0xffffffffu, acc[96], lane & ~3), z1 = __shfl_sync(0xffffffffu, acc[98], lane & ~3);
            g0 = 1.f / (1.f + __expf(-z0)); g1 = 1.f / (1.f + __expf(-z1));
        }
        TS(3);
        const int wrow = (warp & 3) * 16;
        {
            float acc[112];
            int prev = 0;
            for (int s = 0; s < (dry ? 4 : N_FFN1); s++) {
                CWAIT();
                const uint32_t bs = sb + RING_OFF + r.slot * SLOT, as = xa + (s >> 1) * 16384 + (s & 1) * 64;
                wgmma_fence();
                wgmma_ss_n224(acc, desc_a(as), desc_b(bs), s);
                wgmma_ss_n224(acc, desc_a(as + 32), desc_b(bs + 2048), 1);
                wgmma_commit();
                if (s > 0) { wgmma_wait<1>(); if (lane0) mbar_arrive(sb + B_EMPTY + 8 * prev); }
                prev = r.slot; r.next();
            }
            wgmma_wait<0>();
            fence_acc(acc);
            if (lane0) mbar_arrive(sb + B_EMPTY + 8 * prev);
            TS(4);
            const float s0 = 1.f - g0, s1 = 1.f - g1;
            asm volatile("bar.sync %0, 128;" :: "r"(1 + wg) : "memory");
            const uint32_t strow = xa + (wrow + ((lane >> 3) & 1) * 8 + (lane & 7)) * 128;
#pragma unroll
            for (int p = 0; p < 14; p++) {
                const int nt = 2 * p + (lane >> 4);
                const float* a = &acc[8 * p];
                stmatrix_x4(strow + (p >> 2) * 16384 + (((nt & 7) ^ (lane & 7)) << 4),
                            pack_bf16_relu(a[0] * s0, a[1] * s0), pack_bf16_relu(a[2] * s1, a[3] * s1),
                            pack_bf16_relu(a[4] * s0, a[5] * s0), pack_bf16_relu(a[6] * s1, a[7] * s1));
            }
        }
        TS(5);
        {
            fence_async_smem();
            asm volatile("bar.sync 4, 256;" ::: "memory");
            float accA[64], accB[64];
            auto epilogue = [&](float (&acc)[64], int q) {
                fence_acc(acc);
                const uint32_t st = sb + STG_OFF + (q & 1) * 32768 + warp * 4096;
                if (q >= 2 && !dry) mbar_wait(sb + B_SF + 8 * (q & 1), 0);
#pragma unroll
                for (int t2 = 0; t2 < 8; t2++) {
                    uint4 v;
                    v.x = pack_bf16(acc[8 * t2 + 0], acc[8 * t2 + 1]); v.y = pack_bf16(acc[8 * t2 + 2], acc[8 * t2 + 3]);
                    v.z = pack_bf16(acc[8 * t2 + 4], acc[8 * t2 + 5]); v.w = pack_bf16(acc[8 * t2 + 6], acc[8 * t2 + 7]);
                    sts128(st + t2 * 512 + lane * 16, v);
                }
                fence_async_smem();
                __syncwarp();
                if (lane0) mbar_arrive(sb + B_SQ + 8 * q);
            };
            int rel = r.slot;
#pragma unroll
            for (int m = 0; m < N_FFN2; m++) {
                CWAIT();
                wgmma_fence();
#pragma unroll
                for (int h = 0; h < 2; h++) {
                    const int u = 2 * m + h, q = u / 7, rr = u % 7;
                    const uint32_t bs = sb + RING_OFF + r.slot * SLOT + h * 8192;
                    const uint32_t as = xa + (rr >> 1) * 16384 + (rr & 1) * 64;
                    if (!(q & 1)) {
                        wgmma_ss_n128(accA, desc_a(as), desc_b(bs), rr);
                        wgmma_ss_n128(accA, desc_a(as + 32), desc_b(bs + 2048), 1);
                    } else {
                        wgmma_ss_n128(accB, desc_a(as), desc_b(bs), rr);
                        wgmma_ss_n128(accB, desc_a(as + 32), desc_b(bs + 2048), 1);
                    }
                }
                wgmma_commit();
                r.next();
                wgmma_wait<1>();
                if (m > 0) {
                    if (lane0) mbar_arrive(sb + B_EMPTY + 8 * rel);
                    if (++rel == RING) rel = 0;
                }
                if (m == 4) { TS(25); epilogue(accA, 0); }
                if (m == 7) { TS(26); epilogue(accB, 1); }
                if (m == 11) { TS(27); epilogue(accA, 2); }
            }
            wgmma_wait<0>();
            if (lane0) { mbar_arrive(sb + B_EMPTY + 8 * rel); mbar_arrive(sb + B_HDEAD); }
            epilogue(accB, 3);
        }
        TS(6);
        {
            const float SC = 0.25f * 1.4426950408889634f;
            const int gb0 = 8 * ti - 16 + warp;
            int slotK = 0, slotV = 0;
            const uint32_t ostore = sb + OWN_OFF + (warp * 16 + ((lane >> 3) & 1) * 8 + (lane & 7)) * 128;
            uint32_t* odst = reinterpret_cast<uint32_t*>(g_o + (size_t)(ti * 128 + warp * 16 + g) * 512 + tj * 64 + ((lane & 1) ? 8 : 0) + (lane & 2) * 2);
#define NHEADS (dry ? 2 : 4)
#define ATT_KWAIT(kb) do { slotK = r.slot; CWAIT(); kb = sb + RING_OFF + slotK * SLOT + warp * 512 + lane * 16; r.next(); } while (0)
#define ATT_VWAIT(vb) do { slotV = r.slot; CWAIT(); vb = sb + RING_OFF + slotV * SLOT + warp * 512 + lane * 16; r.next(); TS(21 + hh); } while (0)
#define ATT_KREL() do { __syncwarp(); if (lane0) mbar_arrive(sb + B_EMPTY + 8 * slotK); } while (0)
#define ATT_VREL() do { __syncwarp(); if (lane0) mbar_arrive(sb + B_EMPTY + 8 * slotV); } while (0)
#define ATT_NEXTQ(h) do { \
                if ((h) == 1) { q0 = qf[1][0]; q1 = qf[1][1]; q2 = qf[1][2]; q3 = qf[1][3]; } \
                else if ((h) == 2) { q0 = qf[2][0]; q1 = qf[2][1]; q2 = qf[2][2]; q3 = qf[2][3]; } \
                else { q0 = qf[3][0]; q1 = qf[3][1]; q2 = qf[3][2]; q3 = qf[3][3]; } } while (0)
#define ATT_STORE(h, r0, r1, r2, r3) do { \
                if ((h) == 0 && !dry) mbar_wait(sb + B_SF + 8, 1);        \
                stmatrix_x4(ostore + (((2 * (h) + (lane >> 4)) ^ (lane & 7)) << 4), r0, r1, r2, r3); \
                const bool odd = lane & 1; \
                const uint32_t sl = __shfl_xor_sync(0xffffffffu, odd ? (r0) : (r2), 1), sh = __shfl_xor_sync(0xffffffffu, odd ? (r1) : (r3), 1); \
                if (!dry) *reinterpret_cast<uint2*>(odst + 8 * (h)) = odd ? make_uint2(sl, r2) : make_uint2(r0, sl); \
                if (!dry) *reinterpret_cast<uint2*>(odst + 8 * (h) + 8 * 256) = odd ? make_uint2(sh, r3) : make_uint2(r1, sh); \
                } while (0)
            auto attention = [&](auto masked_tag) {
            constexpr bool MASKED = decltype(masked_tag)::value;
            const float NEG = -INFINITY;
            const uint32_t ONES = 0x3F803F80u;
            float sa[8][2][4];
            float o[2][4], ls[4];
            float m0, m1;
            uint32_t q0 = qf[0][0], q1 = qf[0][1], q2 = qf[0][2], q3 = qf[0][3];
            auto qk = [&](float (&s)[8][2][4], int ps, int t, uint32_t kbase, bool merged) {
                if (merged) {
                    const uint4 kd = lds128(kbase + 16 * 512);
                    const uint4 kf = lds128(kbase);
                    float f[2][4];
                    const float ci = (!MASKED || opaque(gb0) >= 0) ? 0.f : NEG;
                    mma16816_c(s[0][0], q0, q1, q2, q3, kd.x, kd.y, 0.f);
                    mma16816_c(s[0][1], q0, q1, q2, q3, kd.z, kd.w, 0.f);
                    mma16816_c(f[0], q0, q1, q2, q3, kf.x, kf.y, ci);
                    mma16816_c(f[1], q0, q1, q2, q3, kf.z, kf.w, ci);
#pragma unroll
                    for (int u = 0; u < 2; u++)
#pragma unroll
                        for (int e = 0; e < 4; e++) {
                            const int row = g + 8 * (e >> 1), col = 8 * u + 2 * c + (e & 1);
                            s[0][u][e] = (col > row) ? f[u][e] : s[0][u][e];
                        }
                } else {
                    const uint4 kf = lds128(kbase + (8 * ps + t) * 512);
                    const float ci = (!MASKED || opaque(gb0) + 8 * ps + t >= 0) ? 0.f : NEG;
                    mma16816_c(s[t][0], q0, q1, q2, q3, kf.x, kf.y, ci);
                    mma16816_c(s[t][1], q0, q1, q2, q3, kf.z, kf.w, ci);
                }
            };
            auto rowmax = [&](float (&s)[8][2][4], float b0, float b1, float& n0, float& n1) {
                int i0 = __float_as_int(b0), i1 = __float_as_int(b1);
#pragma unroll
                for (int t = 0; t < 8; t++)
#pragma unroll
                    for (int u = 0; u < 2; u++) {
                        i0 = __vimax3_s32(i0, __float_as_int(s[t][u][0]), __float_as_int(s[t][u][1]));
                        i1 = __vimax3_s32(i1, __float_as_int(s[t][u][2]), __float_as_int(s[t][u][3]));
                    }
                i0 = max(i0, __shfl_xor_sync(0xffffffffu, i0, 1)); i1 = max(i1, __shfl_xor_sync(0xffffffffu, i1, 1));
                i0 = max(i0, __shfl_xor_sync(0xffffffffu, i0, 2)); i1 = max(i1, __shfl_xor_sync(0xffffffffu, i1, 2));
                n0 = __int_as_float(i0); n1 = __int_as_float(i1);
                if (__any_sync(0xffffffffu, (i0 | i1) < 0)) {
                    asm volatile("" ::: "memory");
                    n0 = b0; n1 = b1;
#pragma unroll
                    for (int t = 0; t < 8; t++)
#pragma unroll
                        for (int u = 0; u < 2; u++) {
                            n0 = fmaxf(n0, fmaxf(s[t][u][0], s[t][u][1]));
                            n1 = fmaxf(n1, fmaxf(s[t][u][2], s[t][u][3]));
                        }
                    n0 = fmaxf(n0, __shfl_xor_sync(0xffffffffu, n0, 1)); n1 = fmaxf(n1, __shfl_xor_sync(0xffffffffu, n1, 1));
                    n0 = fmaxf(n0, __shfl_xor_sync(0xffffffffu, n0, 2)); n1 = fmaxf(n1, __shfl_xor_sync(0xffffffffu, n1, 2));
                }
            };
            auto pv = [&](const float (&p)[2][4], uint32_t vaddr) {
                const uint4 vf = lds128(vaddr);
                const uint32_t a0 = pack_bf16(p[0][0], p[0][1]), a1 = pack_bf16(p[0][2], p[0][3]);
                const uint32_t a2 = pack_bf16(p[1][0], p[1][1]), a3 = pack_bf16(p[1][2], p[1][3]);
                mma16816(o[0], a0, a1, a2, a3, vf.x, vf.y);
                mma16816(o[1], a0, a1, a2, a3, vf.z, vf.w);
                mma16816(ls, a0, a1, a2, a3, ONES, ONES);
            };
            auto expv = [&](float (&s)[8][2][4], int ps, int t, float mc0, float mc1, uint32_t vbase, bool merged) {
                float p[2][4];
#pragma unroll
                for (int u = 0; u < 2; u++) {
                    p[u][0] = ex2(fmaf(s[t][u][0], SC, -mc0)); p[u][1] = ex2(fmaf(s[t][u][1], SC, -mc0));
                    p[u][2] = ex2(fmaf(s[t][u][2], SC, -mc1)); p[u][3] = ex2(fmaf(s[t][u][3], SC, -mc1));
                }
                if (merged) {
                    float pd[2][4], pf[2][4];
#pragma unroll
                    for (int u = 0; u < 2; u++)
#pragma unroll
                        for (int e = 0; e < 4; e++) {
                            const int row = g + 8 * (e >> 1), col = 8 * u + 2 * c + (e & 1);
                            pf[u][e] = (col > row) ? p[u][e] : 0.f;
                            pd[u][e] = (col > row) ? 0.f : p[u][e];
                        }
                    pv(pd, vbase + 16 * 512);
                    pv(pf, vbase);
                } else {
                    pv(p, vbase + (8 * ps + t) * 512);
                }
            };
            uint32_t kbase = 0, vbase = 0;
            m0 = NEG; m1 = NEG;
#pragma unroll 1
            for (int it = 0; it < 2 * NHEADS; it++) {
                const int hh = it >> 1, ps = it & 1;
                if (ps == 0) {
                    ATT_KWAIT(kbase);
                    if (hh > 0) ATT_NEXTQ(hh);
                    qk(sa, 0, 0, kbase, true);
                } else {
                    qk(sa, 1, 0, kbase, false);
                }
#pragma unroll
                for (int t = 1; t < 8; t++) qk(sa, ps, t, kbase, false);
                if (ps == 1) ATT_KREL();
                float n0, n1;
                rowmax(sa, m0, m1, n0, n1);
                if (ps == 0) {
                    ATT_VWAIT(vbase);
#pragma unroll
                    for (int e = 0; e < 4; e++) { o[0][e] = 0.f; o[1][e] = 0.f; ls[e] = 0.f; }
                } else {
                    const float a0 = ex2((m0 - n0) * SC), a1 = ex2((m1 - n1) * SC);
                    ls[0] *= a0; ls[2] *= a1;
                    o[0][0] *= a0; o[0][1] *= a0; o[1][0] *= a0; o[1][1] *= a0;
                    o[0][2] *= a1; o[0][3] *= a1; o[1][2] *= a1; o[1][3] *= a1;
                }
                const float mc0 = n0 * SC, mc1 = n1 * SC;
                if (ps == 0) expv(sa, 0, 0, mc0, mc1, vbase, true); else expv(sa, 1, 0, mc0, mc1, vbase, false);
#pragma unroll
                for (int t = 1; t < 8; t++) expv(sa, ps, t, mc0, mc1, vbase, false);
                if (ps == 0) { m0 = n0; m1 = n1; }
                else {
                    ATT_VREL();
                    m0 = NEG; m1 = NEG;
                    const float f0 = __fdividef(g0, ls[0]), f1 = __fdividef(g1, ls[2]);
                    ATT_STORE(hh, pack_bf16(o[0][0] * f0, o[0][1] * f0), pack_bf16(o[0][2] * f1, o[0][3] * f1),
                                  pack_bf16(o[1][0] * f0, o[1][1] * f0), pack_bf16(o[1][2] * f1, o[1][3] * f1));
                }
            }
            };
            if (ti >= 2) attention(BoolTag<false>{}); else attention(BoolTag<true>{});
            fence_async_smem();
            __syncwarp();
            if (lane0) { mbar_arrive(sb + B_ODONE); red_release(&g_ocnt[blockIdx.x * 32], 1u); }
        }
        TS(7);
        {
            float acc[32];
            uint4 pv[4][4];
            if (!dry) mbar_wait(sb + B_PREADY, 0);
            {
                const uint4* p = g_part + (size_t)((ti * 8 + tj) * 8 + 4) * 1024 + warp * 128 + lane;
#pragma unroll
                for (int s = 0; s < 4; s++)
#pragma unroll
                    for (int n = 0; n < 4; n++) pv[n][s] = dry ? make_uint4(0u, 0u, 0u, 0u) : ldg_weak(p + s * 1024 + n * 32);
            }
            if (!dry) mbar_wait(sb + B_WOFULL, 0);
            if (!dry) mbar_wait(sb + B_ODONE, 0);
            TS(15);
            wgmma_fence();
#pragma unroll
            for (int k = 0; k < 4; k++) wgmma_ss_n64(acc, desc_a(sb + OWN_OFF + wg * 8192 + 32 * k), desc_b(sb + X_OFF + tj * 8192 + 2048 * k), k);
            wgmma_commit();
            TS(16);
#pragma unroll 1
            for (int m = 0; m < N_O; m++) {
                CWAIT();
                uint32_t js; asm volatile("ld.shared.u32 %0, [%1];" : "=r"(js) : "r"(sb + OSRC_OFF + 4 * m) : "memory");
                const uint32_t as = sb + RING_OFF + r.slot * SLOT + wg * 8192;
                const uint32_t bs = sb + X_OFF + (js & 7) * 8192;
                wgmma_fence();
#pragma unroll
                for (int k = 0; k < 4; k++) wgmma_ss_n64(acc, desc_a(as + 32 * k), desc_b(bs + 2048 * k), 1);
                wgmma_commit();
                if (m == 0) { wgmma_wait<0>(); if (lane0) mbar_arrive(sb + B_EMPTY + 8 * r.slot); }
                r.next();
            }
            float base[32];
            if (!dry) mbar_wait(sb + B_HSUM, 0);
#pragma unroll
            for (int n = 0; n < 4; n++) {
                const uint4 u0 = lds128(sb + STG_OFF + (warp * 8 + 2 * n) * 512 + lane * 16), u1 = lds128(sb + STG_OFF + (warp * 8 + 2 * n + 1) * 512 + lane * 16);
                float* a = &base[8 * n];
                a[0] = __uint_as_float(u0.x); a[1] = __uint_as_float(u0.y); a[2] = __uint_as_float(u0.z); a[3] = __uint_as_float(u0.w);
                a[4] = __uint_as_float(u1.x); a[5] = __uint_as_float(u1.y); a[6] = __uint_as_float(u1.z); a[7] = __uint_as_float(u1.w);
#pragma unroll
                for (int s = 0; s < 4; s++) {
                    a[0] += bf_lo(pv[n][s].x); a[1] += bf_hi(pv[n][s].x); a[2] += bf_lo(pv[n][s].y); a[3] += bf_hi(pv[n][s].y);
                    a[4] += bf_lo(pv[n][s].z); a[5] += bf_hi(pv[n][s].z); a[6] += bf_lo(pv[n][s].w); a[7] += bf_hi(pv[n][s].w);
                }
            }
            fence_acc(base);
            wgmma_wait<0>();
            fence_acc(acc);
            TS(17);
#pragma unroll
            for (int k = 0; k < 32; k++) acc[k] += base[k];
            __nv_bfloat16* o = out + (size_t)(ti * 128 + warp * 16 + g) * 512 + tj * 64 + ((lane & 1) ? 8 : 0) + (lane & 2) * 2;
            const bool odd = lane & 1;
#pragma unroll
            for (int t2 = 0; t2 < 4; t2++) {
                const uint32_t lo0 = pack_bf16(acc[8 * t2 + 0], acc[8 * t2 + 1]), hi0 = pack_bf16(acc[8 * t2 + 2], acc[8 * t2 + 3]);
                const uint32_t lo1 = pack_bf16(acc[8 * t2 + 4], acc[8 * t2 + 5]), hi1 = pack_bf16(acc[8 * t2 + 6], acc[8 * t2 + 7]);
                const uint32_t sl = __shfl_xor_sync(0xffffffffu, odd ? lo0 : lo1, 1), sh = __shfl_xor_sync(0xffffffffu, odd ? hi0 : hi1, 1);
                if (!dry) *reinterpret_cast<uint2*>(o + 16 * t2) = odd ? make_uint2(sl, lo1) : make_uint2(lo0, sl);
                if (!dry) *reinterpret_cast<uint2*>(o + 16 * t2 + 8 * 512) = odd ? make_uint2(sh, hi1) : make_uint2(hi0, sh);
            }
            if (tid == 0 && !dry) TSG(30);
        }
        TS(8);
    }
}

typedef CUresult (*PFN_encodeTiled)(CUtensorMap*, CUtensorMapDataType, cuuint32_t, void*, const cuuint64_t*, const cuuint64_t*,
                                    const cuuint32_t*, const cuuint32_t*, CUtensorMapInterleave, CUtensorMapSwizzle,
                                    CUtensorMapL2promotion, CUtensorMapFloatOOBfill);

void make_map(PFN_encodeTiled enc, CUtensorMap* m, const void* base, int rank, const cuuint64_t* dims, const cuuint64_t* strides, const cuuint32_t* box) {
    cuuint32_t es[5] = {1, 1, 1, 1, 1};
    enc(m, CU_TENSOR_MAP_DATA_TYPE_BFLOAT16, (cuuint32_t)rank, const_cast<void*>(base), dims, strides, box, es,
        CU_TENSOR_MAP_INTERLEAVE_NONE, CU_TENSOR_MAP_SWIZZLE_128B, CU_TENSOR_MAP_L2_PROMOTION_L2_256B, CU_TENSOR_MAP_FLOAT_OOB_FILL_NONE);
}

}

extern "C" void kernel_launch(void* const* d_in, const int* in_sizes, int n_in, void* d_out, int out_size) {
    (void)in_sizes; (void)n_in; (void)out_size;
    const void* x = d_in[0]; const void* wqkv = d_in[1]; const void* wo = d_in[2];
    const void* w1 = d_in[4]; const void* w2 = d_in[5]; const void* gate_w = d_in[6];
    static PFN_encodeTiled enc = nullptr;
    if (!enc) {
        void* fn = nullptr; cudaDriverEntryPointQueryResult st;
        cudaGetDriverEntryPoint("cuTensorMapEncodeTiled", &fn, cudaEnableDefault, &st);
        enc = (PFN_encodeTiled)fn;
        cudaFuncSetAttribute(fused_kernel, cudaFuncAttributeMaxDynamicSharedMemorySize, SMEM_BYTES);
    }
    CUtensorMap mx, mqkv, mw1, mw2, mwo, mw1a, mo;
    void* optr = nullptr;
    cudaGetSymbolAddress(&optr, g_o);
    { cuuint64_t d[2] = {512, 2048}, s[1] = {1024}; cuuint32_t b[2] = {64, 128}; make_map(enc, &mo, optr, 2, d, s, b); }
    { cuuint64_t d[4] = {64, 512, 3, 8}, s[3] = {3584, 128, 448}; cuuint32_t b[4] = {64, 32, 3, 1}; make_map(enc, &mw1a, w1, 4, d, s, b); }
    { cuuint64_t d[2] = {512, 2048}, s[1] = {1024}; cuuint32_t b[2] = {64, 128}; make_map(enc, &mx, x, 2, d, s, b); }
    { cuuint64_t d[4] = {64, 512, 8, 3}, s[3] = {3072, 128, 1024}; cuuint32_t b[4] = {64, 32, 1, 3}; make_map(enc, &mqkv, wqkv, 4, d, s, b); }
    { cuuint64_t d[2] = {1792, 512}, s[1] = {3584}; cuuint32_t b[2] = {64, 32}; make_map(enc, &mw1, w1, 2, d, s, b); }
    { cuuint64_t d[3] = {64, 1792, 8}, s[2] = {1024, 128}; cuuint32_t b[3] = {64, 32, 2}; make_map(enc, &mw2, w2, 3, d, s, b); }
    { cuuint64_t d[2] = {512, 512}, s[1] = {1024}; cuuint32_t b[2] = {64, 256}; make_map(enc, &mwo, wo, 2, d, s, b); }
    fused_kernel<<<NCTA, 384, SMEM_BYTES, cudaStreamPerThread>>>(mx, mqkv, mw1, mw2, mwo, mw1a, mo, (const __nv_bfloat16*)gate_w, (__nv_bfloat16*)d_out,
                                           (const uint8_t*)w1, (const uint8_t*)w2, (const uint8_t*)wo);
}
```

```cpp
#include <cuda_runtime.h>
#include <cuda_bf16.h>
#include <cuda.h>
#include <stdint.h>

namespace {

#define PF1_AT 1
#define PF2_AT 5
#define LEAD1 2
#define NCTA 132
constexpr int RING = 6;
constexpr int SLOT = 16384;
constexpr uint32_t X_OFF = 0;
constexpr uint32_t STG_OFF = X_OFF + 4 * 16384;
constexpr uint32_t RING_OFF = 131072;
constexpr uint32_t BAR_OFF = RING_OFF + RING * SLOT;
constexpr uint32_t B_FULL = BAR_OFF, B_EMPTY = BAR_OFF + 64, B_XFULL = BAR_OFF + 128, B_HDEAD = BAR_OFF + 192,
                   B_EREADY = BAR_OFF + 200, B_KVDONE = BAR_OFF + 208, B_ODONE = BAR_OFF + 224,
                   B_KVREADY = BAR_OFF + 232, B_WOFULL = BAR_OFF + 240, B_HSUM = BAR_OFF + 248, B_PREADY = BAR_OFF + 264,
                   B_SQ = BAR_OFF + 272, B_SF = BAR_OFF + 304;
constexpr uint32_t EPOCH_OFF = BAR_OFF + 256, ITEM_OFF = BAR_OFF + 260, OSRC_OFF = BAR_OFF + 384;
constexpr uint32_t OWN_OFF = X_OFF + 6 * 16384;
constexpr uint32_t SMEM_BYTES = BAR_OFF + 1024;

constexpr int N_QKV = 16, N_FFN1 = 16, N_FFN2 = 14, N_KV = 8, N_O = 7;

__device__ uint4 g_kf[32 * 128 * 32];
__device__ uint4 g_vf[32 * 128 * 32];
__device__ uint4 g_part[16 * 8 * 8 * 8 * 4 * 32];
__device__ __nv_bfloat16 g_o[2048 * 512];
__device__ unsigned g_ticket;
__device__ unsigned g_kvcnt[128 * 32];
__device__ unsigned g_pcnt[128 * 32];
__device__ unsigned g_ocnt[128 * 32];
#define TS(k) do {} while (0)
#define TS2(k) do {} while (0)
#define TS2X(k) do {} while (0)
#define TSX(k) do {} while (0)
#define TSG(k) do {} while (0)

__device__ __forceinline__ uint32_t smem_u32(const void* p) { return (uint32_t)__cvta_generic_to_shared(p); }
__device__ __forceinline__ void mbar_init(uint32_t bar, uint32_t cnt) { asm volatile("mbarrier.init.shared::cta.b64 [%0], %1;" :: "r"(bar), "r"(cnt) : "memory"); }
__device__ __forceinline__ void mbar_expect_tx(uint32_t bar, uint32_t bytes) { asm volatile("mbarrier.arrive.expect_tx.shared::cta.b64 _, [%0], %1;" :: "r"(bar), "r"(bytes) : "memory"); }
__device__ __forceinline__ void mbar_expect_only(uint32_t bar, uint32_t bytes) { asm volatile("mbarrier.expect_tx.relaxed.cta.shared::cta.b64 [%0], %1;" :: "r"(bar), "r"(bytes) : "memory"); }
__device__ __forceinline__ void mbar_arrive(uint32_t bar) { asm volatile("mbarrier.arrive.shared::cta.b64 _, [%0];" :: "r"(bar) : "memory"); }
__device__ __forceinline__ void mbar_wait(uint32_t bar, uint32_t parity) {
    asm volatile("{\n.reg .pred P1, P2;\n.reg .u32 n;\nmov.u32 n, 0;\n"
                 "WAIT_LOOP:\n"
                 "mbarrier.try_wait.parity.shared::cta.b64 P1, [%0], %1;\n"
                 "@P1 bra WAIT_DONE;\n"
                 "add.u32 n, n, 1;\n"
                 "setp.lt.u32 P2, n, 0x400000;\n"
                 "@P2 bra WAIT_LOOP;\n"
                 "WAIT_DONE:\n}" :: "r"(bar), "r"(parity) : "memory");
}
__device__ __forceinline__ void tma_2d(uint32_t dst, const void* map, uint32_t bar, int c0, int c1) {
    asm volatile("cp.async.bulk.tensor.2d.shared::cluster.global.mbarrier::complete_tx::bytes [%0], [%1, {%3, %4}], [%2];"
        :: "r"(dst), "l"(map), "r"(bar), "r"(c0), "r"(c1) : "memory");
}
__device__ __forceinline__ void tma_3d(uint32_t dst, const void* map, uint32_t bar, int c0, int c1, int c2) {
    asm volatile("cp.async.bulk.tensor.3d.shared::cluster.global.mbarrier::complete_tx::bytes [%0], [%1, {%3, %4, %5}], [%2];"
        :: "r"(dst), "l"(map), "r"(bar), "r"(c0), "r"(c1), "r"(c2) : "memory");
}
__device__ __forceinline__ void tma_4d(uint32_t dst, const void* map, uint32_t bar, int c0, int c1, int c2, int c3) {
    asm volatile("cp.async.bulk.tensor.4d.shared::cluster.global.mbarrier::complete_tx::bytes [%0], [%1, {%3, %4, %5, %6}], [%2];"
        :: "r"(dst), "l"(map), "r"(bar), "r"(c0), "r"(c1), "r"(c2), "r"(c3) : "memory");
}
__device__ __forceinline__ void bulk_g2s(uint32_t dst, const void* src, uint32_t bytes, uint32_t bar) {
    asm volatile("cp.async.bulk.shared::cluster.global.mbarrier::complete_tx::bytes [%0], [%1], %2, [%3];"
        :: "r"(dst), "l"(src), "r"(bytes), "r"(bar) : "memory");
}
__device__ __forceinline__ void prefetch_l2(const void* src, uint32_t bytes) {
    asm volatile("cp.async.bulk.prefetch.L2.global [%0], %1;" :: "l"(src), "r"(bytes) : "memory");
}
__device__ __forceinline__ bool elect_one() {
    uint32_t p;
    asm volatile("{\n.reg .pred P;\nelect.sync _|P, 0xffffffff;\nselp.u32 %0, 1, 0, P;\n}" : "=r"(p));
    return p != 0;
}
__device__ __forceinline__ void wgmma_fence() { asm volatile("wgmma.fence.sync.aligned;" ::: "memory"); }
__device__ __forceinline__ void wgmma_commit() { asm volatile("wgmma.commit_group.sync.aligned;" ::: "memory"); }
template <int N> __device__ __forceinline__ void wgmma_wait() { asm volatile("wgmma.wait_group.sync.aligned %0;" :: "n"(N) : "memory"); }
__device__ __forceinline__ void fence_async_smem() { asm volatile("fence.proxy.async.shared::cta;" ::: "memory"); }
__device__ __forceinline__ uint64_t desc_a(uint32_t addr) {
    return (uint64_t)((addr & 0x3FFFF) >> 4) | ((uint64_t)1 << 16) | ((uint64_t)(1024 >> 4) << 32) | ((uint64_t)1 << 62);
}
__device__ __forceinline__ uint64_t desc_b(uint32_t addr) {
    return (uint64_t)((addr & 0x3FFFF) >> 4) | ((uint64_t)(4096 >> 4) << 16) | ((uint64_t)(1024 >> 4) << 32) | ((uint64_t)1 << 62);
}
__device__ __forceinline__ uint32_t pack_bf16(float lo, float hi) {
    uint32_t r; asm("cvt.rn.bf16x2.f32 %0, %1, %2;" : "=r"(r) : "f"(hi), "f"(lo)); return r;
}
__device__ __forceinline__ uint32_t pack_bf16_relu(float lo, float hi) {
    uint32_t r; asm("cvt.rn.relu.bf16x2.f32 %0, %1, %2;" : "=r"(r) : "f"(hi), "f"(lo)); return r;
}
__device__ __forceinline__ uint32_t movmatrix(uint32_t a) {
    uint32_t d; asm volatile("movmatrix.sync.aligned.m8n8.trans.b16 %0, %1;" : "=r"(d) : "r"(a)); return d;
}
__device__ __forceinline__ void stmatrix_x4(uint32_t addr, uint32_t r0, uint32_t r1, uint32_t r2, uint32_t r3) {
    asm volatile("stmatrix.sync.aligned.m8n8.x4.shared.b16 [%0], {%1, %2, %3, %4};" :: "r"(addr), "r"(r0), "r"(r1), "r"(r2), "r"(r3) : "memory");
}
__device__ __forceinline__ uint4 lds128(uint32_t addr) {
    uint4 v; asm volatile("ld.shared.v4.b32 {%0, %1, %2, %3}, [%4];" : "=r"(v.x), "=r"(v.y), "=r"(v.z), "=r"(v.w) : "r"(addr) : "memory"); return v;
}
__device__ __forceinline__ void mma16816(float (&c)[4], uint32_t a0, uint32_t a1, uint32_t a2, uint32_t a3, uint32_t b0, uint32_t b1) {
    asm volatile("mma.sync.aligned.m16n8k16.row.col.f32.bf16.bf16.f32 {%0,%1,%2,%3}, {%4,%5,%6,%7}, {%8,%9}, {%0,%1,%2,%3};"
        : "+f"(c[0]), "+f"(c[1]), "+f"(c[2]), "+f"(c[3]) : "r"(a0), "r"(a1), "r"(a2), "r"(a3), "r"(b0), "r"(b1));
}
__device__ __forceinline__ void mma16816_c(float (&c)[4], uint32_t a0, uint32_t a1, uint32_t a2, uint32_t a3, uint32_t b0, uint32_t b1, float ci) {
    asm volatile("mma.sync.aligned.m16n8k16.row.col.f32.bf16.bf16.f32 {%0,%1,%2,%3}, {%4,%5,%6,%7}, {%8,%9}, {%10,%10,%10,%10};"
        : "=f"(c[0]), "=f"(c[1]), "=f"(c[2]), "=f"(c[3]) : "r"(a0), "r"(a1), "r"(a2), "r"(a3), "r"(b0), "r"(b1), "f"(ci));
}
__device__ __forceinline__ int opaque(int v) { asm volatile("" : "+r"(v)); return v; }
__device__ __forceinline__ float ex2(float x) { float y; asm("ex2.approx.ftz.f32 %0, %1;" : "=f"(y) : "f"(x)); return y; }
__device__ __forceinline__ unsigned ld_acquire(const unsigned* p) {
    unsigned v; asm volatile("ld.acquire.gpu.global.u32 %0, [%1];" : "=r"(v) : "l"(p) : "memory"); return v;
}
__device__ __forceinline__ void red_release(unsigned* p, unsigned v) {
    asm volatile("red.release.gpu.global.add.u32 [%0], %1;" :: "l"(p), "r"(v) : "memory");
}
__device__ __forceinline__ void wait_counter(const unsigned* p, unsigned target) {
    uint32_t n = 0;
    while ((int)(ld_acquire(p) - target) < 0) { if (++n > (1u << 20)) break; }
}
__device__ __forceinline__ uint4 ldg_weak(const uint4* p) {
    uint4 v; asm volatile("ld.global.L1::no_allocate.v4.b32 {%0, %1, %2, %3}, [%4];" : "=r"(v.x), "=r"(v.y), "=r"(v.z), "=r"(v.w) : "l"(p) : "memory"); return v;
}
__device__ __forceinline__ float bf_lo(uint32_t v) { return __uint_as_float(v << 16); }
__device__ __forceinline__ float bf_hi(uint32_t v) { return __uint_as_float(v & 0xFFFF0000u); }

__device__ __forceinline__ void wgmma_ss_n64(float (&d)[32], uint64_t da, uint64_t db, int scale_d) {
    asm volatile("{\n.reg .pred p;\nsetp.ne.b32 p, %34, 0;\n"
        "wgmma.mma_async.sync.aligned.m64n64k16.f32.bf16.bf16 {%0, %1, %2, %3, %4, %5, %6, %7, %8, %9, %10, %11, %12, %13, %14, %15, %16, %17, %18, %19, %20, %21, %22, %23, %24, %25, %26, %27, %28, %29, %30, %31}, %32, %33, p, 1, 1, 0, 1;\n}\n"
        : "+f"(d[0]), "+f"(d[1]), "+f"(d[2]), "+f"(d[3]), "+f"(d[4]), "+f"(d[5]), "+f"(d[6]), "+f"(d[7]), "+f"(d[8]), "+f"(d[9]), "+f"(d[10]), "+f"(d[11]), "+f"(d[12]), "+f"(d[13]), "+f"(d[14]), "+f"(d[15]), "+f"(d[16]), "+f"(d[17]), "+f"(d[18]), "+f"(d[19]), "+f"(d[20]), "+f"(d[21]), "+f"(d[22]), "+f"(d[23]), "+f"(d[24]), "+f"(d[25]), "+f"(d[26]), "+f"(d[27]), "+f"(d[28]), "+f"(d[29]), "+f"(d[30]), "+f"(d[31])
        : "l"(da), "l"(db), "r"(scale_d));
}
__device__ __forceinline__ void wgmma_ss_n128(float (&d)[64], uint64_t da, uint64_t db, int scale_d) {
    asm volatile("{\n.reg .pred p;\nsetp.ne.b32 p, %66, 0;\n"
        "wgmma.mma_async.sync.aligned.m64n128k16.f32.bf16.bf16 {%0, %1, %2, %3, %4, %5, %6, %7, %8, %9, %10, %11, %12, %13, %14, %15, %16, %17, %18, %19, %20, %21, %22, %23, %24, %25, %26, %27, %28, %29, %30, %31, %32, %33, %34, %35, %36, %37, %38, %39, %40, %41, %42, %43, %44, %45, %46, %47, %48, %49, %50, %51, %52, %53, %54, %55, %56, %57, %58, %59, %60, %61, %62, %63}, %64, %65, p, 1, 1, 0, 1;\n}\n"
        : "+f"(d[0]), "+f"(d[1]), "+f"(d[2]), "+f"(d[3]), "+f"(d[4]), "+f"(d[5]), "+f"(d[6]), "+f"(d[7]), "+f"(d[8]), "+f"(d[9]), "+f"(d[10]), "+f"(d[11]), "+f"(d[12]), "+f"(d[13]), "+f"(d[14]), "+f"(d[15]), "+f"(d[16]), "+f"(d[17]), "+f"(d[18]), "+f"(d[19]), "+f"(d[20]), "+f"(d[21]), "+f"(d[22]), "+f"(d[23]), "+f"(d[24]), "+f"(d[25]), "+f"(d[26]), "+f"(d[27]), "+f"(d[28]), "+f"(d[29]), "+f"(d[30]), "+f"(d[31]), "+f"(d[32]), "+f"(d[33]), "+f"(d[34]), "+f"(d[35]), "+f"(d[36]), "+f"(d[37]), "+f"(d[38]), "+f"(d[39]), "+f"(d[40]), "+f"(d[41]), "+f"(d[42]), "+f"(d[43]), "+f"(d[44]), "+f"(d[45]), "+f"(d[46]), "+f"(d[47]), "+f"(d[48]), "+f"(d[49]), "+f"(d[50]), "+f"(d[51]), "+f"(d[52]), "+f"(d[53]), "+f"(d[54]), "+f"(d[55]), "+f"(d[56]), "+f"(d[57]), "+f"(d[58]), "+f"(d[59]), "+f"(d[60]), "+f"(d[61]), "+f"(d[62]), "+f"(d[63])
        : "l"(da), "l"(db), "r"(scale_d));
}
__device__ __forceinline__ void wgmma_ss_n200(float (&d)[100], uint64_t da, uint64_t db, int scale_d) {
    asm volatile("{\n.reg .pred p;\nsetp.ne.b32 p, %102, 0;\n"
        "wgmma.mma_async.sync.aligned.m64n200k16.f32.bf16.bf16 {%0, %1, %2, %3, %4, %5, %6, %7, %8, %9, %10, %11, %12, %13, %14, %15, %16, %17, %18, %19, %20, %21, %22, %23, %24, %25, %26, %27, %28, %29, %30, %31, %32, %33, %34, %35, %36, %37, %38, %39, %40, %41, %42, %43, %44, %45, %46, %47, %48, %49, %50, %51, %52, %53, %54, %55, %56, %57, %58, %59, %60, %61, %62, %63, %64, %65, %66, %67, %68, %69, %70, %71, %72, %73, %74, %75, %76, %77, %78, %79, %80, %81, %82, %83, %84, %85, %86, %87, %88, %89, %90, %91, %92, %93, %94, %95, %96, %97, %98, %99}, %100, %101, p, 1, 1, 0, 1;\n}\n"
        : "+f"(d[0]), "+f"(d[1]), "+f"(d[2]), "+f"(d[3]), "+f"(d[4]), "+f"(d[5]), "+f"(d[6]), "+f"(d[7]), "+f"(d[8]), "+f"(d[9]), "+f"(d[10]), "+f"(d[11]), "+f"(d[12]), "+f"(d[13]), "+f"(d[14]), "+f"(d[15]), "+f"(d[16]), "+f"(d[17]), "+f"(d[18]), "+f"(d[19]), "+f"(d[20]), "+f"(d[21]), "+f"(d[22]), "+f"(d[23]), "+f"(d[24]), "+f"(d[25]), "+f"(d[26]), "+f"(d[27]), "+f"(d[28]), "+f"(d[29]), "+f"(d[30]), "+f"(d[31]), "+f"(d[32]), "+f"(d[33]), "+f"(d[34]), "+f"(d[35]), "+f"(d[36]), "+f"(d[37]), "+f"(d[38]), "+f"(d[39]), "+f"(d[40]), "+f"(d[41]), "+f"(d[42]), "+f"(d[43]), "+f"(d[44]), "+f"(d[45]), "+f"(d[46]), "+f"(d[47]), "+f"(d[48]), "+f"(d[49]), "+f"(d[50]), "+f"(d[51]), "+f"(d[52]), "+f"(d[53]), "+f"(d[54]), "+f"(d[55]), "+f"(d[56]), "+f"(d[57]), "+f"(d[58]), "+f"(d[59]), "+f"(d[60]), "+f"(d[61]), "+f"(d[62]), "+f"(d[63]), "+f"(d[64]), "+f"(d[65]), "+f"(d[66]), "+f"(d[67]), "+f"(d[68]), "+f"(d[69]), "+f"(d[70]), "+f"(d[71]), "+f"(d[72]), "+f"(d[73]), "+f"(d[74]), "+f"(d[75]), "+f"(d[76]), "+f"(d[77]), "+f"(d[78]), "+f"(d[79]), "+f"(d[80]), "+f"(d[81]), "+f"(d[82]), "+f"(d[83]), "+f"(d[84]), "+f"(d[85]), "+f"(d[86]), "+f"(d[87]), "+f"(d[88]), "+f"(d[89]), "+f"(d[90]), "+f"(d[91]), "+f"(d[92]), "+f"(d[93]), "+f"(d[94]), "+f"(d[95]), "+f"(d[96]), "+f"(d[97]), "+f"(d[98]), "+f"(d[99])
        : "l"(da), "l"(db), "r"(scale_d));
}
__device__ __forceinline__ void wgmma_ss_n224(float (&d)[112], uint64_t da, uint64_t db, int scale_d) {
    asm volatile("{\n.reg .pred p;\nsetp.ne.b32 p, %114, 0;\n"
        "wgmma.mma_async.sync.aligned.m64n224k16.f32.bf16.bf16 {%0, %1, %2, %3, %4, %5, %6, %7, %8, %9, %10, %11, %12, %13, %14, %15, %16, %17, %18, %19, %20, %21, %22, %23, %24, %25, %26, %27, %28, %29, %30, %31, %32, %33, %34, %35, %36, %37, %38, %39, %40, %41, %42, %43, %44, %45, %46, %47, %48, %49, %50, %51, %52, %53, %54, %55, %56, %57, %58, %59, %60, %61, %62, %63, %64, %65, %66, %67, %68, %69, %70, %71, %72, %73, %74, %75, %76, %77, %78, %79, %80, %81, %82, %83, %84, %85, %86, %87, %88, %89, %90, %91, %92, %93, %94, %95, %96, %97, %98, %99, %100, %101, %102, %103, %104, %105, %106, %107, %108, %109, %110, %111}, %112, %113, p, 1, 1, 0, 1;\n}\n"
        : "+f"(d[0]), "+f"(d[1]), "+f"(d[2]), "+f"(d[3]), "+f"(d[4]), "+f"(d[5]), "+f"(d[6]), "+f"(d[7]), "+f"(d[8]), "+f"(d[9]), "+f"(d[10]), "+f"(d[11]), "+f"(d[12]), "+f"(d[13]), "+f"(d[14]), "+f"(d[15]), "+f"(d[16]), "+f"(d[17]), "+f"(d[18]), "+f"(d[19]), "+f"(d[20]), "+f"(d[21]), "+f"(d[22]), "+f"(d[23]), "+f"(d[24]), "+f"(d[25]), "+f"(d[26]), "+f"(d[27]), "+f"(d[28]), "+f"(d[29]), "+f"(d[30]), "+f"(d[31]), "+f"(d[32]), "+f"(d[33]), "+f"(d[34]), "+f"(d[35]), "+f"(d[36]), "+f"(d[37]), "+f"(d[38]), "+f"(d[39]), "+f"(d[40]), "+f"(d[41]), "+f"(d[42]), "+f"(d[43]), "+f"(d[44]), "+f"(d[45]), "+f"(d[46]), "+f"(d[47]), "+f"(d[48]), "+f"(d[49]), "+f"(d[50]), "+f"(d[51]), "+f"(d[52]), "+f"(d[53]), "+f"(d[54]), "+f"(d[55]), "+f"(d[56]), "+f"(d[57]), "+f"(d[58]), "+f"(d[59]), "+f"(d[60]), "+f"(d[61]), "+f"(d[62]), "+f"(d[63]), "+f"(d[64]), "+f"(d[65]), "+f"(d[66]), "+f"(d[67]), "+f"(d[68]), "+f"(d[69]), "+f"(d[70]), "+f"(d[71]), "+f"(d[72]), "+f"(d[73]), "+f"(d[74]), "+f"(d[75]), "+f"(d[76]), "+f"(d[77]), "+f"(d[78]), "+f"(d[79]), "+f"(d[80]), "+f"(d[81]), "+f"(d[82]), "+f"(d[83]), "+f"(d[84]), "+f"(d[85]), "+f"(d[86]), "+f"(d[87]), "+f"(d[88]), "+f"(d[89]), "+f"(d[90]), "+f"(d[91]), "+f"(d[92]), "+f"(d[93]), "+f"(d[94]), "+f"(d[95]), "+f"(d[96]), "+f"(d[97]), "+f"(d[98]), "+f"(d[99]), "+f"(d[100]), "+f"(d[101]), "+f"(d[102]), "+f"(d[103]), "+f"(d[104]), "+f"(d[105]), "+f"(d[106]), "+f"(d[107]), "+f"(d[108]), "+f"(d[109]), "+f"(d[110]), "+f"(d[111])
        : "l"(da), "l"(db), "r"(scale_d));
}
template <int N> __device__ __forceinline__ void fence_acc(float (&d)[N]) {
#pragma unroll
    for (int i = 0; i < N; i++) asm volatile("" : "+f"(d[i]) :: "memory");
}

__device__ __forceinline__ void bulk_s2g(void* dst, uint32_t src, uint32_t bytes) {
    asm volatile("cp.async.bulk.global.shared::cta.bulk_group [%0], [%1], %2;" :: "l"(dst), "r"(src), "r"(bytes) : "memory");
}
__device__ __forceinline__ void sts128(uint32_t addr, uint4 v) {
    asm volatile("st.shared.v4.b32 [%0], {%1, %2, %3, %4};" :: "r"(addr), "r"(v.x), "r"(v.y), "r"(v.z), "r"(v.w) : "memory");
}
__device__ __forceinline__ void sum_partials(uint32_t sb, int ti, int tj, int lane) {
    for (;;) {
        uint32_t item = 0;
        if (lane == 0) asm volatile("atom.shared.add.u32 %0, [%1], 1;" : "=r"(item) : "r"(sb + ITEM_OFF) : "memory");
        item = __shfl_sync(0xffffffffu, item, 0);
        if (item >= 8) break;
        const uint4* p = g_part + (size_t)((ti * 8 + tj) * 8) * 1024 + item * 128 + lane;
        uint4 v[4][4];
#pragma unroll
        for (int s = 0; s < 4; s++)
#pragma unroll
            for (int n = 0; n < 4; n++) v[n][s] = ldg_weak(p + s * 1024 + n * 32);
#pragma unroll
        for (int n = 0; n < 4; n++) {
            float a[8];
#pragma unroll
            for (int e = 0; e < 8; e++) a[e] = 0.f;
#pragma unroll
            for (int s = 0; s < 4; s++) {
                a[0] += bf_lo(v[n][s].x); a[1] += bf_hi(v[n][s].x); a[2] += bf_lo(v[n][s].y); a[3] += bf_hi(v[n][s].y);
                a[4] += bf_lo(v[n][s].z); a[5] += bf_hi(v[n][s].z); a[6] += bf_lo(v[n][s].w); a[7] += bf_hi(v[n][s].w);
            }
            const uint32_t d = sb + STG_OFF + (item * 8 + n * 2) * 512 + lane * 16;
            sts128(d, make_uint4(__float_as_uint(a[0]), __float_as_uint(a[1]), __float_as_uint(a[2]), __float_as_uint(a[3])));
            sts128(d + 512, make_uint4(__float_as_uint(a[4]), __float_as_uint(a[5]), __float_as_uint(a[6]), __float_as_uint(a[7])));
        }
    }
    __syncwarp();
    if (lane == 0) mbar_arrive(sb + B_HSUM);
}

#define PWAIT() mbar_wait(sb + B_EMPTY + 8 * r.slot, r.phase)
#define CWAIT() do { if (!dry) mbar_wait(sb + B_FULL + 8 * r.slot, r.phase); } while (0)
template <bool B> struct BoolTag { static constexpr bool value = B; };
struct Ring {
    int slot; uint32_t phase;
    __device__ __forceinline__ void next() { if (++slot == RING) { slot = 0; phase ^= 1; } }
};

__global__ void __launch_bounds__(384, 1)
fused_kernel(const __grid_constant__ CUtensorMap map_x, const __grid_constant__ CUtensorMap map_qkv,
             const __grid_constant__ CUtensorMap map_w1, const __grid_constant__ CUtensorMap map_w2,
             const __grid_constant__ CUtensorMap map_wo, const __grid_constant__ CUtensorMap map_w1a,
             const __grid_constant__ CUtensorMap map_o,
             const __nv_bfloat16* __restrict__ gate_w, __nv_bfloat16* __restrict__ out,
             const uint8_t* __restrict__ w1p, const uint8_t* __restrict__ w2p, const uint8_t* __restrict__ wop)
{
    extern __shared__ __align__(1024) uint8_t smem_raw[];
    const uint32_t sb = smem_u32(smem_raw);
    const int tid = threadIdx.x, warp = tid >> 5, lane = tid & 31;
    const bool dry = blockIdx.x >= 128;
    const int ti = dry ? (int)(blockIdx.x & 1) * 2 : blockIdx.x >> 3, tj = blockIdx.x & 7;
    if (dry && warp >= 8) {
        asm volatile("setmaxnreg.dec.sync.aligned.u32 88;");
        return;
    }

    if (tid == 0 && !dry) { TSG(31); TSX(0); }
    if (tid == 320) {
        asm volatile("prefetch.tensormap [%0];" :: "l"(&map_x) : "memory");
        asm volatile("prefetch.tensormap [%0];" :: "l"(&map_qkv) : "memory");
        asm volatile("prefetch.tensormap [%0];" :: "l"(&map_w1) : "memory");
        asm volatile("prefetch.tensormap [%0];" :: "l"(&map_w1a) : "memory");
        asm volatile("prefetch.tensormap [%0];" :: "l"(&map_w2) : "memory");
        asm volatile("prefetch.tensormap [%0];" :: "l"(&map_wo) : "memory");
        asm volatile("prefetch.tensormap [%0];" :: "l"(&map_o) : "memory");
    }
    if (tid == 256) {
        mbar_init(sb + B_FULL, 1); mbar_init(sb + B_XFULL, 1);
        fence_async_smem();
        mbar_expect_tx(sb + B_XFULL, 16384);
        tma_2d(sb + X_OFF, &map_x, sb + B_XFULL, 0, ti * 128);
        mbar_expect_only(sb + B_FULL, 12288);
        tma_4d(sb + RING_OFF, &map_qkv, sb + B_FULL, 0, 0, tj, 0);
    }
    uint32_t gwv[N_QKV / 2];
    if (warp == 8) {
        const unsigned short* gws = reinterpret_cast<const unsigned short*>(gate_w);
#pragma unroll
        for (int n = 0; n < N_QKV / 2; n++) gwv[n] = (uint32_t)__ldg(gws + 64 * n + lane) | ((uint32_t)__ldg(gws + 64 * n + 32 + lane) << 16);
    }
    if (tid == 288) {
        for (int s = 1; s < RING; s++) mbar_init(sb + B_FULL + 8 * s, 1);
        for (int s = 0; s < RING; s++) mbar_init(sb + B_EMPTY + 8 * s, 8);
        for (int s = 1; s < 8; s++) mbar_init(sb + B_XFULL + 8 * s, 1);
        fence_async_smem();
    }
    if (tid == 352) {
        mbar_init(sb + B_HDEAD, 8); mbar_init(sb + B_EREADY, 1); mbar_init(sb + B_KVDONE, 8); mbar_init(sb + B_KVREADY, 1);
        mbar_init(sb + B_ODONE, 8); mbar_init(sb + B_WOFULL, 1); mbar_init(sb + B_HSUM, 3);
        mbar_init(sb + B_PREADY, 1); mbar_init(sb + B_SF, 1); mbar_init(sb + B_SF + 8, 1);
        for (int s = 0; s < 4; s++) mbar_init(sb + B_SQ + 8 * s, 8);
        asm volatile("st.shared.u32 [%0], %1;" :: "r"(sb + ITEM_OFF), "r"(0) : "memory");
        fence_async_smem();
    }
    if (!dry) __syncthreads();

    if (warp >= 8) {
        asm volatile("setmaxnreg.dec.sync.aligned.u32 88;");
        if (warp == 8) {
            Ring r{0, 1};
            const bool leader = elect_one();
#pragma unroll
            for (int n = 0; n < N_QKV; n++) {
                const uint32_t full = sb + B_FULL + 8 * r.slot, dst = sb + RING_OFF + r.slot * SLOT;
                if (n > 0) {
                    if (!(n & 1) && leader) {
                        mbar_expect_tx(sb + B_XFULL + 8 * (n >> 1), 16384);
                        tma_2d(sb + X_OFF + (n >> 1) * 16384, &map_x, sb + B_XFULL + 8 * (n >> 1), (n >> 1) * 64, ti * 128);
                    }
                    if (n >= RING) PWAIT();
                    if (leader) {
                        mbar_expect_only(full, 12288);
                        tma_4d(dst, &map_qkv, full, 0, 32 * n, tj, 0);
                    }
                }
                const uint32_t gv = (n & 1) ? (gwv[n >> 1] >> 16) : (gwv[n >> 1] & 0xFFFFu);
                asm volatile("st.shared.v4.b32 [%0], {%1, %2, %2, %2};" :: "r"(dst + 12288 + lane * 128 + ((lane & 7) << 4)), "r"(gv), "r"(0) : "memory");
                fence_async_smem();
                __syncwarp();
                if (leader) mbar_arrive(full);
                r.next();
            }
#pragma unroll 1
            for (int n = 0; n < N_FFN1; n++) {
                const uint32_t full = sb + B_FULL + 8 * r.slot, dst = sb + RING_OFF + r.slot * SLOT;
                PWAIT();
                if (leader) {
                    mbar_expect_tx(full, 16384);
                    tma_4d(dst, &map_w1a, full, 0, 32 * n, 0, tj);
                    tma_2d(dst + 3 * 4096, &map_w1, full, 224 * tj + 192, 32 * n);
                }
                r.next();
            }
            {
                int q = 0, rr = 0;
#pragma unroll 1
                for (int n = 0; n < N_FFN2; n++) {
                    const uint32_t full = sb + B_FULL + 8 * r.slot, dst = sb + RING_OFF + r.slot * SLOT;
                    PWAIT();
                    if (leader) mbar_expect_tx(full, 16384);
#pragma unroll
                    for (int h = 0; h < 2; h++) {
                        if (leader) tma_3d(dst + h * 8192, &map_w2, full, 0, 224 * tj + 32 * rr, 2 * q);
                        if (++rr == 7) { rr = 0; q++; }
                    }
                    r.next();
                }
            }
            mbar_wait(sb + B_KVREADY, 0);
            asm volatile("fence.proxy.async.global;" ::: "memory");
            {
                const int bbase = 8 * ti - 16, b0 = bbase < 0 ? 0 : bbase;
                const uint32_t bytes = (uint32_t)(8 * ti + 8 - b0) * 512;
#pragma unroll 1
                for (int m = 0; m < N_KV; m++) {
                    const uint32_t full = sb + B_FULL + 8 * r.slot, dst = sb + RING_OFF + r.slot * SLOT;
                    if (m == RING) {
                        mbar_wait(sb + B_HDEAD, 0);
                        if (leader) {
                            mbar_expect_tx(sb + B_WOFULL, 65536);
#pragma unroll
                            for (int e = 0; e < 2; e++) tma_2d(sb + X_OFF + e * 32768, &map_wo, sb + B_WOFULL, 64 * tj, 256 * e);
                        }
                    }
                    PWAIT();
                    if (leader) {
                        const uint4* src = ((m & 1) ? g_vf : g_kf) + ((tj * 4 + (m >> 1)) * 128 + b0) * 32;
                        mbar_expect_tx(full, bytes);
                        bulk_g2s(dst + (b0 - bbase) * 512, src, bytes, full);
                    }
                    r.next();
                }
            }
            {
                mbar_wait(sb + B_EREADY, 0);
                unsigned epoch; asm volatile("ld.shared.u32 %0, [%1];" : "=r"(epoch) : "r"(sb + EPOCH_OFF) : "memory");
                uint32_t pending = 0xFFu & ~(1u << tj), ready = 0;
                mbar_wait(sb + B_HSUM, 0);
#pragma unroll 1
                for (int m = 0; m < N_O; m++) {
                    const uint32_t full = sb + B_FULL + 8 * r.slot, dst = sb + RING_OFF + r.slot * SLOT;
                    PWAIT();
                    for (int it = 0; it < (1 << 20) && !ready; it++) {
                        bool ok = false;
                        if (lane < 8 && ((pending >> lane) & 1)) ok = (int)(ld_acquire(&g_ocnt[(ti * 8 + lane) * 32]) - 8 * (epoch + 1)) >= 0;
                        ready = __ballot_sync(0xffffffffu, ok);
                        if (!ready) __nanosleep(100);
                    }
                    const int js = ready ? __ffs(ready) - 1 : __ffs(pending) - 1;
                    pending &= ~(1u << js); ready &= ~(1u << js);
                    asm volatile("fence.proxy.async.global;" ::: "memory");
                    if (leader) {
                        asm volatile("st.shared.u32 [%0], %1;" :: "r"(sb + OSRC_OFF + 4 * m), "r"(js) : "memory");
                        mbar_expect_tx(full, 16384);
                        tma_2d(dst, &map_o, full, 64 * js, ti * 128);
                    }
                    r.next();
                }
            }
        } else if (warp == 9) {
            unsigned epoch = 0;
            if (lane == 0) {
                epoch = atomicAdd(&g_ticket, 1u) >> 7;
                asm volatile("st.shared.u32 [%0], %1;" :: "r"(sb + EPOCH_OFF), "r"(epoch) : "memory");
                mbar_arrive(sb + B_EREADY);
                mbar_wait(sb + B_XFULL + 8 * PF1_AT, 0);
                prefetch_l2(w1p + (size_t)blockIdx.x * 14336, 14336);
                mbar_wait(sb + B_XFULL + 8 * PF2_AT, 0);
                prefetch_l2(w2p + (size_t)blockIdx.x * 14336, 14336);
                prefetch_l2(wop + (size_t)blockIdx.x * 4096, 4096);
                mbar_wait(sb + B_KVDONE, 0);
                red_release(&g_kvcnt[blockIdx.x * 32], 1u);
            }
            epoch = __shfl_sync(0xffffffffu, epoch, 0);
            if (lane < 3 && ti - lane >= 0) wait_counter(&g_kvcnt[((ti - lane) * 8 + tj) * 32], epoch + 1);
            __syncwarp();
            if (lane == 0) mbar_arrive(sb + B_KVREADY);
            mbar_wait(sb + B_SQ + 24, 0);
            if (lane < 8) wait_counter(&g_pcnt[(ti * 8 + lane) * 32], epoch + 1);
            __syncwarp();
            if (lane == 0) { mbar_arrive(sb + B_PREADY); TSX(13); }
            sum_partials(sb, ti, tj, lane);
            if (lane == 0) TSX(14);
        } else {
            if (warp == 10) {
#pragma unroll 1
                for (int q = 0; q < 4; q++) {
                    mbar_wait(sb + B_SQ + 8 * q, 0);
                    if (lane < 16) {
                        uint4* d = g_part + (size_t)(((ti * 8 + 2 * q + (lane & 1)) * 8 + tj) * 8 + (lane >> 1)) * 128;
                        bulk_s2g(d, sb + STG_OFF + (q & 1) * 32768 + lane * 2048, 2048);
                        asm volatile("cp.async.bulk.commit_group;" ::: "memory");
                        asm volatile("cp.async.bulk.wait_group.read 0;" ::: "memory");
                    }
                    __syncwarp();
                    if (lane == 0) mbar_arrive(sb + B_SF + 8 * (q & 1));
                }
                asm volatile("cp.async.bulk.wait_group 0;" ::: "memory");
                asm volatile("fence.proxy.async.global;" ::: "memory");
                __syncwarp();
                if (lane == 0) { red_release(&g_pcnt[blockIdx.x * 32], 1u); TSX(12); }
            }
            mbar_wait(sb + B_PREADY, 0);
            sum_partials(sb, ti, tj, lane);
        }
    } else {
        asm volatile("setmaxnreg.inc.sync.aligned.u32 208;");
        const int wg = warp >> 2, g = lane >> 2, c = lane & 3;
        const uint32_t xa = sb + X_OFF + wg * 8192;
        Ring r{0, 0};
        const bool lane0 = lane == 0 && !dry;
        uint32_t qf[4][4];
        float g0, g1;
        TS(9);
        {
            float acc[100];
            int prev = 0;
            if (wg == 1) asm volatile("bar.sync 3, 256;" ::: "memory");
            for (int s = 0; s < (dry ? 4 : N_QKV); s++) {
                if (!(s & 1) && !dry) mbar_wait(sb + B_XFULL + 8 * (s >> 1), 0);
                CWAIT();
                if (s == 0) TS(1);
                if (s == 2) TS(28);
                if (s == 6) TS(29);
                if (s == 10) TS(20);
                const uint32_t bs = sb + RING_OFF + r.slot * SLOT, as = xa + (s >> 1) * 16384 + (s & 1) * 64;
                wgmma_fence();
                wgmma_ss_n200(acc, desc_a(as), desc_b(bs), s);
                wgmma_ss_n200(acc, desc_a(as + 32), desc_b(bs + 2048), 1);
                wgmma_commit();
                if (wg == 0 && s == LEAD1) asm volatile("bar.arrive 3, 256;" ::: "memory");
                if (s > 0) { wgmma_wait<1>(); if (lane0) mbar_arrive(sb + B_EMPTY + 8 * prev); }
                prev = r.slot; r.next();
            }
            wgmma_wait<0>();
            fence_acc(acc);
            if (lane0) mbar_arrive(sb + B_EMPTY + 8 * prev);
            TS(2);
            const int blk = ti * 8 + warp;
#pragma unroll
            for (int hh = 0; hh < 4; hh++) {
                const float* t0 = &acc[8 * hh]; const float* t1 = &acc[8 * hh + 4];
                qf[hh][0] = pack_bf16(t0[0], t0[1]); qf[hh][1] = pack_bf16(t0[2], t0[3]);
                qf[hh][2] = pack_bf16(t1[0], t1[1]); qf[hh][3] = pack_bf16(t1[2], t1[3]);
                const float* k0 = &acc[32 + 8 * hh]; const float* k1 = &acc[32 + 8 * hh + 4];
                uint4 kv;
                kv.x = pack_bf16(k0[0], k0[1]); kv.y = pack_bf16(k1[0], k1[1]);
                kv.z = pack_bf16(k0[2], k0[3]); kv.w = pack_bf16(k1[2], k1[3]);
                if (!dry) g_kf[((tj * 4 + hh) * 128 + blk) * 32 + lane] = kv;
                const float* v0 = &acc[64 + 8 * hh]; const float* v1 = &acc[64 + 8 * hh + 4];
                uint4 vv;
                vv.x = movmatrix(pack_bf16(v0[0], v0[1])); vv.y = movmatrix(pack_bf16(v0[2], v0[3]));
                vv.z = movmatrix(pack_bf16(v1[0], v1[1])); vv.w = movmatrix(pack_bf16(v1[2], v1[3]));
                if (!dry) g_vf[((tj * 4 + hh) * 128 + blk) * 32 + lane] = vv;
            }
            __syncwarp();
            if (lane0) mbar_arrive(sb + B_KVDONE);
            const float z0 = __shfl_sync(0xffffffffu, acc[96], lane & ~3), z1 = __shfl_sync(0xffffffffu, acc[98], lane & ~3);
            g0 = 1.f / (1.f + __expf(-z0)); g1 = 1.f / (1.f + __expf(-z1));
        }
        TS(3);
        const int wrow = (warp & 3) * 16;
        {
            float acc[112];
            int prev = 0;
            for (int s = 0; s < (dry ? 4 : N_FFN1); s++) {
                CWAIT();
                const uint32_t bs = sb + RING_OFF + r.slot * SLOT, as = xa + (s >> 1) * 16384 + (s & 1) * 64;
                wgmma_fence();
                wgmma_ss_n224(acc, desc_a(as), desc_b(bs), s);
                wgmma_ss_n224(acc, desc_a(as + 32), desc_b(bs + 2048), 1);
                wgmma_commit();
                if (s > 0) { wgmma_wait<1>(); if (lane0) mbar_arrive(sb + B_EMPTY + 8 * prev); }
                prev = r.slot; r.next();
            }
            wgmma_wait<0>();
            fence_acc(acc);
            if (lane0) mbar_arrive(sb + B_EMPTY + 8 * prev);
            TS(4);
            const float s0 = 1.f - g0, s1 = 1.f - g1;
            asm volatile("bar.sync %0, 128;" :: "r"(1 + wg) : "memory");
            const uint32_t strow = xa + (wrow + ((lane >> 3) & 1) * 8 + (lane & 7)) * 128;
#pragma unroll
            for (int p = 0; p < 14; p++) {
                const int nt = 2 * p + (lane >> 4);
                const float* a = &acc[8 * p];
                stmatrix_x4(strow + (p >> 2) * 16384 + (((nt & 7) ^ (lane & 7)) << 4),
                            pack_bf16_relu(a[0] * s0, a[1] * s0), pack_bf16_relu(a[2] * s1, a[3] * s1),
                            pack_bf16_relu(a[4] * s0, a[5] * s0), pack_bf16_relu(a[6] * s1, a[7] * s1));
            }
        }
        TS(5);
        {
            fence_async_smem();
            asm volatile("bar.sync 4, 256;" ::: "memory");
            float accA[64], accB[64];
            auto epilogue = [&](float (&acc)[64], int q) {
                fence_acc(acc);
                const uint32_t st = sb + STG_OFF + (q & 1) * 32768 + warp * 4096;
                if (q >= 2 && !dry) mbar_wait(sb + B_SF + 8 * (q & 1), 0);
#pragma unroll
                for (int t2 = 0; t2 < 8; t2++) {
                    uint4 v;
                    v.x = pack_bf16(acc[8 * t2 + 0], acc[8 * t2 + 1]); v.y = pack_bf16(acc[8 * t2 + 2], acc[8 * t2 + 3]);
                    v.z = pack_bf16(acc[8 * t2 + 4], acc[8 * t2 + 5]); v.w = pack_bf16(acc[8 * t2 + 6], acc[8 * t2 + 7]);
                    sts128(st + t2 * 512 + lane * 16, v);
                }
                fence_async_smem();
                __syncwarp();
                if (lane0) mbar_arrive(sb + B_SQ + 8 * q);
            };
            int rel = r.slot;
#pragma unroll
            for (int m = 0; m < N_FFN2; m++) {
                CWAIT();
                wgmma_fence();
#pragma unroll
                for (int h = 0; h < 2; h++) {
                    const int u = 2 * m + h, q = u / 7, rr = u % 7;
                    const uint32_t bs = sb + RING_OFF + r.slot * SLOT + h * 8192;
                    const uint32_t as = xa + (rr >> 1) * 16384 + (rr & 1) * 64;
                    if (!(q & 1)) {
                        wgmma_ss_n128(accA, desc_a(as), desc_b(bs), rr);
                        wgmma_ss_n128(accA, desc_a(as + 32), desc_b(bs + 2048), 1);
                    } else {
                        wgmma_ss_n128(accB, desc_a(as), desc_b(bs), rr);
                        wgmma_ss_n128(accB, desc_a(as + 32), desc_b(bs + 2048), 1);
                    }
                }
                wgmma_commit();
                r.next();
                wgmma_wait<1>();
                if (m > 0) {
                    if (lane0) mbar_arrive(sb + B_EMPTY + 8 * rel);
                    if (++rel == RING) rel = 0;
                }
                if (m == 4) { TS(25); epilogue(accA, 0); }
                if (m == 7) { TS(26); epilogue(accB, 1); }
                if (m == 11) { TS(27); epilogue(accA, 2); }
            }
            wgmma_wait<0>();
            if (lane0) { mbar_arrive(sb + B_EMPTY + 8 * rel); mbar_arrive(sb + B_HDEAD); }
            epilogue(accB, 3);
        }
        TS(6);
        {
            const float SC = 0.25f * 1.4426950408889634f;
            const int gb0 = 8 * ti - 16 + warp;
            int slotK = 0, slotV = 0;
            const uint32_t ostore = sb + OWN_OFF + (warp * 16 + ((lane >> 3) & 1) * 8 + (lane & 7)) * 128;
            uint32_t* odst = reinterpret_cast<uint32_t*>(g_o + (size_t)(ti * 128 + warp * 16 + g) * 512 + tj * 64 + ((lane & 1) ? 8 : 0) + (lane & 2) * 2);
#define NHEADS (dry ? 2 : 4)
#define ATT_KWAIT(kb) do { slotK = r.slot; CWAIT(); kb = sb + RING_OFF + slotK * SLOT + warp * 512 + lane * 16; r.next(); } while (0)
#define ATT_VWAIT(vb) do { slotV = r.slot; CWAIT(); vb = sb + RING_OFF + slotV * SLOT + warp * 512 + lane * 16; r.next(); TS(21 + hh); } while (0)
#define ATT_KREL() do { __syncwarp(); if (lane0) mbar_arrive(sb + B_EMPTY + 8 * slotK); } while (0)
#define ATT_VREL() do { __syncwarp(); if (lane0) mbar_arrive(sb + B_EMPTY + 8 * slotV); } while (0)
#define ATT_NEXTQ(h) do { \
                if ((h) == 1) { q0 = qf[1][0]; q1 = qf[1][1]; q2 = qf[1][2]; q3 = qf[1][3]; } \
                else if ((h) == 2) { q0 = qf[2][0]; q1 = qf[2][1]; q2 = qf[2][2]; q3 = qf[2][3]; } \
                else { q0 = qf[3][0]; q1 = qf[3][1]; q2 = qf[3][2]; q3 = qf[3][3]; } } while (0)
#define ATT_STORE(h, r0, r1, r2, r3) do { \
                if ((h) == 0 && !dry) mbar_wait(sb + B_SF + 8, 1);        \
                stmatrix_x4(ostore + (((2 * (h) + (lane >> 4)) ^ (lane & 7)) << 4), r0, r1, r2, r3); \
                const bool odd = lane & 1; \
                const uint32_t sl = __shfl_xor_sync(0xffffffffu, odd ? (r0) : (r2), 1), sh = __shfl_xor_sync(0xffffffffu, odd ? (r1) : (r3), 1); \
                if (!dry) *reinterpret_cast<uint2*>(odst + 8 * (h)) = odd ? make_uint2(sl, r2) : make_uint2(r0, sl); \
                if (!dry) *reinterpret_cast<uint2*>(odst + 8 * (h) + 8 * 256) = odd ? make_uint2(sh, r3) : make_uint2(r1, sh); \
                } while (0)
            auto attention = [&](auto masked_tag) {
            constexpr bool MASKED = decltype(masked_tag)::value;
            const float NEG = -INFINITY;
            const uint32_t ONES = 0x3F803F80u;
            float sa[8][2][4];
            float o[2][4], ls[4];
            float m0, m1;
            uint32_t q0 = qf[0][0], q1 = qf[0][1], q2 = qf[0][2], q3 = qf[0][3];
            auto qk = [&](float (&s)[8][2][4], int ps, int t, uint32_t kbase, bool merged) {
                if (merged) {
                    const uint4 kd = lds128(kbase + 16 * 512);
                    const uint4 kf = lds128(kbase);
                    float f[2][4];
                    const float ci = (!MASKED || opaque(gb0) >= 0) ? 0.f : NEG;
                    mma16816_c(s[0][0], q0, q1, q2, q3, kd.x, kd.y, 0.f);
                    mma16816_c(s[0][1], q0, q1, q2, q3, kd.z, kd.w, 0.f);
                    mma16816_c(f[0], q0, q1, q2, q3, kf.x, kf.y, ci);
                    mma16816_c(f[1], q0, q1, q2, q3, kf.z, kf.w, ci);
#pragma unroll
                    for (int u = 0; u < 2; u++)
#pragma unroll
                        for (int e = 0; e < 4; e++) {
                            const int row = g + 8 * (e >> 1), col = 8 * u + 2 * c + (e & 1);
                            s[0][u][e] = (col > row) ? f[u][e] : s[0][u][e];
                        }
                } else {
                    const uint4 kf = lds128(kbase + (8 * ps + t) * 512);
                    const float ci = (!MASKED || opaque(gb0) + 8 * ps + t >= 0) ? 0.f : NEG;
                    mma16816_c(s[t][0], q0, q1, q2, q3, kf.x, kf.y, ci);
                    mma16816_c(s[t][1], q0, q1, q2, q3, kf.z, kf.w, ci);
                }
            };
            auto rowmax = [&](float (&s)[8][2][4], float b0, float b1, float& n0, float& n1) {
                int i0 = __float_as_int(b0), i1 = __float_as_int(b1);
#pragma unroll
                for (int t = 0; t < 8; t++)
#pragma unroll
                    for (int u = 0; u < 2; u++) {
                        i0 = __vimax3_s32(i0, __float_as_int(s[t][u][0]), __float_as_int(s[t][u][1]));
                        i1 = __vimax3_s32(i1, __float_as_int(s[t][u][2]), __float_as_int(s[t][u][3]));
                    }
                i0 = max(i0, __shfl_xor_sync(0xffffffffu, i0, 1)); i1 = max(i1, __shfl_xor_sync(0xffffffffu, i1, 1));
                i0 = max(i0, __shfl_xor_sync(0xffffffffu, i0, 2)); i1 = max(i1, __shfl_xor_sync(0xffffffffu, i1, 2));
                n0 = __int_as_float(i0); n1 = __int_as_float(i1);
                if (__any_sync(0xffffffffu, (i0 | i1) < 0)) {
                    asm volatile("" ::: "memory");
                    n0 = b0; n1 = b1;
#pragma unroll
                    for (int t = 0; t < 8; t++)
#pragma unroll
                        for (int u = 0; u < 2; u++) {
                            n0 = fmaxf(n0, fmaxf(s[t][u][0], s[t][u][1]));
                            n1 = fmaxf(n1, fmaxf(s[t][u][2], s[t][u][3]));
                        }
                    n0 = fmaxf(n0, __shfl_xor_sync(0xffffffffu, n0, 1)); n1 = fmaxf(n1, __shfl_xor_sync(0xffffffffu, n1, 1));
                    n0 = fmaxf(n0, __shfl_xor_sync(0xffffffffu, n0, 2)); n1 = fmaxf(n1, __shfl_xor_sync(0xffffffffu, n1, 2));
                }
            };
            auto pv = [&](const float (&p)[2][4], uint32_t vaddr) {
                const uint4 vf = lds128(vaddr);
                const uint32_t a0 = pack_bf16(p[0][0], p[0][1]), a1 = pack_bf16(p[0][2], p[0][3]);
                const uint32_t a2 = pack_bf16(p[1][0], p[1][1]), a3 = pack_bf16(p[1][2], p[1][3]);
                mma16816(o[0], a0, a1, a2, a3, vf.x, vf.y);
                mma16816(o[1], a0, a1, a2, a3, vf.z, vf.w);
                mma16816(ls, a0, a1, a2, a3, ONES, ONES);
            };
            auto expv = [&](float (&s)[8][2][4], int ps, int t, float mc0, float mc1, uint32_t vbase, bool merged) {
                float p[2][4];
#pragma unroll
                for (int u = 0; u < 2; u++) {
                    p[u][0] = ex2(fmaf(s[t][u][0], SC, -mc0)); p[u][1] = ex2(fmaf(s[t][u][1], SC, -mc0));
                    p[u][2] = ex2(fmaf(s[t][u][2], SC, -mc1)); p[u][3] = ex2(fmaf(s[t][u][3], SC, -mc1));
                }
                if (merged) {
                    float pd[2][4], pf[2][4];
#pragma unroll
                    for (int u = 0; u < 2; u++)
#pragma unroll
                        for (int e = 0; e < 4; e++) {
                            const int row = g + 8 * (e >> 1), col = 8 * u + 2 * c + (e & 1);
                            pf[u][e] = (col > row) ? p[u][e] : 0.f;
                            pd[u][e] = (col > row) ? 0.f : p[u][e];
                        }
                    pv(pd, vbase + 16 * 512);
                    pv(pf, vbase);
                } else {
                    pv(p, vbase + (8 * ps + t) * 512);
                }
            };
            uint32_t kbase = 0, vbase = 0;
#pragma unroll 1
            for (int hh = 0; hh < NHEADS; hh++) {
                ATT_KWAIT(kbase);
                if (hh > 0) ATT_NEXTQ(hh);
#pragma unroll
                for (int ps = 0; ps < 2; ps++) {
#pragma unroll
                    for (int t = 0; t < 8; t++) qk(sa, ps, t, kbase, ps == 0 && t == 0);
                    if (ps == 1) ATT_KREL();
                    float n0, n1;
                    rowmax(sa, ps ? m0 : NEG, ps ? m1 : NEG, n0, n1);
                    if (ps == 0) {
                        ATT_VWAIT(vbase);
#pragma unroll
                        for (int e = 0; e < 4; e++) { o[0][e] = 0.f; o[1][e] = 0.f; ls[e] = 0.f; }
                    } else {
                        const float a0 = ex2((m0 - n0) * SC), a1 = ex2((m1 - n1) * SC);
                        ls[0] *= a0; ls[2] *= a1;
                        o[0][0] *= a0; o[0][1] *= a0; o[1][0] *= a0; o[1][1] *= a0;
                        o[0][2] *= a1; o[0][3] *= a1; o[1][2] *= a1; o[1][3] *= a1;
                    }
                    m0 = n0; m1 = n1;
                    const float mc0 = n0 * SC, mc1 = n1 * SC;
#pragma unroll
                    for (int t = 0; t < 8; t++) expv(sa, ps, t, mc0, mc1, vbase, ps == 0 && t == 0);
                }
                ATT_VREL();
                const float f0 = __fdividef(g0, ls[0]), f1 = __fdividef(g1, ls[2]);
                ATT_STORE(hh, pack_bf16(o[0][0] * f0, o[0][1] * f0), pack_bf16(o[0][2] * f1, o[0][3] * f1),
                              pack_bf16(o[1][0] * f0, o[1][1] * f0), pack_bf16(o[1][2] * f1, o[1][3] * f1));
            }
            };
            if (ti >= 2) attention(BoolTag<false>{}); else attention(BoolTag<true>{});
            fence_async_smem();
            __syncwarp();
            if (lane0) { mbar_arrive(sb + B_ODONE); red_release(&g_ocnt[blockIdx.x * 32], 1u); }
        }
        TS(7);
        {
            float acc[32];
            uint4 pv[4][4];
            if (!dry) mbar_wait(sb + B_PREADY, 0);
            {
                const uint4* p = g_part + (size_t)((ti * 8 + tj) * 8 + 4) * 1024 + warp * 128 + lane;
#pragma unroll
                for (int s = 0; s < 4; s++)
#pragma unroll
                    for (int n = 0; n < 4; n++) pv[n][s] = dry ? make_uint4(0u, 0u, 0u, 0u) : ldg_weak(p + s * 1024 + n * 32);
            }
            if (!dry) mbar_wait(sb + B_WOFULL, 0);
            if (!dry) mbar_wait(sb + B_ODONE, 0);
            TS(15);
            wgmma_fence();
#pragma unroll
            for (int k = 0; k < 4; k++) wgmma_ss_n64(acc, desc_a(sb + OWN_OFF + wg * 8192 + 32 * k), desc_b(sb + X_OFF + tj * 8192 + 2048 * k), k);
            wgmma_commit();
            TS(16);
#pragma unroll 1
            for (int m = 0; m < N_O; m++) {
                CWAIT();
                uint32_t js; asm volatile("ld.shared.u32 %0, [%1];" : "=r"(js) : "r"(sb + OSRC_OFF + 4 * m) : "memory");
                const uint32_t as = sb + RING_OFF + r.slot * SLOT + wg * 8192;
                const uint32_t bs = sb + X_OFF + (js & 7) * 8192;
                wgmma_fence();
#pragma unroll
                for (int k = 0; k < 4; k++) wgmma_ss_n64(acc, desc_a(as + 32 * k), desc_b(bs + 2048 * k), 1);
                wgmma_commit();
                if (m == 0) { wgmma_wait<0>(); if (lane0) mbar_arrive(sb + B_EMPTY + 8 * r.slot); }
                r.next();
            }
            float base[32];
            if (!dry) mbar_wait(sb + B_HSUM, 0);
#pragma unroll
            for (int n = 0; n < 4; n++) {
                const uint4 u0 = lds128(sb + STG_OFF + (warp * 8 + 2 * n) * 512 + lane * 16), u1 = lds128(sb + STG_OFF + (warp * 8 + 2 * n + 1) * 512 + lane * 16);
                float* a = &base[8 * n];
                a[0] = __uint_as_float(u0.x); a[1] = __uint_as_float(u0.y); a[2] = __uint_as_float(u0.z); a[3] = __uint_as_float(u0.w);
                a[4] = __uint_as_float(u1.x); a[5] = __uint_as_float(u1.y); a[6] = __uint_as_float(u1.z); a[7] = __uint_as_float(u1.w);
#pragma unroll
                for (int s = 0; s < 4; s++) {
                    a[0] += bf_lo(pv[n][s].x); a[1] += bf_hi(pv[n][s].x); a[2] += bf_lo(pv[n][s].y); a[3] += bf_hi(pv[n][s].y);
                    a[4] += bf_lo(pv[n][s].z); a[5] += bf_hi(pv[n][s].z); a[6] += bf_lo(pv[n][s].w); a[7] += bf_hi(pv[n][s].w);
                }
            }
            fence_acc(base);
            wgmma_wait<0>();
            fence_acc(acc);
            TS(17);
#pragma unroll
            for (int k = 0; k < 32; k++) acc[k] += base[k];
            __nv_bfloat16* o = out + (size_t)(ti * 128 + warp * 16 + g) * 512 + tj * 64 + ((lane & 1) ? 8 : 0) + (lane & 2) * 2;
            const bool odd = lane & 1;
#pragma unroll
            for (int t2 = 0; t2 < 4; t2++) {
                const uint32_t lo0 = pack_bf16(acc[8 * t2 + 0], acc[8 * t2 + 1]), hi0 = pack_bf16(acc[8 * t2 + 2], acc[8 * t2 + 3]);
                const uint32_t lo1 = pack_bf16(acc[8 * t2 + 4], acc[8 * t2 + 5]), hi1 = pack_bf16(acc[8 * t2 + 6], acc[8 * t2 + 7]);
                const uint32_t sl = __shfl_xor_sync(0xffffffffu, odd ? lo0 : lo1, 1), sh = __shfl_xor_sync(0xffffffffu, odd ? hi0 : hi1, 1);
                if (!dry) *reinterpret_cast<uint2*>(o + 16 * t2) = odd ? make_uint2(sl, lo1) : make_uint2(lo0, sl);
                if (!dry) *reinterpret_cast<uint2*>(o + 16 * t2 + 8 * 512) = odd ? make_uint2(sh, hi1) : make_uint2(hi0, sh);
            }
            if (tid == 0 && !dry) TSG(30);
        }
        TS(8);
    }
}

typedef CUresult (*PFN_encodeTiled)(CUtensorMap*, CUtensorMapDataType, cuuint32_t, void*, const cuuint64_t*, const cuuint64_t*,
                                    const cuuint32_t*, const cuuint32_t*, CUtensorMapInterleave, CUtensorMapSwizzle,
                                    CUtensorMapL2promotion, CUtensorMapFloatOOBfill);

void make_map(PFN_encodeTiled enc, CUtensorMap* m, const void* base, int rank, const cuuint64_t* dims, const cuuint64_t* strides, const cuuint32_t* box) {
    cuuint32_t es[5] = {1, 1, 1, 1, 1};
    enc(m, CU_TENSOR_MAP_DATA_TYPE_BFLOAT16, (cuuint32_t)rank, const_cast<void*>(base), dims, strides, box, es,
        CU_TENSOR_MAP_INTERLEAVE_NONE, CU_TENSOR_MAP_SWIZZLE_128B, CU_TENSOR_MAP_L2_PROMOTION_L2_256B, CU_TENSOR_MAP_FLOAT_OOB_FILL_NONE);
}

}

extern "C" void kernel_launch(void* const* d_in, const int* in_sizes, int n_in, void* d_out, int out_size) {
    (void)in_sizes; (void)n_in; (void)out_size;
    const void* x = d_in[0]; const void* wqkv = d_in[1]; const void* wo = d_in[2];
    const void* w1 = d_in[4]; const void* w2 = d_in[5]; const void* gate_w = d_in[6];
    static PFN_encodeTiled enc = nullptr;
    if (!enc) {
        void* fn = nullptr; cudaDriverEntryPointQueryResult st;
        cudaGetDriverEntryPoint("cuTensorMapEncodeTiled", &fn, cudaEnableDefault, &st);
        enc = (PFN_encodeTiled)fn;
        cudaFuncSetAttribute(fused_kernel, cudaFuncAttributeMaxDynamicSharedMemorySize, SMEM_BYTES);
    }
    CUtensorMap mx, mqkv, mw1, mw2, mwo, mw1a, mo;
    void* optr = nullptr;
    cudaGetSymbolAddress(&optr, g_o);
    { cuuint64_t d[2] = {512, 2048}, s[1] = {1024}; cuuint32_t b[2] = {64, 128}; make_map(enc, &mo, optr, 2, d, s, b); }
    { cuuint64_t d[4] = {64, 512, 3, 8}, s[3] = {3584, 128, 448}; cuuint32_t b[4] = {64, 32, 3, 1}; make_map(enc, &mw1a, w1, 4, d, s, b); }
    { cuuint64_t d[2] = {512, 2048}, s[1] = {1024}; cuuint32_t b[2] = {64, 128}; make_map(enc, &mx, x, 2, d, s, b); }
    { cuuint64_t d[4] = {64, 512, 8, 3}, s[3] = {3072, 128, 1024}; cuuint32_t b[4] = {64, 32, 1, 3}; make_map(enc, &mqkv, wqkv, 4, d, s, b); }
    { cuuint64_t d[2] = {1792, 512}, s[1] = {3584}; cuuint32_t b[2] = {64, 32}; make_map(enc, &mw1, w1, 2, d, s, b); }
    { cuuint64_t d[3] = {64, 1792, 8}, s[2] = {1024, 128}; cuuint32_t b[3] = {64, 32, 2}; make_map(enc, &mw2, w2, 3, d, s, b); }
    { cuuint64_t d[2] = {512, 512}, s[1] = {1024}; cuuint32_t b[2] = {64, 256}; make_map(enc, &mwo, wo, 2, d, s, b); }
    fused_kernel<<<NCTA, 384, SMEM_BYTES, cudaStreamPerThread>>>(mx, mqkv, mw1, mw2, mwo, mw1a, mo, (const __nv_bfloat16*)gate_w, (__nv_bfloat16*)d_out,
                                           (const uint8_t*)w1, (const uint8_t*)w2, (const uint8_t*)wo);
}
```

```cpp
#include <cuda_runtime.h>
#include <cuda_bf16.h>
#include <cuda.h>
#include <stdint.h>

namespace {

#define PF1_AT 1
#define PF2_AT 5
#define LEAD1 2
#define NCTA 132
constexpr int RING = 6;
constexpr int SLOT = 16384;
constexpr uint32_t X_OFF = 0;
constexpr uint32_t STG_OFF = X_OFF + 4 * 16384;
constexpr uint32_t RING_OFF = 131072;
constexpr uint32_t BAR_OFF = RING_OFF + RING * SLOT;
constexpr uint32_t B_FULL = BAR_OFF, B_EMPTY = BAR_OFF + 64, B_XFULL = BAR_OFF + 128, B_HDEAD = BAR_OFF + 192,
                   B_EREADY = BAR_OFF + 200, B_KVDONE = BAR_OFF + 208, B_ODONE = BAR_OFF + 224,
                   B_KVREADY = BAR_OFF + 232, B_WOFULL = BAR_OFF + 240, B_HSUM = BAR_OFF + 248, B_PREADY = BAR_OFF + 264,
                   B_SQ = BAR_OFF + 272, B_SF = BAR_OFF + 304;
constexpr uint32_t EPOCH_OFF = BAR_OFF + 256, ITEM_OFF = BAR_OFF + 260, OSRC_OFF = BAR_OFF + 384;
constexpr uint32_t OWN_OFF = X_OFF + 4 * 16384;
constexpr uint32_t HSUM_OFF = X_OFF + 6 * 16384;
constexpr uint32_t SMEM_BYTES = BAR_OFF + 1024;

constexpr int N_QKV = 16, N_FFN1 = 16, N_FFN2 = 14, N_KV = 8, N_O = 7;

__device__ uint4 g_kf[32 * 128 * 32];
__device__ uint4 g_vf[32 * 128 * 32];
__device__ uint4 g_part[16 * 8 * 8 * 8 * 4 * 32];
__device__ __nv_bfloat16 g_o[2048 * 512];
__device__ unsigned g_ticket;
__device__ unsigned g_kvcnt[128 * 32];
__device__ unsigned g_pcnt[128 * 32];
__device__ unsigned g_ocnt[128 * 32];
#define TS(k) do {} while (0)
#define TS2(k) do {} while (0)
#define TS2X(k) do {} while (0)
#define TSX(k) do {} while (0)
#define TSG(k) do {} while (0)

__device__ __forceinline__ uint32_t smem_u32(const void* p) { return (uint32_t)__cvta_generic_to_shared(p); }
__device__ __forceinline__ void mbar_init(uint32_t bar, uint32_t cnt) { asm volatile("mbarrier.init.shared::cta.b64 [%0], %1;" :: "r"(bar), "r"(cnt) : "memory"); }
__device__ __forceinline__ void mbar_expect_tx(uint32_t bar, uint32_t bytes) { asm volatile("mbarrier.arrive.expect_tx.shared::cta.b64 _, [%0], %1;" :: "r"(bar), "r"(bytes) : "memory"); }
__device__ __forceinline__ void mbar_expect_only(uint32_t bar, uint32_t bytes) { asm volatile("mbarrier.expect_tx.relaxed.cta.shared::cta.b64 [%0], %1;" :: "r"(bar), "r"(bytes) : "memory"); }
__device__ __forceinline__ void mbar_arrive(uint32_t bar) { asm volatile("mbarrier.arrive.shared::cta.b64 _, [%0];" :: "r"(bar) : "memory"); }
__device__ __forceinline__ void mbar_wait(uint32_t bar, uint32_t parity) {
    asm volatile("{\n.reg .pred P1, P2;\n.reg .u32 n;\nmov.u32 n, 0;\n"
                 "WAIT_LOOP:\n"
                 "mbarrier.try_wait.parity.shared::cta.b64 P1, [%0], %1;\n"
                 "@P1 bra WAIT_DONE;\n"
                 "add.u32 n, n, 1;\n"
                 "setp.lt.u32 P2, n, 0x400000;\n"
                 "@P2 bra WAIT_LOOP;\n"
                 "WAIT_DONE:\n}" :: "r"(bar), "r"(parity) : "memory");
}
__device__ __forceinline__ void tma_2d(uint32_t dst, const void* map, uint32_t bar, int c0, int c1) {
    asm volatile("cp.async.bulk.tensor.2d.shared::cluster.global.mbarrier::complete_tx::bytes [%0], [%1, {%3, %4}], [%2];"
        :: "r"(dst), "l"(map), "r"(bar), "r"(c0), "r"(c1) : "memory");
}
__device__ __forceinline__ void tma_3d(uint32_t dst, const void* map, uint32_t bar, int c0, int c1, int c2) {
    asm volatile("cp.async.bulk.tensor.3d.shared::cluster.global.mbarrier::complete_tx::bytes [%0], [%1, {%3, %4, %5}], [%2];"
        :: "r"(dst), "l"(map), "r"(bar), "r"(c0), "r"(c1), "r"(c2) : "memory");
}
__device__ __forceinline__ void tma_4d(uint32_t dst, const void* map, uint32_t bar, int c0, int c1, int c2, int c3) {
    asm volatile("cp.async.bulk.tensor.4d.shared::cluster.global.mbarrier::complete_tx::bytes [%0], [%1, {%3, %4, %5, %6}], [%2];"
        :: "r"(dst), "l"(map), "r"(bar), "r"(c0), "r"(c1), "r"(c2), "r"(c3) : "memory");
}
__device__ __forceinline__ void bulk_g2s(uint32_t dst, const void* src, uint32_t bytes, uint32_t bar) {
    asm volatile("cp.async.bulk.shared::cluster.global.mbarrier::complete_tx::bytes [%0], [%1], %2, [%3];"
        :: "r"(dst), "l"(src), "r"(bytes), "r"(bar) : "memory");
}
__device__ __forceinline__ void prefetch_l2(const void* src, uint32_t bytes) {
    asm volatile("cp.async.bulk.prefetch.L2.global [%0], %1;" :: "l"(src), "r"(bytes) : "memory");
}
__device__ __forceinline__ bool elect_one() {
    uint32_t p;
    asm volatile("{\n.reg .pred P;\nelect.sync _|P, 0xffffffff;\nselp.u32 %0, 1, 0, P;\n}" : "=r"(p));
    return p != 0;
}
__device__ __forceinline__ void wgmma_fence() { asm volatile("wgmma.fence.sync.aligned;" ::: "memory"); }
__device__ __forceinline__ void wgmma_commit() { asm volatile("wgmma.commit_group.sync.aligned;" ::: "memory"); }
template <int N> __device__ __forceinline__ void wgmma_wait() { asm volatile("wgmma.wait_group.sync.aligned %0;" :: "n"(N) : "memory"); }
__device__ __forceinline__ void fence_async_smem() { asm volatile("fence.proxy.async.shared::cta;" ::: "memory"); }
__device__ __forceinline__ uint64_t desc_a(uint32_t addr) {
    return (uint64_t)((addr & 0x3FFFF) >> 4) | ((uint64_t)1 << 16) | ((uint64_t)(1024 >> 4) << 32) | ((uint64_t)1 << 62);
}
__device__ __forceinline__ uint64_t desc_b(uint32_t addr) {
    return (uint64_t)((addr & 0x3FFFF) >> 4) | ((uint64_t)(4096 >> 4) << 16) | ((uint64_t)(1024 >> 4) << 32) | ((uint64_t)1 << 62);
}
__device__ __forceinline__ uint32_t pack_bf16(float lo, float hi) {
    uint32_t r; asm("cvt.rn.bf16x2.f32 %0, %1, %2;" : "=r"(r) : "f"(hi), "f"(lo)); return r;
}
__device__ __forceinline__ uint32_t pack_bf16_relu(float lo, float hi) {
    uint32_t r; asm("cvt.rn.relu.bf16x2.f32 %0, %1, %2;" : "=r"(r) : "f"(hi), "f"(lo)); return r;
}
__device__ __forceinline__ uint32_t movmatrix(uint32_t a) {
    uint32_t d; asm volatile("movmatrix.sync.aligned.m8n8.trans.b16 %0, %1;" : "=r"(d) : "r"(a)); return d;
}
__device__ __forceinline__ void stmatrix_x4(uint32_t addr, uint32_t r0, uint32_t r1, uint32_t r2, uint32_t r3) {
    asm volatile("stmatrix.sync.aligned.m8n8.x4.shared.b16 [%0], {%1, %2, %3, %4};" :: "r"(addr), "r"(r0), "r"(r1), "r"(r2), "r"(r3) : "memory");
}
__device__ __forceinline__ uint4 lds128(uint32_t addr) {
    uint4 v; asm volatile("ld.shared.v4.b32 {%0, %1, %2, %3}, [%4];" : "=r"(v.x), "=r"(v.y), "=r"(v.z), "=r"(v.w) : "r"(addr) : "memory"); return v;
}
__device__ __forceinline__ void mma16816(float (&c)[4], uint32_t a0, uint32_t a1, uint32_t a2, uint32_t a3, uint32_t b0, uint32_t b1) {
    asm volatile("mma.sync.aligned.m16n8k16.row.col.f32.bf16.bf16.f32 {%0,%1,%2,%3}, {%4,%5,%6,%7}, {%8,%9}, {%0,%1,%2,%3};"
        : "+f"(c[0]), "+f"(c[1]), "+f"(c[2]), "+f"(c[3]) : "r"(a0), "r"(a1), "r"(a2), "r"(a3), "r"(b0), "r"(b1));
}
__device__ __forceinline__ void mma16816_c(float (&c)[4], uint32_t a0, uint32_t a1, uint32_t a2, uint32_t a3, uint32_t b0, uint32_t b1, float ci) {
    asm volatile("mma.sync.aligned.m16n8k16.row.col.f32.bf16.bf16.f32 {%0,%1,%2,%3}, {%4,%5,%6,%7}, {%8,%9}, {%10,%10,%10,%10};"
        : "=f"(c[0]), "=f"(c[1]), "=f"(c[2]), "=f"(c[3]) : "r"(a0), "r"(a1), "r"(a2), "r"(a3), "r"(b0), "r"(b1), "f"(ci));
}
__device__ __forceinline__ int opaque(int v) { asm volatile("" : "+r"(v)); return v; }
__device__ __forceinline__ float ex2(float x) { float y; asm("ex2.approx.ftz.f32 %0, %1;" : "=f"(y) : "f"(x)); return y; }
__device__ __forceinline__ unsigned ld_acquire(const unsigned* p) {
    unsigned v; asm volatile("ld.acquire.gpu.global.u32 %0, [%1];" : "=r"(v) : "l"(p) : "memory"); return v;
}
__device__ __forceinline__ void red_release(unsigned* p, unsigned v) {
    asm volatile("red.release.gpu.global.add.u32 [%0], %1;" :: "l"(p), "r"(v) : "memory");
}
__device__ __forceinline__ void wait_counter(const unsigned* p, unsigned target) {
    uint32_t n = 0;
    while ((int)(ld_acquire(p) - target) < 0) { if (++n > (1u << 20)) break; }
}
__device__ __forceinline__ uint4 ldg_weak(const uint4* p) {
    uint4 v; asm volatile("ld.global.L1::no_allocate.v4.b32 {%0, %1, %2, %3}, [%4];" : "=r"(v.x), "=r"(v.y), "=r"(v.z), "=r"(v.w) : "l"(p) : "memory"); return v;
}
__device__ __forceinline__ float bf_lo(uint32_t v) { return __uint_as_float(v << 16); }
__device__ __forceinline__ float bf_hi(uint32_t v) { return __uint_as_float(v & 0xFFFF0000u); }

__device__ __forceinline__ void wgmma_ss_n64(float (&d)[32], uint64_t da, uint64_t db, int scale_d) {
    asm volatile("{\n.reg .pred p;\nsetp.ne.b32 p, %34, 0;\n"
        "wgmma.mma_async.sync.aligned.m64n64k16.f32.bf16.bf16 {%0, %1, %2, %3, %4, %5, %6, %7, %8, %9, %10, %11, %12, %13, %14, %15, %16, %17, %18, %19, %20, %21, %22, %23, %24, %25, %26, %27, %28, %29, %30, %31}, %32, %33, p, 1, 1, 0, 1;\n}\n"
        : "+f"(d[0]), "+f"(d[1]), "+f"(d[2]), "+f"(d[3]), "+f"(d[4]), "+f"(d[5]), "+f"(d[6]), "+f"(d[7]), "+f"(d[8]), "+f"(d[9]), "+f"(d[10]), "+f"(d[11]), "+f"(d[12]), "+f"(d[13]), "+f"(d[14]), "+f"(d[15]), "+f"(d[16]), "+f"(d[17]), "+f"(d[18]), "+f"(d[19]), "+f"(d[20]), "+f"(d[21]), "+f"(d[22]), "+f"(d[23]), "+f"(d[24]), "+f"(d[25]), "+f"(d[26]), "+f"(d[27]), "+f"(d[28]), "+f"(d[29]), "+f"(d[30]), "+f"(d[31])
        : "l"(da), "l"(db), "r"(scale_d));
}
__device__ __forceinline__ void wgmma_ss_n128(float (&d)[64], uint64_t da, uint64_t db, int scale_d) {
    asm volatile("{\n.reg .pred p;\nsetp.ne.b32 p, %66, 0;\n"
        "wgmma.mma_async.sync.aligned.m64n128k16.f32.bf16.bf16 {%0, %1, %2, %3, %4, %5, %6, %7, %8, %9, %10, %11, %12, %13, %14, %15, %16, %17, %18, %19, %20, %21, %22, %23, %24, %25, %26, %27, %28, %29, %30, %31, %32, %33, %34, %35, %36, %37, %38, %39, %40, %41, %42, %43, %44, %45, %46, %47, %48, %49, %50, %51, %52, %53, %54, %55, %56, %57, %58, %59, %60, %61, %62, %63}, %64, %65, p, 1, 1, 0, 1;\n}\n"
        : "+f"(d[0]), "+f"(d[1]), "+f"(d[2]), "+f"(d[3]), "+f"(d[4]), "+f"(d[5]), "+f"(d[6]), "+f"(d[7]), "+f"(d[8]), "+f"(d[9]), "+f"(d[10]), "+f"(d[11]), "+f"(d[12]), "+f"(d[13]), "+f"(d[14]), "+f"(d[15]), "+f"(d[16]), "+f"(d[17]), "+f"(d[18]), "+f"(d[19]), "+f"(d[20]), "+f"(d[21]), "+f"(d[22]), "+f"(d[23]), "+f"(d[24]), "+f"(d[25]), "+f"(d[26]), "+f"(d[27]), "+f"(d[28]), "+f"(d[29]), "+f"(d[30]), "+f"(d[31]), "+f"(d[32]), "+f"(d[33]), "+f"(d[34]), "+f"(d[35]), "+f"(d[36]), "+f"(d[37]), "+f"(d[38]), "+f"(d[39]), "+f"(d[40]), "+f"(d[41]), "+f"(d[42]), "+f"(d[43]), "+f"(d[44]), "+f"(d[45]), "+f"(d[46]), "+f"(d[47]), "+f"(d[48]), "+f"(d[49]), "+f"(d[50]), "+f"(d[51]), "+f"(d[52]), "+f"(d[53]), "+f"(d[54]), "+f"(d[55]), "+f"(d[56]), "+f"(d[57]), "+f"(d[58]), "+f"(d[59]), "+f"(d[60]), "+f"(d[61]), "+f"(d[62]), "+f"(d[63])
        : "l"(da), "l"(db), "r"(scale_d));
}
__device__ __forceinline__ void wgmma_ss_n200(float (&d)[100], uint64_t da, uint64_t db, int scale_d) {
    asm volatile("{\n.reg .pred p;\nsetp.ne.b32 p, %102, 0;\n"
        "wgmma.mma_async.sync.aligned.m64n200k16.f32.bf16.bf16 {%0, %1, %2, %3, %4, %5, %6, %7, %8, %9, %10, %11, %12, %13, %14, %15, %16, %17, %18, %19, %20, %21, %22, %23, %24, %25, %26, %27, %28, %29, %30, %31, %32, %33, %34, %35, %36, %37, %38, %39, %40, %41, %42, %43, %44, %45, %46, %47, %48, %49, %50, %51, %52, %53, %54, %55, %56, %57, %58, %59, %60, %61, %62, %63, %64, %65, %66, %67, %68, %69, %70, %71, %72, %73, %74, %75, %76, %77, %78, %79, %80, %81, %82, %83, %84, %85, %86, %87, %88, %89, %90, %91, %92, %93, %94, %95, %96, %97, %98, %99}, %100, %101, p, 1, 1, 0, 1;\n}\n"
        : "+f"(d[0]), "+f"(d[1]), "+f"(d[2]), "+f"(d[3]), "+f"(d[4]), "+f"(d[5]), "+f"(d[6]), "+f"(d[7]), "+f"(d[8]), "+f"(d[9]), "+f"(d[10]), "+f"(d[11]), "+f"(d[12]), "+f"(d[13]), "+f"(d[14]), "+f"(d[15]), "+f"(d[16]), "+f"(d[17]), "+f"(d[18]), "+f"(d[19]), "+f"(d[20]), "+f"(d[21]), "+f"(d[22]), "+f"(d[23]), "+f"(d[24]), "+f"(d[25]), "+f"(d[26]), "+f"(d[27]), "+f"(d[28]), "+f"(d[29]), "+f"(d[30]), "+f"(d[31]), "+f"(d[32]), "+f"(d[33]), "+f"(d[34]), "+f"(d[35]), "+f"(d[36]), "+f"(d[37]), "+f"(d[38]), "+f"(d[39]), "+f"(d[40]), "+f"(d[41]), "+f"(d[42]), "+f"(d[43]), "+f"(d[44]), "+f"(d[45]), "+f"(d[46]), "+f"(d[47]), "+f"(d[48]), "+f"(d[49]), "+f"(d[50]), "+f"(d[51]), "+f"(d[52]), "+f"(d[53]), "+f"(d[54]), "+f"(d[55]), "+f"(d[56]), "+f"(d[57]), "+f"(d[58]), "+f"(d[59]), "+f"(d[60]), "+f"(d[61]), "+f"(d[62]), "+f"(d[63]), "+f"(d[64]), "+f"(d[65]), "+f"(d[66]), "+f"(d[67]), "+f"(d[68]), "+f"(d[69]), "+f"(d[70]), "+f"(d[71]), "+f"(d[72]), "+f"(d[73]), "+f"(d[74]), "+f"(d[75]), "+f"(d[76]), "+f"(d[77]), "+f"(d[78]), "+f"(d[79]), "+f"(d[80]), "+f"(d[81]), "+f"(d[82]), "+f"(d[83]), "+f"(d[84]), "+f"(d[85]), "+f"(d[86]), "+f"(d[87]), "+f"(d[88]), "+f"(d[89]), "+f"(d[90]), "+f"(d[91]), "+f"(d[92]), "+f"(d[93]), "+f"(d[94]), "+f"(d[95]), "+f"(d[96]), "+f"(d[97]), "+f"(d[98]), "+f"(d[99])
        : "l"(da), "l"(db), "r"(scale_d));
}
__device__ __forceinline__ void wgmma_ss_n224(float (&d)[112], uint64_t da, uint64_t db, int scale_d) {
    asm volatile("{\n.reg .pred p;\nsetp.ne.b32 p, %114, 0;\n"
        "wgmma.mma_async.sync.aligned.m64n224k16.f32.bf16.bf16 {%0, %1, %2, %3, %4, %5, %6, %7, %8, %9, %10, %11, %12, %13, %14, %15, %16, %17, %18, %19, %20, %21, %22, %23, %24, %25, %26, %27, %28, %29, %30, %31, %32, %33, %34, %35, %36, %37, %38, %39, %40, %41, %42, %43, %44, %45, %46, %47, %48, %49, %50, %51, %52, %53, %54, %55, %56, %57, %58, %59, %60, %61, %62, %63, %64, %65, %66, %67, %68, %69, %70, %71, %72, %73, %74, %75, %76, %77, %78, %79, %80, %81, %82, %83, %84, %85, %86, %87, %88, %89, %90, %91, %92, %93, %94, %95, %96, %97, %98, %99, %100, %101, %102, %103, %104, %105, %106, %107, %108, %109, %110, %111}, %112, %113, p, 1, 1, 0, 1;\n}\n"
        : "+f"(d[0]), "+f"(d[1]), "+f"(d[2]), "+f"(d[3]), "+f"(d[4]), "+f"(d[5]), "+f"(d[6]), "+f"(d[7]), "+f"(d[8]), "+f"(d[9]), "+f"(d[10]), "+f"(d[11]), "+f"(d[12]), "+f"(d[13]), "+f"(d[14]), "+f"(d[15]), "+f"(d[16]), "+f"(d[17]), "+f"(d[18]), "+f"(d[19]), "+f"(d[20]), "+f"(d[21]), "+f"(d[22]), "+f"(d[23]), "+f"(d[24]), "+f"(d[25]), "+f"(d[26]), "+f"(d[27]), "+f"(d[28]), "+f"(d[29]), "+f"(d[30]), "+f"(d[31]), "+f"(d[32]), "+f"(d[33]), "+f"(d[34]), "+f"(d[35]), "+f"(d[36]), "+f"(d[37]), "+f"(d[38]), "+f"(d[39]), "+f"(d[40]), "+f"(d[41]), "+f"(d[42]), "+f"(d[43]), "+f"(d[44]), "+f"(d[45]), "+f"(d[46]), "+f"(d[47]), "+f"(d[48]), "+f"(d[49]), "+f"(d[50]), "+f"(d[51]), "+f"(d[52]), "+f"(d[53]), "+f"(d[54]), "+f"(d[55]), "+f"(d[56]), "+f"(d[57]), "+f"(d[58]), "+f"(d[59]), "+f"(d[60]), "+f"(d[61]), "+f"(d[62]), "+f"(d[63]), "+f"(d[64]), "+f"(d[65]), "+f"(d[66]), "+f"(d[67]), "+f"(d[68]), "+f"(d[69]), "+f"(d[70]), "+f"(d[71]), "+f"(d[72]), "+f"(d[73]), "+f"(d[74]), "+f"(d[75]), "+f"(d[76]), "+f"(d[77]), "+f"(d[78]), "+f"(d[79]), "+f"(d[80]), "+f"(d[81]), "+f"(d[82]), "+f"(d[83]), "+f"(d[84]), "+f"(d[85]), "+f"(d[86]), "+f"(d[87]), "+f"(d[88]), "+f"(d[89]), "+f"(d[90]), "+f"(d[91]), "+f"(d[92]), "+f"(d[93]), "+f"(d[94]), "+f"(d[95]), "+f"(d[96]), "+f"(d[97]), "+f"(d[98]), "+f"(d[99]), "+f"(d[100]), "+f"(d[101]), "+f"(d[102]), "+f"(d[103]), "+f"(d[104]), "+f"(d[105]), "+f"(d[106]), "+f"(d[107]), "+f"(d[108]), "+f"(d[109]), "+f"(d[110]), "+f"(d[111])
        : "l"(da), "l"(db), "r"(scale_d));
}
template <int N> __device__ __forceinline__ void fence_acc(float (&d)[N]) {
#pragma unroll
    for (int i = 0; i < N; i++) asm volatile("" : "+f"(d[i]) :: "memory");
}

__device__ __forceinline__ void bulk_s2g(void* dst, uint32_t src, uint32_t bytes) {
    asm volatile("cp.async.bulk.global.shared::cta.bulk_group [%0], [%1], %2;" :: "l"(dst), "r"(src), "r"(bytes) : "memory");
}
__device__ __forceinline__ void sts128(uint32_t addr, uint4 v) {
    asm volatile("st.shared.v4.b32 [%0], {%1, %2, %3, %4};" :: "r"(addr), "r"(v.x), "r"(v.y), "r"(v.z), "r"(v.w) : "memory");
}
__device__ __forceinline__ void sum_partials(uint32_t sb, int ti, int tj, int lane) {
    for (;;) {
        uint32_t item = 0;
        if (lane == 0) asm volatile("atom.shared.add.u32 %0, [%1], 1;" : "=r"(item) : "r"(sb + ITEM_OFF) : "memory");
        item = __shfl_sync(0xffffffffu, item, 0);
        if (item >= 8) break;
        const uint4* p = g_part + (size_t)((ti * 8 + tj) * 8) * 1024 + item * 128 + lane;
        uint4 v[4][4];
#pragma unroll
        for (int s = 0; s < 4; s++)
#pragma unroll
            for (int n = 0; n < 4; n++) v[n][s] = ldg_weak(p + s * 1024 + n * 32);
#pragma unroll
        for (int n = 0; n < 4; n++) {
            float a[8];
#pragma unroll
            for (int e = 0; e < 8; e++) a[e] = 0.f;
#pragma unroll
            for (int s = 0; s < 4; s++) {
                a[0] += bf_lo(v[n][s].x); a[1] += bf_hi(v[n][s].x); a[2] += bf_lo(v[n][s].y); a[3] += bf_hi(v[n][s].y);
                a[4] += bf_lo(v[n][s].z); a[5] += bf_hi(v[n][s].z); a[6] += bf_lo(v[n][s].w); a[7] += bf_hi(v[n][s].w);
            }
            const uint32_t d = sb + HSUM_OFF + (item * 8 + n * 2) * 512 + lane * 16;
            sts128(d, make_uint4(__float_as_uint(a[0]), __float_as_uint(a[1]), __float_as_uint(a[2]), __float_as_uint(a[3])));
            sts128(d + 512, make_uint4(__float_as_uint(a[4]), __float_as_uint(a[5]), __float_as_uint(a[6]), __float_as_uint(a[7])));
        }
    }
    __syncwarp();
    if (lane == 0) mbar_arrive(sb + B_HSUM);
}

#define PWAIT() mbar_wait(sb + B_EMPTY + 8 * r.slot, r.phase)
#define CWAIT() do { if (!dry) mbar_wait(sb + B_FULL + 8 * r.slot, r.phase); } while (0)
template <bool B> struct BoolTag { static constexpr bool value = B; };
struct Ring {
    int slot; uint32_t phase;
    __device__ __forceinline__ void next() { if (++slot == RING) { slot = 0; phase ^= 1; } }
};

__global__ void __launch_bounds__(384, 1)
fused_kernel(const __grid_constant__ CUtensorMap map_x, const __grid_constant__ CUtensorMap map_qkv,
             const __grid_constant__ CUtensorMap map_w1, const __grid_constant__ CUtensorMap map_w2,
             const __grid_constant__ CUtensorMap map_wo, const __grid_constant__ CUtensorMap map_w1a,
             const __grid_constant__ CUtensorMap map_o,
             const __nv_bfloat16* __restrict__ gate_w, __nv_bfloat16* __restrict__ out,
             const uint8_t* __restrict__ w1p, const uint8_t* __restrict__ w2p, const uint8_t* __restrict__ wop)
{
    extern __shared__ __align__(1024) uint8_t smem_raw[];
    const uint32_t sb = smem_u32(smem_raw);
    const int tid = threadIdx.x, warp = tid >> 5, lane = tid & 31;
    const bool dry = blockIdx.x >= 128;
    const int ti = dry ? (int)(blockIdx.x & 1) * 2 : blockIdx.x >> 3, tj = blockIdx.x & 7;
    if (dry && warp >= 8) {
        asm volatile("setmaxnreg.dec.sync.aligned.u32 88;");
        return;
    }

    if (tid == 0 && !dry) { TSG(31); TSX(0); }
    if (tid == 320) {
        asm volatile("prefetch.tensormap [%0];" :: "l"(&map_x) : "memory");
        asm volatile("prefetch.tensormap [%0];" :: "l"(&map_qkv) : "memory");
        asm volatile("prefetch.tensormap [%0];" :: "l"(&map_w1) : "memory");
        asm volatile("prefetch.tensormap [%0];" :: "l"(&map_w1a) : "memory");
        asm volatile("prefetch.tensormap [%0];" :: "l"(&map_w2) : "memory");
        asm volatile("prefetch.tensormap [%0];" :: "l"(&map_wo) : "memory");
        asm volatile("prefetch.tensormap [%0];" :: "l"(&map_o) : "memory");
    }
    if (tid == 256) {
        mbar_init(sb + B_FULL, 1); mbar_init(sb + B_XFULL, 1);
        fence_async_smem();
        mbar_expect_tx(sb + B_XFULL, 16384);
        tma_2d(sb + X_OFF, &map_x, sb + B_XFULL, 0, ti * 128);
        mbar_expect_only(sb + B_FULL, 12288);
        tma_4d(sb + RING_OFF, &map_qkv, sb + B_FULL, 0, 0, tj, 0);
    }
    uint32_t gwv[N_QKV / 2];
    if (warp == 8) {
        const unsigned short* gws = reinterpret_cast<const unsigned short*>(gate_w);
#pragma unroll
        for (int n = 0; n < N_QKV / 2; n++) gwv[n] = (uint32_t)__ldg(gws + 64 * n + lane) | ((uint32_t)__ldg(gws + 64 * n + 32 + lane) << 16);
    }
    if (tid == 288) {
        for (int s = 1; s < RING; s++) mbar_init(sb + B_FULL + 8 * s, 1);
        for (int s = 0; s < RING; s++) mbar_init(sb + B_EMPTY + 8 * s, 8);
        for (int s = 1; s < 8; s++) mbar_init(sb + B_XFULL + 8 * s, 1);
        fence_async_smem();
    }
    if (tid == 352) {
        mbar_init(sb + B_HDEAD, 8); mbar_init(sb + B_EREADY, 1); mbar_init(sb + B_KVDONE, 8); mbar_init(sb + B_KVREADY, 1);
        mbar_init(sb + B_ODONE, 8); mbar_init(sb + B_WOFULL, 1); mbar_init(sb + B_HSUM, 3);
        mbar_init(sb + B_PREADY, 1); mbar_init(sb + B_SF, 1); mbar_init(sb + B_SF + 8, 1);
        for (int s = 0; s < 4; s++) mbar_init(sb + B_SQ + 8 * s, 8);
        asm volatile("st.shared.u32 [%0], %1;" :: "r"(sb + ITEM_OFF), "r"(0) : "memory");
        fence_async_smem();
    }
    if (!dry) __syncthreads();

    if (warp >= 8) {
        asm volatile("setmaxnreg.dec.sync.aligned.u32 88;");
        if (warp == 8) {
            Ring r{0, 1};
            const bool leader = elect_one();
#pragma unroll
            for (int n = 0; n < N_QKV; n++) {
                const uint32_t full = sb + B_FULL + 8 * r.slot, dst = sb + RING_OFF + r.slot * SLOT;
                if (n > 0) {
                    if (!(n & 1) && leader) {
                        mbar_expect_tx(sb + B_XFULL + 8 * (n >> 1), 16384);
                        tma_2d(sb + X_OFF + (n >> 1) * 16384, &map_x, sb + B_XFULL + 8 * (n >> 1), (n >> 1) * 64, ti * 128);
                    }
                    if (n >= RING) PWAIT();
                    if (leader) {
                        mbar_expect_only(full, 12288);
                        tma_4d(dst, &map_qkv, full, 0, 32 * n, tj, 0);
                    }
                }
                const uint32_t gv = (n & 1) ? (gwv[n >> 1] >> 16) : (gwv[n >> 1] & 0xFFFFu);
                asm volatile("st.shared.v4.b32 [%0], {%1, %2, %2, %2};" :: "r"(dst + 12288 + lane * 128 + ((lane & 7) << 4)), "r"(gv), "r"(0) : "memory");
                fence_async_smem();
                __syncwarp();
                if (leader) mbar_arrive(full);
                r.next();
            }
#pragma unroll 1
            for (int n = 0; n < N_FFN1; n++) {
                const uint32_t full = sb + B_FULL + 8 * r.slot, dst = sb + RING_OFF + r.slot * SLOT;
                PWAIT();
                if (leader) {
                    mbar_expect_tx(full, 16384);
                    tma_4d(dst, &map_w1a, full, 0, 32 * n, 0, tj);
                    tma_2d(dst + 3 * 4096, &map_w1, full, 224 * tj + 192, 32 * n);
                }
                r.next();
            }
            {
                int q = 0, rr = 0;
#pragma unroll 1
                for (int n = 0; n < N_FFN2; n++) {
                    const uint32_t full = sb + B_FULL + 8 * r.slot, dst = sb + RING_OFF + r.slot * SLOT;
                    PWAIT();
                    if (leader) mbar_expect_tx(full, 16384);
#pragma unroll
                    for (int h = 0; h < 2; h++) {
                        if (leader) tma_3d(dst + h * 8192, &map_w2, full, 0, 224 * tj + 32 * rr, 2 * q);
                        if (++rr == 7) { rr = 0; q++; }
                    }
                    r.next();
                }
            }
            mbar_wait(sb + B_KVREADY, 0);
            asm volatile("fence.proxy.async.global;" ::: "memory");
            {
                const int bbase = 8 * ti - 16, b0 = bbase < 0 ? 0 : bbase;
                const uint32_t bytes = (uint32_t)(8 * ti + 8 - b0) * 512;
#pragma unroll 1
                for (int m = 0; m < N_KV; m++) {
                    const uint32_t full = sb + B_FULL + 8 * r.slot, dst = sb + RING_OFF + r.slot * SLOT;
                    if (m == RING) {
                        mbar_wait(sb + B_HDEAD, 0);
                        if (leader) {
                            mbar_expect_tx(sb + B_WOFULL, 65536);
#pragma unroll
                            for (int e = 0; e < 2; e++) tma_2d(sb + X_OFF + e * 32768, &map_wo, sb + B_WOFULL, 64 * tj, 256 * e);
                        }
                    }
                    PWAIT();
                    if (leader) {
                        const uint4* src = ((m & 1) ? g_vf : g_kf) + ((tj * 4 + (m >> 1)) * 128 + b0) * 32;
                        mbar_expect_tx(full, bytes);
                        bulk_g2s(dst + (b0 - bbase) * 512, src, bytes, full);
                    }
                    r.next();
                }
            }
            {
                mbar_wait(sb + B_EREADY, 0);
                unsigned epoch; asm volatile("ld.shared.u32 %0, [%1];" : "=r"(epoch) : "r"(sb + EPOCH_OFF) : "memory");
                uint32_t pending = 0xFFu & ~(1u << tj), ready = 0;
                mbar_wait(sb + B_HSUM, 0);
#pragma unroll 1
                for (int m = 0; m < N_O; m++) {
                    const uint32_t full = sb + B_FULL + 8 * r.slot, dst = sb + RING_OFF + r.slot * SLOT;
                    PWAIT();
                    for (int it = 0; it < (1 << 20) && !ready; it++) {
                        bool ok = false;
                        if (lane < 8 && ((pending >> lane) & 1)) ok = (int)(ld_acquire(&g_ocnt[(ti * 8 + lane) * 32]) - (epoch + 1)) >= 0;
                        ready = __ballot_sync(0xffffffffu, ok);
                        if (!ready) __nanosleep(100);
                    }
                    const int js = ready ? __ffs(ready) - 1 : __ffs(pending) - 1;
                    pending &= ~(1u << js); ready &= ~(1u << js);
                    asm volatile("fence.proxy.async.global;" ::: "memory");
                    if (leader) {
                        asm volatile("st.shared.u32 [%0], %1;" :: "r"(sb + OSRC_OFF + 4 * m), "r"(js) : "memory");
                        mbar_expect_tx(full, 16384);
                        tma_2d(dst, &map_o, full, 64 * js, ti * 128);
                    }
                    r.next();
                }
            }
        } else if (warp == 9) {
            unsigned epoch = 0;
            if (lane == 0) {
                epoch = atomicAdd(&g_ticket, 1u) >> 7;
                asm volatile("st.shared.u32 [%0], %1;" :: "r"(sb + EPOCH_OFF), "r"(epoch) : "memory");
                mbar_arrive(sb + B_EREADY);
                mbar_wait(sb + B_XFULL + 8 * PF1_AT, 0);
                prefetch_l2(w1p + (size_t)blockIdx.x * 14336, 14336);
                mbar_wait(sb + B_XFULL + 8 * PF2_AT, 0);
                prefetch_l2(w2p + (size_t)blockIdx.x * 14336, 14336);
                prefetch_l2(wop + (size_t)blockIdx.x * 4096, 4096);
                mbar_wait(sb + B_KVDONE, 0);
                red_release(&g_kvcnt[blockIdx.x * 32], 1u);
            }
            epoch = __shfl_sync(0xffffffffu, epoch, 0);
            if (lane < 3 && ti - lane >= 0) wait_counter(&g_kvcnt[((ti - lane) * 8 + tj) * 32], epoch + 1);
            __syncwarp();
            if (lane == 0) mbar_arrive(sb + B_KVREADY);
            mbar_wait(sb + B_SQ + 24, 0);
            if (lane < 8) wait_counter(&g_pcnt[(ti * 8 + lane) * 32], epoch + 1);
            __syncwarp();
            if (lane == 0) { mbar_arrive(sb + B_PREADY); TSX(13); }
            sum_partials(sb, ti, tj, lane);
            if (lane == 0) TSX(14);
        } else {
            if (warp == 10) {
#pragma unroll 1
                for (int q = 0; q < 4; q++) {
                    mbar_wait(sb + B_SQ + 8 * q, 0);
                    if (lane < 16) {
                        uint4* d = g_part + (size_t)(((ti * 8 + 2 * q + (lane & 1)) * 8 + tj) * 8 + (lane >> 1)) * 128;
                        bulk_s2g(d, sb + STG_OFF + (q & 1) * 32768 + lane * 2048, 2048);
                        asm volatile("cp.async.bulk.commit_group;" ::: "memory");
                        asm volatile("cp.async.bulk.wait_group.read 0;" ::: "memory");
                    }
                    __syncwarp();
                    if (lane == 0) mbar_arrive(sb + B_SF + 8 * (q & 1));
                }
                asm volatile("cp.async.bulk.wait_group 0;" ::: "memory");
                asm volatile("fence.proxy.async.global;" ::: "memory");
                __syncwarp();
                if (lane == 0) { red_release(&g_pcnt[blockIdx.x * 32], 1u); TSX(12); }
            }
            mbar_wait(sb + B_PREADY, 0);
            sum_partials(sb, ti, tj, lane);
            if (warp == 11 && lane == 0) {
                mbar_wait(sb + B_ODONE, 0);
                red_release(&g_ocnt[blockIdx.x * 32], 1u);
            }
        }
    } else {
        asm volatile("setmaxnreg.inc.sync.aligned.u32 208;");
        const int wg = warp >> 2, g = lane >> 2, c = lane & 3;
        const uint32_t xa = sb + X_OFF + wg * 8192;
        Ring r{0, 0};
        const bool lane0 = lane == 0 && !dry;
        uint32_t qf[4][4];
        float g0, g1;
        TS(9);
        {
            float acc[100];
            int prev = 0;
            if (wg == 1) asm volatile("bar.sync 3, 256;" ::: "memory");
            for (int s = 0; s < (dry ? 4 : N_QKV); s++) {
                if (!(s & 1) && !dry) mbar_wait(sb + B_XFULL + 8 * (s >> 1), 0);
                CWAIT();
                if (s == 0) TS(1);
                if (s == 2) TS(28);
                if (s == 6) TS(29);
                if (s == 10) TS(20);
                const uint32_t bs = sb + RING_OFF + r.slot * SLOT, as = xa + (s >> 1) * 16384 + (s & 1) * 64;
                wgmma_fence();
                wgmma_ss_n200(acc, desc_a(as), desc_b(bs), s);
                wgmma_ss_n200(acc, desc_a(as + 32), desc_b(bs + 2048), 1);
                wgmma_commit();
                if (wg == 0 && s == LEAD1) asm volatile("bar.arrive 3, 256;" ::: "memory");
                if (s > 0) { wgmma_wait<1>(); if (lane0) mbar_arrive(sb + B_EMPTY + 8 * prev); }
                prev = r.slot; r.next();
            }
            wgmma_wait<0>();
            fence_acc(acc);
            if (lane0) mbar_arrive(sb + B_EMPTY + 8 * prev);
            TS(2);
            const int blk = ti * 8 + warp;
#pragma unroll
            for (int hh = 0; hh < 4; hh++) {
                const float* t0 = &acc[8 * hh]; const float* t1 = &acc[8 * hh + 4];
                qf[hh][0] = pack_bf16(t0[0], t0[1]); qf[hh][1] = pack_bf16(t0[2], t0[3]);
                qf[hh][2] = pack_bf16(t1[0], t1[1]); qf[hh][3] = pack_bf16(t1[2], t1[3]);
                const float* k0 = &acc[32 + 8 * hh]; const float* k1 = &acc[32 + 8 * hh + 4];
                uint4 kv;
                kv.x = pack_bf16(k0[0], k0[1]); kv.y = pack_bf16(k1[0], k1[1]);
                kv.z = pack_bf16(k0[2], k0[3]); kv.w = pack_bf16(k1[2], k1[3]);
                if (!dry) g_kf[((tj * 4 + hh) * 128 + blk) * 32 + lane] = kv;
                const float* v0 = &acc[64 + 8 * hh]; const float* v1 = &acc[64 + 8 * hh + 4];
                uint4 vv;
                vv.x = movmatrix(pack_bf16(v0[0], v0[1])); vv.y = movmatrix(pack_bf16(v0[2], v0[3]));
                vv.z = movmatrix(pack_bf16(v1[0], v1[1])); vv.w = movmatrix(pack_bf16(v1[2], v1[3]));
                if (!dry) g_vf[((tj * 4 + hh) * 128 + blk) * 32 + lane] = vv;
            }
            __syncwarp();
            if (lane0) mbar_arrive(sb + B_KVDONE);
            const float z0 = __shfl_sync(0xffffffffu, acc[96], lane & ~3), z1 = __shfl_sync(0xffffffffu, acc[98], lane & ~3);
            g0 = 1.f / (1.f + __expf(-z0)); g1 = 1.f / (1.f + __expf(-z1));
        }
        TS(3);
        const int wrow = (warp & 3) * 16;
        {
            float acc[112];
            int prev = 0;
            for (int s = 0; s < (dry ? 4 : N_FFN1); s++) {
                CWAIT();
                const uint32_t bs = sb + RING_OFF + r.slot * SLOT, as = xa + (s >> 1) * 16384 + (s & 1) * 64;
                wgmma_fence();
                wgmma_ss_n224(acc, desc_a(as), desc_b(bs), s);
                wgmma_ss_n224(acc, desc_a(as + 32), desc_b(bs + 2048), 1);
                wgmma_commit();
                if (s > 0) { wgmma_wait<1>(); if (lane0) mbar_arrive(sb + B_EMPTY + 8 * prev); }
                prev = r.slot; r.next();
            }
            wgmma_wait<0>();
            fence_acc(acc);
            if (lane0) mbar_arrive(sb + B_EMPTY + 8 * prev);
            TS(4);
            const float s0 = 1.f - g0, s1 = 1.f - g1;
            asm volatile("bar.sync %0, 128;" :: "r"(1 + wg) : "memory");
            const uint32_t strow = xa + (wrow + ((lane >> 3) & 1) * 8 + (lane & 7)) * 128;
#pragma unroll
            for (int p = 0; p < 14; p++) {
                const int nt = 2 * p + (lane >> 4);
                const float* a = &acc[8 * p];
                stmatrix_x4(strow + (p >> 2) * 16384 + (((nt & 7) ^ (lane & 7)) << 4),
                            pack_bf16_relu(a[0] * s0, a[1] * s0), pack_bf16_relu(a[2] * s1, a[3] * s1),
                            pack_bf16_relu(a[4] * s0, a[5] * s0), pack_bf16_relu(a[6] * s1, a[7] * s1));
            }
        }
        TS(5);
        {
            fence_async_smem();
            asm volatile("bar.sync 4, 256;" ::: "memory");
            float accA[64], accB[64];
            auto epilogue = [&](float (&acc)[64], int q) {
                fence_acc(acc);
                const uint32_t st = sb + STG_OFF + (q & 1) * 32768 + warp * 4096;
                if (q >= 2 && !dry) mbar_wait(sb + B_SF + 8 * (q & 1), 0);
#pragma unroll
                for (int t2 = 0; t2 < 8; t2++) {
                    uint4 v;
                    v.x = pack_bf16(acc[8 * t2 + 0], acc[8 * t2 + 1]); v.y = pack_bf16(acc[8 * t2 + 2], acc[8 * t2 + 3]);
                    v.z = pack_bf16(acc[8 * t2 + 4], acc[8 * t2 + 5]); v.w = pack_bf16(acc[8 * t2 + 6], acc[8 * t2 + 7]);
                    sts128(st + t2 * 512 + lane * 16, v);
                }
                fence_async_smem();
                __syncwarp();
                if (lane0) mbar_arrive(sb + B_SQ + 8 * q);
            };
            int rel = r.slot;
#pragma unroll
            for (int m = 0; m < N_FFN2; m++) {
                CWAIT();
                wgmma_fence();
#pragma unroll
                for (int h = 0; h < 2; h++) {
                    const int u = 2 * m + h, q = u / 7, rr = u % 7;
                    const uint32_t bs = sb + RING_OFF + r.slot * SLOT + h * 8192;
                    const uint32_t as = xa + (rr >> 1) * 16384 + (rr & 1) * 64;
                    if (!(q & 1)) {
                        wgmma_ss_n128(accA, desc_a(as), desc_b(bs), rr);
                        wgmma_ss_n128(accA, desc_a(as + 32), desc_b(bs + 2048), 1);
                    } else {
                        wgmma_ss_n128(accB, desc_a(as), desc_b(bs), rr);
                        wgmma_ss_n128(accB, desc_a(as + 32), desc_b(bs + 2048), 1);
                    }
                }
                wgmma_commit();
                r.next();
                wgmma_wait<1>();
                if (m > 0) {
                    if (lane0) mbar_arrive(sb + B_EMPTY + 8 * rel);
                    if (++rel == RING) rel = 0;
                }
                if (m == 4) { TS(25); epilogue(accA, 0); }
                if (m == 7) { TS(26); epilogue(accB, 1); }
                if (m == 11) { TS(27); epilogue(accA, 2); }
            }
            wgmma_wait<0>();
            if (lane0) { mbar_arrive(sb + B_EMPTY + 8 * rel); mbar_arrive(sb + B_HDEAD); }
            epilogue(accB, 3);
        }
        TS(6);
        {
            const float SC = 0.25f * 1.4426950408889634f;
            const int gb0 = 8 * ti - 16 + warp;
            int slotK = 0, slotV = 0;
            const uint32_t ostore = sb + OWN_OFF + (warp * 16 + ((lane >> 3) & 1) * 8 + (lane & 7)) * 128;
            uint32_t* odst = reinterpret_cast<uint32_t*>(g_o + (size_t)(ti * 128 + warp * 16 + g) * 512 + tj * 64 + ((lane & 1) ? 8 : 0) + (lane & 2) * 2);
#define NHEADS (dry ? 2 : 4)
#define ATT_KWAIT(kb) do { slotK = r.slot; CWAIT(); kb = sb + RING_OFF + slotK * SLOT + warp * 512 + lane * 16; r.next(); } while (0)
#define ATT_VWAIT(vb) do { slotV = r.slot; CWAIT(); vb = sb + RING_OFF + slotV * SLOT + warp * 512 + lane * 16; r.next(); TS(21 + hh); } while (0)
#define ATT_KREL() do { __syncwarp(); if (lane0) mbar_arrive(sb + B_EMPTY + 8 * slotK); } while (0)
#define ATT_VREL() do { __syncwarp(); if (lane0) mbar_arrive(sb + B_EMPTY + 8 * slotV); } while (0)
#define ATT_NEXTQ(h) do { \
                if ((h) == 1) { q0 = qf[1][0]; q1 = qf[1][1]; q2 = qf[1][2]; q3 = qf[1][3]; } \
                else if ((h) == 2) { q0 = qf[2][0]; q1 = qf[2][1]; q2 = qf[2][2]; q3 = qf[2][3]; } \
                else { q0 = qf[3][0]; q1 = qf[3][1]; q2 = qf[3][2]; q3 = qf[3][3]; } } while (0)
#define ATT_STORE(h, r0, r1, r2, r3) do { \
                if ((h) == 0 && !dry) mbar_wait(sb + B_SF, 1);        \
                stmatrix_x4(ostore + (((2 * (h) + (lane >> 4)) ^ (lane & 7)) << 4), r0, r1, r2, r3); \
                const bool odd = lane & 1; \
                const uint32_t sl = __shfl_xor_sync(0xffffffffu, odd ? (r0) : (r2), 1), sh = __shfl_xor_sync(0xffffffffu, odd ? (r1) : (r3), 1); \
                if (!dry) *reinterpret_cast<uint2*>(odst + 8 * (h)) = odd ? make_uint2(sl, r2) : make_uint2(r0, sl); \
                if (!dry) *reinterpret_cast<uint2*>(odst + 8 * (h) + 8 * 256) = odd ? make_uint2(sh, r3) : make_uint2(r1, sh); \
                } while (0)
            auto attention = [&](auto masked_tag) {
            constexpr bool MASKED = decltype(masked_tag)::value;
            const float NEG = -INFINITY;
            const uint32_t ONES = 0x3F803F80u;
            float sa[8][2][4];
            float o[2][4], ls[4];
            float m0, m1;
            uint32_t q0 = qf[0][0], q1 = qf[0][1], q2 = qf[0][2], q3 = qf[0][3];
            auto qk = [&](float (&s)[8][2][4], int ps, int t, uint32_t kbase, bool merged) {
                if (merged) {
                    const uint4 kd = lds128(kbase + 16 * 512);
                    const uint4 kf = lds128(kbase);
                    float f[2][4];
                    const float ci = (!MASKED || opaque(gb0) >= 0) ? 0.f : NEG;
                    mma16816_c(s[0][0], q0, q1, q2, q3, kd.x, kd.y, 0.f);
                    mma16816_c(s[0][1], q0, q1, q2, q3, kd.z, kd.w, 0.f);
                    mma16816_c(f[0], q0, q1, q2, q3, kf.x, kf.y, ci);
                    mma16816_c(f[1], q0, q1, q2, q3, kf.z, kf.w, ci);
#pragma unroll
                    for (int u = 0; u < 2; u++)
#pragma unroll
                        for (int e = 0; e < 4; e++) {
                            const int row = g + 8 * (e >> 1), col = 8 * u + 2 * c + (e & 1);
                            s[0][u][e] = (col > row) ? f[u][e] : s[0][u][e];
                        }
                } else {
                    const uint4 kf = lds128(kbase + (8 * ps + t) * 512);
                    const float ci = (!MASKED || opaque(gb0) + 8 * ps + t >= 0) ? 0.f : NEG;
                    mma16816_c(s[t][0], q0, q1, q2, q3, kf.x, kf.y, ci);
                    mma16816_c(s[t][1], q0, q1, q2, q3, kf.z, kf.w, ci);
                }
            };
            auto rowmax = [&](float (&s)[8][2][4], float b0, float b1, float& n0, float& n1) {
                int i0 = __float_as_int(b0), i1 = __float_as_int(b1);
#pragma unroll
                for (int t = 0; t < 8; t++)
#pragma unroll
                    for (int u = 0; u < 2; u++) {
                        i0 = __vimax3_s32(i0, __float_as_int(s[t][u][0]), __float_as_int(s[t][u][1]));
                        i1 = __vimax3_s32(i1, __float_as_int(s[t][u][2]), __float_as_int(s[t][u][3]));
                    }
                i0 = max(i0, __shfl_xor_sync(0xffffffffu, i0, 1)); i1 = max(i1, __shfl_xor_sync(0xffffffffu, i1, 1));
                i0 = max(i0, __shfl_xor_sync(0xffffffffu, i0, 2)); i1 = max(i1, __shfl_xor_sync(0xffffffffu, i1, 2));
                n0 = __int_as_float(i0); n1 = __int_as_float(i1);
                if (__any_sync(0xffffffffu, (i0 | i1) < 0)) {
                    asm volatile("" ::: "memory");
                    n0 = b0; n1 = b1;
#pragma unroll
                    for (int t = 0; t < 8; t++)
#pragma unroll
                        for (int u = 0; u < 2; u++) {
                            n0 = fmaxf(n0, fmaxf(s[t][u][0], s[t][u][1]));
                            n1 = fmaxf(n1, fmaxf(s[t][u][2], s[t][u][3]));
                        }
                    n0 = fmaxf(n0, __shfl_xor_sync(0xffffffffu, n0, 1)); n1 = fmaxf(n1, __shfl_xor_sync(0xffffffffu, n1, 1));
                    n0 = fmaxf(n0, __shfl_xor_sync(0xffffffffu, n0, 2)); n1 = fmaxf(n1, __shfl_xor_sync(0xffffffffu, n1, 2));
                }
            };
            auto pv = [&](const float (&p)[2][4], uint32_t vaddr) {
                const uint4 vf = lds128(vaddr);
                const uint32_t a0 = pack_bf16(p[0][0], p[0][1]), a1 = pack_bf16(p[0][2], p[0][3]);
                const uint32_t a2 = pack_bf16(p[1][0], p[1][1]), a3 = pack_bf16(p[1][2], p[1][3]);
                mma16816(o[0], a0, a1, a2, a3, vf.x, vf.y);
                mma16816(o[1], a0, a1, a2, a3, vf.z, vf.w);
                mma16816(ls, a0, a1, a2, a3, ONES, ONES);
            };
            auto expv = [&](float (&s)[8][2][4], int ps, int t, float mc0, float mc1, uint32_t vbase, bool merged) {
                float p[2][4];
#pragma unroll
                for (int u = 0; u < 2; u++) {
                    p[u][0] = ex2(fmaf(s[t][u][0], SC, -mc0)); p[u][1] = ex2(fmaf(s[t][u][1], SC, -mc0));
                    p[u][2] = ex2(fmaf(s[t][u][2], SC, -mc1)); p[u][3] = ex2(fmaf(s[t][u][3], SC, -mc1));
                }
                if (merged) {
                    float pd[2][4], pf[2][4];
#pragma unroll
                    for (int u = 0; u < 2; u++)
#pragma unroll
                        for (int e = 0; e < 4; e++) {
                            const int row = g + 8 * (e >> 1), col = 8 * u + 2 * c + (e & 1);
                            pf[u][e] = (col > row) ? p[u][e] : 0.f;
                            pd[u][e] = (col > row) ? 0.f : p[u][e];
                        }
                    pv(pd, vbase + 16 * 512);
                    pv(pf, vbase);
                } else {
                    pv(p, vbase + (8 * ps + t) * 512);
                }
            };
            uint32_t kbase = 0, vbase = 0;
#pragma unroll 1
            for (int hh = 0; hh < NHEADS; hh++) {
                ATT_KWAIT(kbase);
                if (hh > 0) ATT_NEXTQ(hh);
#pragma unroll
                for (int ps = 0; ps < 2; ps++) {
#pragma unroll
                    for (int t = 0; t < 8; t++) qk(sa, ps, t, kbase, ps == 0 && t == 0);
                    if (ps == 1) ATT_KREL();
                    float n0, n1;
                    rowmax(sa, ps ? m0 : NEG, ps ? m1 : NEG, n0, n1);
                    if (ps == 0) {
                        ATT_VWAIT(vbase);
#pragma unroll
                        for (int e = 0; e < 4; e++) { o[0][e] = 0.f; o[1][e] = 0.f; ls[e] = 0.f; }
                    } else {
                        const float a0 = ex2((m0 - n0) * SC), a1 = ex2((m1 - n1) * SC);
                        ls[0] *= a0; ls[2] *= a1;
                        o[0][0] *= a0; o[0][1] *= a0; o[1][0] *= a0; o[1][1] *= a0;
                        o[0][2] *= a1; o[0][3] *= a1; o[1][2] *= a1; o[1][3] *= a1;
                    }
                    m0 = n0; m1 = n1;
                    const float mc0 = n0 * SC, mc1 = n1 * SC;
#pragma unroll
                    for (int t = 0; t < 8; t++) expv(sa, ps, t, mc0, mc1, vbase, ps == 0 && t == 0);
                }
                ATT_VREL();
                const float f0 = __fdividef(g0, ls[0]), f1 = __fdividef(g1, ls[2]);
                ATT_STORE(hh, pack_bf16(o[0][0] * f0, o[0][1] * f0), pack_bf16(o[0][2] * f1, o[0][3] * f1),
                              pack_bf16(o[1][0] * f0, o[1][1] * f0), pack_bf16(o[1][2] * f1, o[1][3] * f1));
            }
            };
            if (ti >= 2) attention(BoolTag<false>{}); else attention(BoolTag<true>{});
            fence_async_smem();
            __syncwarp();
            if (lane0) mbar_arrive(sb + B_ODONE);
        }
        TS(7);
        {
            float acc[32];
            uint4 pv[4][4];
            if (!dry) mbar_wait(sb + B_PREADY, 0);
            {
                const uint4* p = g_part + (size_t)((ti * 8 + tj) * 8 + 4) * 1024 + warp * 128 + lane;
#pragma unroll
                for (int s = 0; s < 4; s++)
#pragma unroll
                    for (int n = 0; n < 4; n++) pv[n][s] = dry ? make_uint4(0u, 0u, 0u, 0u) : ldg_weak(p + s * 1024 + n * 32);
            }
            if (!dry) mbar_wait(sb + B_WOFULL, 0);
            if (!dry) mbar_wait(sb + B_ODONE, 0);
            TS(15);
            wgmma_fence();
#pragma unroll
            for (int k = 0; k < 4; k++) wgmma_ss_n64(acc, desc_a(sb + OWN_OFF + wg * 8192 + 32 * k), desc_b(sb + X_OFF + tj * 8192 + 2048 * k), k);
            wgmma_commit();
            TS(16);
#pragma unroll 1
            for (int m = 0; m < N_O; m++) {
                CWAIT();
                uint32_t js; asm volatile("ld.shared.u32 %0, [%1];" : "=r"(js) : "r"(sb + OSRC_OFF + 4 * m) : "memory");
                const uint32_t as = sb + RING_OFF + r.slot * SLOT + wg * 8192;
                const uint32_t bs = sb + X_OFF + (js & 7) * 8192;
                wgmma_fence();
#pragma unroll
                for (int k = 0; k < 4; k++) wgmma_ss_n64(acc, desc_a(as + 32 * k), desc_b(bs + 2048 * k), 1);
                wgmma_commit();
                if (m == 0) { wgmma_wait<0>(); if (lane0) mbar_arrive(sb + B_EMPTY + 8 * r.slot); }
                r.next();
            }
            float base[32];
            if (!dry) mbar_wait(sb + B_HSUM, 0);
#pragma unroll
            for (int n = 0; n < 4; n++) {
                const uint4 u0 = lds128(sb + HSUM_OFF + (warp * 8 + 2 * n) * 512 + lane * 16), u1 = lds128(sb + HSUM_OFF + (warp * 8 + 2 * n + 1) * 512 + lane * 16);
                float* a = &base[8 * n];
                a[0] = __uint_as_float(u0.x); a[1] = __uint_as_float(u0.y); a[2] = __uint_as_float(u0.z); a[3] = __uint_as_float(u0.w);
                a[4] = __uint_as_float(u1.x); a[5] = __uint_as_float(u1.y); a[6] = __uint_as_float(u1.z); a[7] = __uint_as_float(u1.w);
#pragma unroll
                for (int s = 0; s < 4; s++) {
                    a[0] += bf_lo(pv[n][s].x); a[1] += bf_hi(pv[n][s].x); a[2] += bf_lo(pv[n][s].y); a[3] += bf_hi(pv[n][s].y);
                    a[4] += bf_lo(pv[n][s].z); a[5] += bf_hi(pv[n][s].z); a[6] += bf_lo(pv[n][s].w); a[7] += bf_hi(pv[n][s].w);
                }
            }
            fence_acc(base);
            wgmma_wait<0>();
            fence_acc(acc);
            TS(17);
#pragma unroll
            for (int k = 0; k < 32; k++) acc[k] += base[k];
            __nv_bfloat16* o = out + (size_t)(ti * 128 + warp * 16 + g) * 512 + tj * 64 + ((lane & 1) ? 8 : 0) + (lane & 2) * 2;
            const bool odd = lane & 1;
#pragma unroll
            for (int t2 = 0; t2 < 4; t2++) {
                const uint32_t lo0 = pack_bf16(acc[8 * t2 + 0], acc[8 * t2 + 1]), hi0 = pack_bf16(acc[8 * t2 + 2], acc[8 * t2 + 3]);
                const uint32_t lo1 = pack_bf16(acc[8 * t2 + 4], acc[8 * t2 + 5]), hi1 = pack_bf16(acc[8 * t2 + 6], acc[8 * t2 + 7]);
                const uint32_t sl = __shfl_xor_sync(0xffffffffu, odd ? lo0 : lo1, 1), sh = __shfl_xor_sync(0xffffffffu, odd ? hi0 : hi1, 1);
                if (!dry) *reinterpret_cast<uint2*>(o + 16 * t2) = odd ? make_uint2(sl, lo1) : make_uint2(lo0, sl);
                if (!dry) *reinterpret_cast<uint2*>(o + 16 * t2 + 8 * 512) = odd ? make_uint2(sh, hi1) : make_uint2(hi0, sh);
            }
            if (tid == 0 && !dry) TSG(30);
        }
        TS(8);
    }
}

typedef CUresult (*PFN_encodeTiled)(CUtensorMap*, CUtensorMapDataType, cuuint32_t, void*, const cuuint64_t*, const cuuint64_t*,
                                    const cuuint32_t*, const cuuint32_t*, CUtensorMapInterleave, CUtensorMapSwizzle,
                                    CUtensorMapL2promotion, CUtensorMapFloatOOBfill);

void make_map(PFN_encodeTiled enc, CUtensorMap* m, const void* base, int rank, const cuuint64_t* dims, const cuuint64_t* strides, const cuuint32_t* box) {
    cuuint32_t es[5] = {1, 1, 1, 1, 1};
    enc(m, CU_TENSOR_MAP_DATA_TYPE_BFLOAT16, (cuuint32_t)rank, const_cast<void*>(base), dims, strides, box, es,
        CU_TENSOR_MAP_INTERLEAVE_NONE, CU_TENSOR_MAP_SWIZZLE_128B, CU_TENSOR_MAP_L2_PROMOTION_L2_256B, CU_TENSOR_MAP_FLOAT_OOB_FILL_NONE);
}

}

extern "C" void kernel_launch(void* const* d_in, const int* in_sizes, int n_in, void* d_out, int out_size) {
    (void)in_sizes; (void)n_in; (void)out_size;
    const void* x = d_in[0]; const void* wqkv = d_in[1]; const void* wo = d_in[2];
    const void* w1 = d_in[4]; const void* w2 = d_in[5]; const void* gate_w = d_in[6];
    static PFN_encodeTiled enc = nullptr;
    if (!enc) {
        void* fn = nullptr; cudaDriverEntryPointQueryResult st;
        cudaGetDriverEntryPoint("cuTensorMapEncodeTiled", &fn, cudaEnableDefault, &st);
        enc = (PFN_encodeTiled)fn;
        cudaFuncSetAttribute(fused_kernel, cudaFuncAttributeMaxDynamicSharedMemorySize, SMEM_BYTES);
    }
    CUtensorMap mx, mqkv, mw1, mw2, mwo, mw1a, mo;
    void* optr = nullptr;
    cudaGetSymbolAddress(&optr, g_o);
    { cuuint64_t d[2] = {512, 2048}, s[1] = {1024}; cuuint32_t b[2] = {64, 128}; make_map(enc, &mo, optr, 2, d, s, b); }
    { cuuint64_t d[4] = {64, 512, 3, 8}, s[3] = {3584, 128, 448}; cuuint32_t b[4] = {64, 32, 3, 1}; make_map(enc, &mw1a, w1, 4, d, s, b); }
    { cuuint64_t d[2] = {512, 2048}, s[1] = {1024}; cuuint32_t b[2] = {64, 128}; make_map(enc, &mx, x, 2, d, s, b); }
    { cuuint64_t d[4] = {64, 512, 8, 3}, s[3] = {3072, 128, 1024}; cuuint32_t b[4] = {64, 32, 1, 3}; make_map(enc, &mqkv, wqkv, 4, d, s, b); }
    { cuuint64_t d[2] = {1792, 512}, s[1] = {3584}; cuuint32_t b[2] = {64, 32}; make_map(enc, &mw1, w1, 2, d, s, b); }
    { cuuint64_t d[3] = {64, 1792, 8}, s[2] = {1024, 128}; cuuint32_t b[3] = {64, 32, 2}; make_map(enc, &mw2, w2, 3, d, s, b); }
    { cuuint64_t d[2] = {512, 512}, s[1] = {1024}; cuuint32_t b[2] = {64, 256}; make_map(enc, &mwo, wo, 2, d, s, b); }
    fused_kernel<<<NCTA, 384, SMEM_BYTES, cudaStreamPerThread>>>(mx, mqkv, mw1, mw2, mwo, mw1a, mo, (const __nv_bfloat16*)gate_w, (__nv_bfloat16*)d_out,
                                           (const uint8_t*)w1, (const uint8_t*)w2, (const uint8_t*)wo);
}
```

```cpp
#include <cuda_runtime.h>
#include <cuda_bf16.h>
#include <cuda.h>
#include <stdint.h>

namespace {

#define PF1_AT 1
#define PF2_AT 5
#define LEAD1 2
#define NCTA 132
constexpr int RING = 6;
constexpr int SLOT = 16384;
constexpr uint32_t X_OFF = 0;
constexpr uint32_t STG_OFF = X_OFF + 4 * 16384;
constexpr uint32_t RING_OFF = 131072;
constexpr uint32_t BAR_OFF = RING_OFF + RING * SLOT;
constexpr uint32_t B_FULL = BAR_OFF, B_EMPTY = BAR_OFF + 64, B_XFULL = BAR_OFF + 128, B_HDEAD = BAR_OFF + 192,
                   B_EREADY = BAR_OFF + 200, B_KVDONE = BAR_OFF + 208, B_ODONE = BAR_OFF + 224,
                   B_KVREADY = BAR_OFF + 232, B_WOFULL = BAR_OFF + 240, B_HSUM = BAR_OFF + 248, B_PREADY = BAR_OFF + 264,
                   B_SQ = BAR_OFF + 272, B_SF = BAR_OFF + 304;
constexpr uint32_t EPOCH_OFF = BAR_OFF + 256, ITEM_OFF = BAR_OFF + 260;
constexpr uint32_t OWN_OFF = X_OFF + 4 * 16384;
constexpr uint32_t HSUM_OFF = X_OFF + 6 * 16384;
constexpr uint32_t SMEM_BYTES = BAR_OFF + 1024;

constexpr int N_QKV = 16, N_FFN1 = 16, N_FFN2 = 14, N_KV = 8;

__device__ uint4 g_kf[32 * 128 * 32];
__device__ uint4 g_vf[32 * 128 * 32];
__device__ uint4 g_part[16 * 8 * 8 * 8 * 4 * 32];
__device__ uint4 g_of[16 * 8 * 8 * 4 * 32];
__device__ unsigned g_ticket;
__device__ unsigned g_kvcnt[128 * 32];
__device__ unsigned g_pcnt[128 * 32];
#define TS(k) do {} while (0)
#define TS2(k) do {} while (0)
#define TS2X(k) do {} while (0)
#define TSX(k) do {} while (0)
#define TSG(k) do {} while (0)

__device__ __forceinline__ uint32_t smem_u32(const void* p) { return (uint32_t)__cvta_generic_to_shared(p); }
__device__ __forceinline__ void mbar_init(uint32_t bar, uint32_t cnt) { asm volatile("mbarrier.init.shared::cta.b64 [%0], %1;" :: "r"(bar), "r"(cnt) : "memory"); }
__device__ __forceinline__ void mbar_expect_tx(uint32_t bar, uint32_t bytes) { asm volatile("mbarrier.arrive.expect_tx.shared::cta.b64 _, [%0], %1;" :: "r"(bar), "r"(bytes) : "memory"); }
__device__ __forceinline__ void mbar_expect_only(uint32_t bar, uint32_t bytes) { asm volatile("mbarrier.expect_tx.relaxed.cta.shared::cta.b64 [%0], %1;" :: "r"(bar), "r"(bytes) : "memory"); }
__device__ __forceinline__ void mbar_arrive(uint32_t bar) { asm volatile("mbarrier.arrive.shared::cta.b64 _, [%0];" :: "r"(bar) : "memory"); }
__device__ __forceinline__ void mbar_wait(uint32_t bar, uint32_t parity) {
    asm volatile("{\n.reg .pred P1, P2;\n.reg .u32 n;\nmov.u32 n, 0;\n"
                 "WAIT_LOOP:\n"
                 "mbarrier.try_wait.parity.shared::cta.b64 P1, [%0], %1;\n"
                 "@P1 bra WAIT_DONE;\n"
                 "add.u32 n, n, 1;\n"
                 "setp.lt.u32 P2, n, 0x400000;\n"
                 "@P2 bra WAIT_LOOP;\n"
                 "WAIT_DONE:\n}" :: "r"(bar), "r"(parity) : "memory");
}
__device__ __forceinline__ void tma_2d(uint32_t dst, const void* map, uint32_t bar, int c0, int c1) {
    asm volatile("cp.async.bulk.tensor.2d.shared::cluster.global.mbarrier::complete_tx::bytes [%0], [%1, {%3, %4}], [%2];"
        :: "r"(dst), "l"(map), "r"(bar), "r"(c0), "r"(c1) : "memory");
}
__device__ __forceinline__ void tma_3d(uint32_t dst, const void* map, uint32_t bar, int c0, int c1, int c2) {
    asm volatile("cp.async.bulk.tensor.3d.shared::cluster.global.mbarrier::complete_tx::bytes [%0], [%1, {%3, %4, %5}], [%2];"
        :: "r"(dst), "l"(map), "r"(bar), "r"(c0), "r"(c1), "r"(c2) : "memory");
}
__device__ __forceinline__ void tma_4d(uint32_t dst, const void* map, uint32_t bar, int c0, int c1, int c2, int c3) {
    asm volatile("cp.async.bulk.tensor.4d.shared::cluster.global.mbarrier::complete_tx::bytes [%0], [%1, {%3, %4, %5, %6}], [%2];"
        :: "r"(dst), "l"(map), "r"(bar), "r"(c0), "r"(c1), "r"(c2), "r"(c3) : "memory");
}
__device__ __forceinline__ void bulk_g2s(uint32_t dst, const void* src, uint32_t bytes, uint32_t bar) {
    asm volatile("cp.async.bulk.shared::cluster.global.mbarrier::complete_tx::bytes [%0], [%1], %2, [%3];"
        :: "r"(dst), "l"(src), "r"(bytes), "r"(bar) : "memory");
}
__device__ __forceinline__ void prefetch_l2(const void* src, uint32_t bytes) {
    asm volatile("cp.async.bulk.prefetch.L2.global [%0], %1;" :: "l"(src), "r"(bytes) : "memory");
}
__device__ __forceinline__ bool elect_one() {
    uint32_t p;
    asm volatile("{\n.reg .pred P;\nelect.sync _|P, 0xffffffff;\nselp.u32 %0, 1, 0, P;\n}" : "=r"(p));
    return p != 0;
}
__device__ __forceinline__ void wgmma_fence() { asm volatile("wgmma.fence.sync.aligned;" ::: "memory"); }
__device__ __forceinline__ void wgmma_commit() { asm volatile("wgmma.commit_group.sync.aligned;" ::: "memory"); }
template <int N> __device__ __forceinline__ void wgmma_wait() { asm volatile("wgmma.wait_group.sync.aligned %0;" :: "n"(N) : "memory"); }
__device__ __forceinline__ void fence_async_smem() { asm volatile("fence.proxy.async.shared::cta;" ::: "memory"); }
__device__ __forceinline__ uint64_t desc_a(uint32_t addr) {
    return (uint64_t)((addr & 0x3FFFF) >> 4) | ((uint64_t)1 << 16) | ((uint64_t)(1024 >> 4) << 32) | ((uint64_t)1 << 62);
}
__device__ __forceinline__ uint64_t desc_b(uint32_t addr) {
    return (uint64_t)((addr & 0x3FFFF) >> 4) | ((uint64_t)(4096 >> 4) << 16) | ((uint64_t)(1024 >> 4) << 32) | ((uint64_t)1 << 62);
}
__device__ __forceinline__ uint32_t pack_bf16(float lo, float hi) {
    uint32_t r; asm("cvt.rn.bf16x2.f32 %0, %1, %2;" : "=r"(r) : "f"(hi), "f"(lo)); return r;
}
__device__ __forceinline__ uint32_t pack_bf16_relu(float lo, float hi) {
    uint32_t r; asm("cvt.rn.relu.bf16x2.f32 %0, %1, %2;" : "=r"(r) : "f"(hi), "f"(lo)); return r;
}
__device__ __forceinline__ uint32_t movmatrix(uint32_t a) {
    uint32_t d; asm volatile("movmatrix.sync.aligned.m8n8.trans.b16 %0, %1;" : "=r"(d) : "r"(a)); return d;
}
__device__ __forceinline__ void stmatrix_x4(uint32_t addr, uint32_t r0, uint32_t r1, uint32_t r2, uint32_t r3) {
    asm volatile("stmatrix.sync.aligned.m8n8.x4.shared.b16 [%0], {%1, %2, %3, %4};" :: "r"(addr), "r"(r0), "r"(r1), "r"(r2), "r"(r3) : "memory");
}
__device__ __forceinline__ uint4 lds128(uint32_t addr) {
    uint4 v; asm volatile("ld.shared.v4.b32 {%0, %1, %2, %3}, [%4];" : "=r"(v.x), "=r"(v.y), "=r"(v.z), "=r"(v.w) : "r"(addr) : "memory"); return v;
}
__device__ __forceinline__ void mma16816(float (&c)[4], uint32_t a0, uint32_t a1, uint32_t a2, uint32_t a3, uint32_t b0, uint32_t b1) {
    asm volatile("mma.sync.aligned.m16n8k16.row.col.f32.bf16.bf16.f32 {%0,%1,%2,%3}, {%4,%5,%6,%7}, {%8,%9}, {%0,%1,%2,%3};"
        : "+f"(c[0]), "+f"(c[1]), "+f"(c[2]), "+f"(c[3]) : "r"(a0), "r"(a1), "r"(a2), "r"(a3), "r"(b0), "r"(b1));
}
__device__ __forceinline__ void mma16816_c(float (&c)[4], uint32_t a0, uint32_t a1, uint32_t a2, uint32_t a3, uint32_t b0, uint32_t b1, float ci) {
    asm volatile("mma.sync.aligned.m16n8k16.row.col.f32.bf16.bf16.f32 {%0,%1,%2,%3}, {%4,%5,%6,%7}, {%8,%9}, {%10,%10,%10,%10};"
        : "=f"(c[0]), "=f"(c[1]), "=f"(c[2]), "=f"(c[3]) : "r"(a0), "r"(a1), "r"(a2), "r"(a3), "r"(b0), "r"(b1), "f"(ci));
}
__device__ __forceinline__ int opaque(int v) { asm volatile("" : "+r"(v)); return v; }
__device__ __forceinline__ float ex2(float x) { float y; asm("ex2.approx.ftz.f32 %0, %1;" : "=f"(y) : "f"(x)); return y; }
__device__ __forceinline__ unsigned ld_acquire(const unsigned* p) {
    unsigned v; asm volatile("ld.acquire.gpu.global.u32 %0, [%1];" : "=r"(v) : "l"(p) : "memory"); return v;
}
__device__ __forceinline__ void red_release(unsigned* p, unsigned v) {
    asm volatile("red.release.gpu.global.add.u32 [%0], %1;" :: "l"(p), "r"(v) : "memory");
}
__device__ __forceinline__ void wait_counter(const unsigned* p, unsigned target) {
    uint32_t n = 0;
    while ((int)(ld_acquire(p) - target) < 0) { if (++n > (1u << 20)) break; }
}
__device__ __forceinline__ uint4 ldg_weak(const uint4* p) {
    uint4 v; asm volatile("ld.global.L1::no_allocate.v4.b32 {%0, %1, %2, %3}, [%4];" : "=r"(v.x), "=r"(v.y), "=r"(v.z), "=r"(v.w) : "l"(p) : "memory"); return v;
}
__device__ __forceinline__ float bf_lo(uint32_t v) { return __uint_as_float(v << 16); }
__device__ __forceinline__ float bf_hi(uint32_t v) { return __uint_as_float(v & 0xFFFF0000u); }

__device__ __forceinline__ void wgmma_ss_n64(float (&d)[32], uint64_t da, uint64_t db, int scale_d) {
    asm volatile("{\n.reg .pred p;\nsetp.ne.b32 p, %34, 0;\n"
        "wgmma.mma_async.sync.aligned.m64n64k16.f32.bf16.bf16 {%0, %1, %2, %3, %4, %5, %6, %7, %8, %9, %10, %11, %12, %13, %14, %15, %16, %17, %18, %19, %20, %21, %22, %23, %24, %25, %26, %27, %28, %29, %30, %31}, %32, %33, p, 1, 1, 0, 1;\n}\n"
        : "+f"(d[0]), "+f"(d[1]), "+f"(d[2]), "+f"(d[3]), "+f"(d[4]), "+f"(d[5]), "+f"(d[6]), "+f"(d[7]), "+f"(d[8]), "+f"(d[9]), "+f"(d[10]), "+f"(d[11]), "+f"(d[12]), "+f"(d[13]), "+f"(d[14]), "+f"(d[15]), "+f"(d[16]), "+f"(d[17]), "+f"(d[18]), "+f"(d[19]), "+f"(d[20]), "+f"(d[21]), "+f"(d[22]), "+f"(d[23]), "+f"(d[24]), "+f"(d[25]), "+f"(d[26]), "+f"(d[27]), "+f"(d[28]), "+f"(d[29]), "+f"(d[30]), "+f"(d[31])
        : "l"(da), "l"(db), "r"(scale_d));
}
__device__ __forceinline__ void wgmma_rs_n64(float (&d)[32], uint32_t a0, uint32_t a1, uint32_t a2, uint32_t a3, uint64_t db, int scale_d) {
    asm volatile("{\n.reg .pred p;\nsetp.ne.b32 p, %37, 0;\n"
        "wgmma.mma_async.sync.aligned.m64n64k16.f32.bf16.bf16 {%0, %1, %2, %3, %4, %5, %6, %7, %8, %9, %10, %11, %12, %13, %14, %15, %16, %17, %18, %19, %20, %21, %22, %23, %24, %25, %26, %27, %28, %29, %30, %31}, {%32, %33, %34, %35}, %36, p, 1, 1, 1;\n}\n"
        : "+f"(d[0]), "+f"(d[1]), "+f"(d[2]), "+f"(d[3]), "+f"(d[4]), "+f"(d[5]), "+f"(d[6]), "+f"(d[7]), "+f"(d[8]), "+f"(d[9]), "+f"(d[10]), "+f"(d[11]), "+f"(d[12]), "+f"(d[13]), "+f"(d[14]), "+f"(d[15]), "+f"(d[16]), "+f"(d[17]), "+f"(d[18]), "+f"(d[19]), "+f"(d[20]), "+f"(d[21]), "+f"(d[22]), "+f"(d[23]), "+f"(d[24]), "+f"(d[25]), "+f"(d[26]), "+f"(d[27]), "+f"(d[28]), "+f"(d[29]), "+f"(d[30]), "+f"(d[31])
        : "r"(a0), "r"(a1), "r"(a2), "r"(a3), "l"(db), "r"(scale_d));
}
__device__ __forceinline__ void wgmma_ss_n128(float (&d)[64], uint64_t da, uint64_t db, int scale_d) {
    asm volatile("{\n.reg .pred p;\nsetp.ne.b32 p, %66, 0;\n"
        "wgmma.mma_async.sync.aligned.m64n128k16.f32.bf16.bf16 {%0, %1, %2, %3, %4, %5, %6, %7, %8, %9, %10, %11, %12, %13, %14, %15, %16, %17, %18, %19, %20, %21, %22, %23, %24, %25, %26, %27, %28, %29, %30, %31, %32, %33, %34, %35, %36, %37, %38, %39, %40, %41, %42, %43, %44, %45, %46, %47, %48, %49, %50, %51, %52, %53, %54, %55, %56, %57, %58, %59, %60, %61, %62, %63}, %64, %65, p, 1, 1, 0, 1;\n}\n"
        : "+f"(d[0]), "+f"(d[1]), "+f"(d[2]), "+f"(d[3]), "+f"(d[4]), "+f"(d[5]), "+f"(d[6]), "+f"(d[7]), "+f"(d[8]), "+f"(d[9]), "+f"(d[10]), "+f"(d[11]), "+f"(d[12]), "+f"(d[13]), "+f"(d[14]), "+f"(d[15]), "+f"(d[16]), "+f"(d[17]), "+f"(d[18]), "+f"(d[19]), "+f"(d[20]), "+f"(d[21]), "+f"(d[22]), "+f"(d[23]), "+f"(d[24]), "+f"(d[25]), "+f"(d[26]), "+f"(d[27]), "+f"(d[28]), "+f"(d[29]), "+f"(d[30]), "+f"(d[31]), "+f"(d[32]), "+f"(d[33]), "+f"(d[34]), "+f"(d[35]), "+f"(d[36]), "+f"(d[37]), "+f"(d[38]), "+f"(d[39]), "+f"(d[40]), "+f"(d[41]), "+f"(d[42]), "+f"(d[43]), "+f"(d[44]), "+f"(d[45]), "+f"(d[46]), "+f"(d[47]), "+f"(d[48]), "+f"(d[49]), "+f"(d[50]), "+f"(d[51]), "+f"(d[52]), "+f"(d[53]), "+f"(d[54]), "+f"(d[55]), "+f"(d[56]), "+f"(d[57]), "+f"(d[58]), "+f"(d[59]), "+f"(d[60]), "+f"(d[61]), "+f"(d[62]), "+f"(d[63])
        : "l"(da), "l"(db), "r"(scale_d));
}
__device__ __forceinline__ void wgmma_ss_n200(float (&d)[100], uint64_t da, uint64_t db, int scale_d) {
    asm volatile("{\n.reg .pred p;\nsetp.ne.b32 p, %102, 0;\n"
        "wgmma.mma_async.sync.aligned.m64n200k16.f32.bf16.bf16 {%0, %1, %2, %3, %4, %5, %6, %7, %8, %9, %10, %11, %12, %13, %14, %15, %16, %17, %18, %19, %20, %21, %22, %23, %24, %25, %26, %27, %28, %29, %30, %31, %32, %33, %34, %35, %36, %37, %38, %39, %40, %41, %42, %43, %44, %45, %46, %47, %48, %49, %50, %51, %52, %53, %54, %55, %56, %57, %58, %59, %60, %61, %62, %63, %64, %65, %66, %67, %68, %69, %70, %71, %72, %73, %74, %75, %76, %77, %78, %79, %80, %81, %82, %83, %84, %85, %86, %87, %88, %89, %90, %91, %92, %93, %94, %95, %96, %97, %98, %99}, %100, %101, p, 1, 1, 0, 1;\n}\n"
        : "+f"(d[0]), "+f"(d[1]), "+f"(d[2]), "+f"(d[3]), "+f"(d[4]), "+f"(d[5]), "+f"(d[6]), "+f"(d[7]), "+f"(d[8]), "+f"(d[9]), "+f"(d[10]), "+f"(d[11]), "+f"(d[12]), "+f"(d[13]), "+f"(d[14]), "+f"(d[15]), "+f"(d[16]), "+f"(d[17]), "+f"(d[18]), "+f"(d[19]), "+f"(d[20]), "+f"(d[21]), "+f"(d[22]), "+f"(d[23]), "+f"(d[24]), "+f"(d[25]), "+f"(d[26]), "+f"(d[27]), "+f"(d[28]), "+f"(d[29]), "+f"(d[30]), "+f"(d[31]), "+f"(d[32]), "+f"(d[33]), "+f"(d[34]), "+f"(d[35]), "+f"(d[36]), "+f"(d[37]), "+f"(d[38]), "+f"(d[39]), "+f"(d[40]), "+f"(d[41]), "+f"(d[42]), "+f"(d[43]), "+f"(d[44]), "+f"(d[45]), "+f"(d[46]), "+f"(d[47]), "+f"(d[48]), "+f"(d[49]), "+f"(d[50]), "+f"(d[51]), "+f"(d[52]), "+f"(d[53]), "+f"(d[54]), "+f"(d[55]), "+f"(d[56]), "+f"(d[57]), "+f"(d[58]), "+f"(d[59]), "+f"(d[60]), "+f"(d[61]), "+f"(d[62]), "+f"(d[63]), "+f"(d[64]), "+f"(d[65]), "+f"(d[66]), "+f"(d[67]), "+f"(d[68]), "+f"(d[69]), "+f"(d[70]), "+f"(d[71]), "+f"(d[72]), "+f"(d[73]), "+f"(d[74]), "+f"(d[75]), "+f"(d[76]), "+f"(d[77]), "+f"(d[78]), "+f"(d[79]), "+f"(d[80]), "+f"(d[81]), "+f"(d[82]), "+f"(d[83]), "+f"(d[84]), "+f"(d[85]), "+f"(d[86]), "+f"(d[87]), "+f"(d[88]), "+f"(d[89]), "+f"(d[90]), "+f"(d[91]), "+f"(d[92]), "+f"(d[93]), "+f"(d[94]), "+f"(d[95]), "+f"(d[96]), "+f"(d[97]), "+f"(d[98]), "+f"(d[99])
        : "l"(da), "l"(db), "r"(scale_d));
}
__device__ __forceinline__ void wgmma_ss_n224(float (&d)[112], uint64_t da, uint64_t db, int scale_d) {
    asm volatile("{\n.reg .pred p;\nsetp.ne.b32 p, %114, 0;\n"
        "wgmma.mma_async.sync.aligned.m64n224k16.f32.bf16.bf16 {%0, %1, %2, %3, %4, %5, %6, %7, %8, %9, %10, %11, %12, %13, %14, %15, %16, %17, %18, %19, %20, %21, %22, %23, %24, %25, %26, %27, %28, %29, %30, %31, %32, %33, %34, %35, %36, %37, %38, %39, %40, %41, %42, %43, %44, %45, %46, %47, %48, %49, %50, %51, %52, %53, %54, %55, %56, %57, %58, %59, %60, %61, %62, %63, %64, %65, %66, %67, %68, %69, %70, %71, %72, %73, %74, %75, %76, %77, %78, %79, %80, %81, %82, %83, %84, %85, %86, %87, %88, %89, %90, %91, %92, %93, %94, %95, %96, %97, %98, %99, %100, %101, %102, %103, %104, %105, %106, %107, %108, %109, %110, %111}, %112, %113, p, 1, 1, 0, 1;\n}\n"
        : "+f"(d[0]), "+f"(d[1]), "+f"(d[2]), "+f"(d[3]), "+f"(d[4]), "+f"(d[5]), "+f"(d[6]), "+f"(d[7]), "+f"(d[8]), "+f"(d[9]), "+f"(d[10]), "+f"(d[11]), "+f"(d[12]), "+f"(d[13]), "+f"(d[14]), "+f"(d[15]), "+f"(d[16]), "+f"(d[17]), "+f"(d[18]), "+f"(d[19]), "+f"(d[20]), "+f"(d[21]), "+f"(d[22]), "+f"(d[23]), "+f"(d[24]), "+f"(d[25]), "+f"(d[26]), "+f"(d[27]), "+f"(d[28]), "+f"(d[29]), "+f"(d[30]), "+f"(d[31]), "+f"(d[32]), "+f"(d[33]), "+f"(d[34]), "+f"(d[35]), "+f"(d[36]), "+f"(d[37]), "+f"(d[38]), "+f"(d[39]), "+f"(d[40]), "+f"(d[41]), "+f"(d[42]), "+f"(d[43]), "+f"(d[44]), "+f"(d[45]), "+f"(d[46]), "+f"(d[47]), "+f"(d[48]), "+f"(d[49]), "+f"(d[50]), "+f"(d[51]), "+f"(d[52]), "+f"(d[53]), "+f"(d[54]), "+f"(d[55]), "+f"(d[56]), "+f"(d[57]), "+f"(d[58]), "+f"(d[59]), "+f"(d[60]), "+f"(d[61]), "+f"(d[62]), "+f"(d[63]), "+f"(d[64]), "+f"(d[65]), "+f"(d[66]), "+f"(d[67]), "+f"(d[68]), "+f"(d[69]), "+f"(d[70]), "+f"(d[71]), "+f"(d[72]), "+f"(d[73]), "+f"(d[74]), "+f"(d[75]), "+f"(d[76]), "+f"(d[77]), "+f"(d[78]), "+f"(d[79]), "+f"(d[80]), "+f"(d[81]), "+f"(d[82]), "+f"(d[83]), "+f"(d[84]), "+f"(d[85]), "+f"(d[86]), "+f"(d[87]), "+f"(d[88]), "+f"(d[89]), "+f"(d[90]), "+f"(d[91]), "+f"(d[92]), "+f"(d[93]), "+f"(d[94]), "+f"(d[95]), "+f"(d[96]), "+f"(d[97]), "+f"(d[98]), "+f"(d[99]), "+f"(d[100]), "+f"(d[101]), "+f"(d[102]), "+f"(d[103]), "+f"(d[104]), "+f"(d[105]), "+f"(d[106]), "+f"(d[107]), "+f"(d[108]), "+f"(d[109]), "+f"(d[110]), "+f"(d[111])
        : "l"(da), "l"(db), "r"(scale_d));
}
template <int N> __device__ __forceinline__ void fence_acc(float (&d)[N]) {
#pragma unroll
    for (int i = 0; i < N; i++) asm volatile("" : "+f"(d[i]) :: "memory");
}

__device__ __forceinline__ uint4 ldg_relaxed(const uint4* p) {
    uint4 v; asm volatile("ld.relaxed.gpu.global.v4.b32 {%0, %1, %2, %3}, [%4];" : "=r"(v.x), "=r"(v.y), "=r"(v.z), "=r"(v.w) : "l"(p) : "memory"); return v;
}
__device__ __forceinline__ void stg_relaxed(uint4* p, uint4 v) {
    asm volatile("st.relaxed.gpu.global.v4.b32 [%0], {%1, %2, %3, %4};" :: "l"(p), "r"(v.x), "r"(v.y), "r"(v.z), "r"(v.w) : "memory");
}
__device__ __forceinline__ void bulk_s2g(void* dst, uint32_t src, uint32_t bytes) {
    asm volatile("cp.async.bulk.global.shared::cta.bulk_group [%0], [%1], %2;" :: "l"(dst), "r"(src), "r"(bytes) : "memory");
}
__device__ __forceinline__ void sts128(uint32_t addr, uint4 v) {
    asm volatile("st.shared.v4.b32 [%0], {%1, %2, %3, %4};" :: "r"(addr), "r"(v.x), "r"(v.y), "r"(v.z), "r"(v.w) : "memory");
}
constexpr int NHS = 6;
__device__ __forceinline__ void sum_partials(uint32_t sb, int ti, int tj, int lane) {
    for (;;) {
        uint32_t item = 0;
        if (lane == 0) asm volatile("atom.shared.add.u32 %0, [%1], 1;" : "=r"(item) : "r"(sb + ITEM_OFF) : "memory");
        item = __shfl_sync(0xffffffffu, item, 0);
        if (item >= 16) break;
        const uint4* p = g_part + (size_t)((ti * 8 + tj) * 8) * 1024 + item * 64 + lane;
        uint4 v[2][NHS];
#pragma unroll
        for (int s = 0; s < NHS; s++) { v[0][s] = ldg_weak(p + s * 1024); v[1][s] = ldg_weak(p + s * 1024 + 32); }
#pragma unroll
        for (int n = 0; n < 2; n++) {
            float a[8];
#pragma unroll
            for (int e = 0; e < 8; e++) a[e] = 0.f;
#pragma unroll
            for (int s = 0; s < NHS; s++) {
                a[0] += bf_lo(v[n][s].x); a[1] += bf_hi(v[n][s].x); a[2] += bf_lo(v[n][s].y); a[3] += bf_hi(v[n][s].y);
                a[4] += bf_lo(v[n][s].z); a[5] += bf_hi(v[n][s].z); a[6] += bf_lo(v[n][s].w); a[7] += bf_hi(v[n][s].w);
            }
            const uint32_t d = sb + HSUM_OFF + (item * 4 + n * 2) * 512 + lane * 16;
            sts128(d, make_uint4(__float_as_uint(a[0]), __float_as_uint(a[1]), __float_as_uint(a[2]), __float_as_uint(a[3])));
            sts128(d + 512, make_uint4(__float_as_uint(a[4]), __float_as_uint(a[5]), __float_as_uint(a[6]), __float_as_uint(a[7])));
        }
    }
    __syncwarp();
    if (lane == 0) mbar_arrive(sb + B_HSUM);
}

#define PWAIT() mbar_wait(sb + B_EMPTY + 8 * r.slot, r.phase)
#define CWAIT() do { if (!dry) mbar_wait(sb + B_FULL + 8 * r.slot, r.phase); } while (0)
template <bool B> struct BoolTag { static constexpr bool value = B; };
struct Ring {
    int slot; uint32_t phase;
    __device__ __forceinline__ void next() { if (++slot == RING) { slot = 0; phase ^= 1; } }
};

__global__ void __launch_bounds__(384, 1)
fused_kernel(const __grid_constant__ CUtensorMap map_x, const __grid_constant__ CUtensorMap map_qkv,
             const __grid_constant__ CUtensorMap map_w1, const __grid_constant__ CUtensorMap map_w2,
             const __grid_constant__ CUtensorMap map_wo, const __grid_constant__ CUtensorMap map_w1a,
             const __nv_bfloat16* __restrict__ gate_w, __nv_bfloat16* __restrict__ out,
             const uint8_t* __restrict__ w1p, const uint8_t* __restrict__ w2p, const uint8_t* __restrict__ wop)
{
    extern __shared__ __align__(1024) uint8_t smem_raw[];
    const uint32_t sb = smem_u32(smem_raw);
    const int tid = threadIdx.x, warp = tid >> 5, lane = tid & 31;
    const bool dry = blockIdx.x >= 128;
    const int ti = dry ? (int)(blockIdx.x & 1) * 2 : blockIdx.x >> 3, tj = blockIdx.x & 7;
    if (dry && warp >= 8) {
        asm volatile("setmaxnreg.dec.sync.aligned.u32 88;");
        return;
    }

    if (tid == 0 && !dry) { TSG(31); TSX(0); }
    if (tid == 320) {
        asm volatile("prefetch.tensormap [%0];" :: "l"(&map_x) : "memory");
        asm volatile("prefetch.tensormap [%0];" :: "l"(&map_qkv) : "memory");
        asm volatile("prefetch.tensormap [%0];" :: "l"(&map_w1) : "memory");
        asm volatile("prefetch.tensormap [%0];" :: "l"(&map_w1a) : "memory");
        asm volatile("prefetch.tensormap [%0];" :: "l"(&map_w2) : "memory");
        asm volatile("prefetch.tensormap [%0];" :: "l"(&map_wo) : "memory");
    }
    if (tid == 256) {
        mbar_init(sb + B_FULL, 1); mbar_init(sb + B_XFULL, 1);
        fence_async_smem();
        mbar_expect_tx(sb + B_XFULL, 16384);
        tma_2d(sb + X_OFF, &map_x, sb + B_XFULL, 0, ti * 128);
        mbar_expect_only(sb + B_FULL, 12288);
        tma_4d(sb + RING_OFF, &map_qkv, sb + B_FULL, 0, 0, tj, 0);
    }
    uint32_t gwv[N_QKV / 2];
    if (warp == 8) {
        const unsigned short* gws = reinterpret_cast<const unsigned short*>(gate_w);
#pragma unroll
        for (int n = 0; n < N_QKV / 2; n++) gwv[n] = (uint32_t)__ldg(gws + 64 * n + lane) | ((uint32_t)__ldg(gws + 64 * n + 32 + lane) << 16);
    }
    if (tid == 288) {
        for (int s = 1; s < RING; s++) mbar_init(sb + B_FULL + 8 * s, 1);
        for (int s = 0; s < RING; s++) mbar_init(sb + B_EMPTY + 8 * s, 8);
        for (int s = 1; s < 8; s++) mbar_init(sb + B_XFULL + 8 * s, 1);
        fence_async_smem();
    }
    if (tid == 352) {
        mbar_init(sb + B_HDEAD, 8); mbar_init(sb + B_EREADY, 1); mbar_init(sb + B_KVDONE, 8); mbar_init(sb + B_KVREADY, 1);
        mbar_init(sb + B_ODONE, 8); mbar_init(sb + B_WOFULL, 1); mbar_init(sb + B_HSUM, 4);
        mbar_init(sb + B_PREADY, 1); mbar_init(sb + B_SF, 1); mbar_init(sb + B_SF + 8, 1);
        for (int s = 0; s < 4; s++) mbar_init(sb + B_SQ + 8 * s, 8);
        asm volatile("st.shared.u32 [%0], %1;" :: "r"(sb + ITEM_OFF), "r"(0) : "memory");
        fence_async_smem();
    }
    if (!dry) __syncthreads();

    if (warp >= 8) {
        asm volatile("setmaxnreg.dec.sync.aligned.u32 88;");
        if (warp == 8) {
            Ring r{0, 1};
            const bool leader = elect_one();
#pragma unroll
            for (int n = 0; n < N_QKV; n++) {
                const uint32_t full = sb + B_FULL + 8 * r.slot, dst = sb + RING_OFF + r.slot * SLOT;
                if (n > 0) {
                    if (!(n & 1) && leader) {
                        mbar_expect_tx(sb + B_XFULL + 8 * (n >> 1), 16384);
                        tma_2d(sb + X_OFF + (n >> 1) * 16384, &map_x, sb + B_XFULL + 8 * (n >> 1), (n >> 1) * 64, ti * 128);
                    }
                    if (n >= RING) PWAIT();
                    if (leader) {
                        mbar_expect_only(full, 12288);
                        tma_4d(dst, &map_qkv, full, 0, 32 * n, tj, 0);
                    }
                }
                const uint32_t gv = (n & 1) ? (gwv[n >> 1] >> 16) : (gwv[n >> 1] & 0xFFFFu);
                asm volatile("st.shared.v4.b32 [%0], {%1, %2, %2, %2};" :: "r"(dst + 12288 + lane * 128 + ((lane & 7) << 4)), "r"(gv), "r"(0) : "memory");
                fence_async_smem();
                __syncwarp();
                if (leader) mbar_arrive(full);
                r.next();
            }
#pragma unroll 1
            for (int n = 0; n < N_FFN1; n++) {
                const uint32_t full = sb + B_FULL + 8 * r.slot, dst = sb + RING_OFF + r.slot * SLOT;
                PWAIT();
                if (leader) {
                    mbar_expect_tx(full, 16384);
                    tma_4d(dst, &map_w1a, full, 0, 32 * n, 0, tj);
                    tma_2d(dst + 3 * 4096, &map_w1, full, 224 * tj + 192, 32 * n);
                }
                r.next();
            }
            {
                int q = 0, rr = 0;
#pragma unroll 1
                for (int n = 0; n < N_FFN2; n++) {
                    const uint32_t full = sb + B_FULL + 8 * r.slot, dst = sb + RING_OFF + r.slot * SLOT;
                    PWAIT();
                    if (leader) mbar_expect_tx(full, 16384);
#pragma unroll
                    for (int h = 0; h < 2; h++) {
                        if (leader) tma_3d(dst + h * 8192, &map_w2, full, 0, 224 * tj + 32 * rr, 2 * q);
                        if (++rr == 7) { rr = 0; q++; }
                    }
                    r.next();
                }
            }
            mbar_wait(sb + B_KVREADY, 0);
            asm volatile("fence.proxy.async.global;" ::: "memory");
            {
                const int bbase = 8 * ti - 16, b0 = bbase < 0 ? 0 : bbase;
                const uint32_t bytes = (uint32_t)(8 * ti + 8 - b0) * 512;
#pragma unroll 1
                for (int m = 0; m < N_KV; m++) {
                    const uint32_t full = sb + B_FULL + 8 * r.slot, dst = sb + RING_OFF + r.slot * SLOT;
                    if (m == RING) {
                        mbar_wait(sb + B_HDEAD, 0);
                        if (leader) {
                            mbar_expect_tx(sb + B_WOFULL, 65536);
#pragma unroll
                            for (int e = 0; e < 2; e++) tma_2d(sb + X_OFF + e * 32768, &map_wo, sb + B_WOFULL, 64 * tj, 256 * e);
                        }
                    }
                    PWAIT();
                    if (leader) {
                        const uint4* src = ((m & 1) ? g_vf : g_kf) + ((tj * 4 + (m >> 1)) * 128 + b0) * 32;
                        mbar_expect_tx(full, bytes);
                        bulk_g2s(dst + (b0 - bbase) * 512, src, bytes, full);
                    }
                    r.next();
                }
            }
            mbar_wait(sb + B_PREADY, 0);
            sum_partials(sb, ti, tj, lane);
        } else if (warp == 9) {
            unsigned epoch = 0;
            if (lane == 0) {
                epoch = atomicAdd(&g_ticket, 1u) >> 7;
                asm volatile("st.shared.u32 [%0], %1;" :: "r"(sb + EPOCH_OFF), "r"(epoch) : "memory");
                mbar_arrive(sb + B_EREADY);
                mbar_wait(sb + B_XFULL + 8 * PF1_AT, 0);
                prefetch_l2(w1p + (size_t)blockIdx.x * 14336, 14336);
                mbar_wait(sb + B_XFULL + 8 * PF2_AT, 0);
                prefetch_l2(w2p + (size_t)blockIdx.x * 14336, 14336);
                prefetch_l2(wop + (size_t)blockIdx.x * 4096, 4096);
                mbar_wait(sb + B_KVDONE, 0);
                red_release(&g_kvcnt[blockIdx.x * 32], 1u);
            }
            epoch = __shfl_sync(0xffffffffu, epoch, 0);
            if (lane < 3 && ti - lane >= 0) wait_counter(&g_kvcnt[((ti - lane) * 8 + tj) * 32], epoch + 1);
            __syncwarp();
            if (lane == 0) mbar_arrive(sb + B_KVREADY);
            mbar_wait(sb + B_SQ + 24, 0);
            if (lane < 8) wait_counter(&g_pcnt[(ti * 8 + lane) * 32], epoch + 1);
            __syncwarp();
            if (lane == 0) { mbar_arrive(sb + B_PREADY); TSX(13); }
            sum_partials(sb, ti, tj, lane);
            if (lane == 0) TSX(14);
        } else {
            if (warp == 10) {
#pragma unroll 1
                for (int q = 0; q < 4; q++) {
                    mbar_wait(sb + B_SQ + 8 * q, 0);
                    if (lane < 16) {
                        uint4* d = g_part + (size_t)(((ti * 8 + 2 * q + (lane & 1)) * 8 + tj) * 8 + (lane >> 1)) * 128;
                        bulk_s2g(d, sb + STG_OFF + (q & 1) * 32768 + lane * 2048, 2048);
                        asm volatile("cp.async.bulk.commit_group;" ::: "memory");
                        asm volatile("cp.async.bulk.wait_group.read 0;" ::: "memory");
                    }
                    __syncwarp();
                    if (lane == 0) mbar_arrive(sb + B_SF + 8 * (q & 1));
                }
                asm volatile("cp.async.bulk.wait_group 0;" ::: "memory");
                asm volatile("fence.proxy.async.global;" ::: "memory");
                __syncwarp();
                if (lane == 0) { red_release(&g_pcnt[blockIdx.x * 32], 1u); TSX(12); }
            }
            mbar_wait(sb + B_PREADY, 0);
            sum_partials(sb, ti, tj, lane);
        }
    } else {
        asm volatile("setmaxnreg.inc.sync.aligned.u32 208;");
        const int wg = warp >> 2, g = lane >> 2, c = lane & 3;
        const uint32_t xa = sb + X_OFF + wg * 8192;
        Ring r{0, 0};
        const bool lane0 = lane == 0 && !dry;
        uint32_t qf[4][4];
        float g0, g1;
        uint32_t tag;
        TS(9);
        {
            float acc[100];
            int prev = 0;
            if (wg == 1) asm volatile("bar.sync 3, 256;" ::: "memory");
            for (int s = 0; s < (dry ? 4 : N_QKV); s++) {
                if (!(s & 1) && !dry) mbar_wait(sb + B_XFULL + 8 * (s >> 1), 0);
                CWAIT();
                if (s == 0) TS(1);
                if (s == 2) TS(28);
                if (s == 6) TS(29);
                if (s == 10) TS(20);
                const uint32_t bs = sb + RING_OFF + r.slot * SLOT, as = xa + (s >> 1) * 16384 + (s & 1) * 64;
                wgmma_fence();
                wgmma_ss_n200(acc, desc_a(as), desc_b(bs), s);
                wgmma_ss_n200(acc, desc_a(as + 32), desc_b(bs + 2048), 1);
                wgmma_commit();
                if (wg == 0 && s == LEAD1) asm volatile("bar.arrive 3, 256;" ::: "memory");
                if (s > 0) { wgmma_wait<1>(); if (lane0) mbar_arrive(sb + B_EMPTY + 8 * prev); }
                prev = r.slot; r.next();
            }
            wgmma_wait<0>();
            fence_acc(acc);
            if (lane0) mbar_arrive(sb + B_EMPTY + 8 * prev);
            TS(2);
            const int blk = ti * 8 + warp;
#pragma unroll
            for (int hh = 0; hh < 4; hh++) {
                const float* t0 = &acc[8 * hh]; const float* t1 = &acc[8 * hh + 4];
                qf[hh][0] = pack_bf16(t0[0], t0[1]); qf[hh][1] = pack_bf16(t0[2], t0[3]);
                qf[hh][2] = pack_bf16(t1[0], t1[1]); qf[hh][3] = pack_bf16(t1[2], t1[3]);
                const float* k0 = &acc[32 + 8 * hh]; const float* k1 = &acc[32 + 8 * hh + 4];
                uint4 kv;
                kv.x = pack_bf16(k0[0], k0[1]); kv.y = pack_bf16(k1[0], k1[1]);
                kv.z = pack_bf16(k0[2], k0[3]); kv.w = pack_bf16(k1[2], k1[3]);
                if (!dry) g_kf[((tj * 4 + hh) * 128 + blk) * 32 + lane] = kv;
                const float* v0 = &acc[64 + 8 * hh]; const float* v1 = &acc[64 + 8 * hh + 4];
                uint4 vv;
                vv.x = movmatrix(pack_bf16(v0[0], v0[1])); vv.y = movmatrix(pack_bf16(v0[2], v0[3]));
                vv.z = movmatrix(pack_bf16(v1[0], v1[1])); vv.w = movmatrix(pack_bf16(v1[2], v1[3]));
                if (!dry) g_vf[((tj * 4 + hh) * 128 + blk) * 32 + lane] = vv;
            }
            __syncwarp();
            if (lane0) mbar_arrive(sb + B_KVDONE);
            const float z0 = __shfl_sync(0xffffffffu, acc[96], lane & ~3), z1 = __shfl_sync(0xffffffffu, acc[98], lane & ~3);
            g0 = 1.f / (1.f + __expf(-z0)); g1 = 1.f / (1.f + __expf(-z1));
        }
        TS(3);
        const int wrow = (warp & 3) * 16;
        {
            float acc[112];
            int prev = 0;
            for (int s = 0; s < (dry ? 4 : N_FFN1); s++) {
                CWAIT();
                const uint32_t bs = sb + RING_OFF + r.slot * SLOT, as = xa + (s >> 1) * 16384 + (s & 1) * 64;
                wgmma_fence();
                wgmma_ss_n224(acc, desc_a(as), desc_b(bs), s);
                wgmma_ss_n224(acc, desc_a(as + 32), desc_b(bs + 2048), 1);
                wgmma_commit();
                if (s > 0) { wgmma_wait<1>(); if (lane0) mbar_arrive(sb + B_EMPTY + 8 * prev); }
                prev = r.slot; r.next();
            }
            wgmma_wait<0>();
            fence_acc(acc);
            if (lane0) mbar_arrive(sb + B_EMPTY + 8 * prev);
            TS(4);
            const float s0 = 1.f - g0, s1 = 1.f - g1;
            asm volatile("bar.sync %0, 128;" :: "r"(1 + wg) : "memory");
            const uint32_t strow = xa + (wrow + ((lane >> 3) & 1) * 8 + (lane & 7)) * 128;
#pragma unroll
            for (int p = 0; p < 14; p++) {
                const int nt = 2 * p + (lane >> 4);
                const float* a = &acc[8 * p];
                stmatrix_x4(strow + (p >> 2) * 16384 + (((nt & 7) ^ (lane & 7)) << 4),
                            pack_bf16_relu(a[0] * s0, a[1] * s0), pack_bf16_relu(a[2] * s1, a[3] * s1),
                            pack_bf16_relu(a[4] * s0, a[5] * s0), pack_bf16_relu(a[6] * s1, a[7] * s1));
            }
        }
        TS(5);
        {
            fence_async_smem();
            asm volatile("bar.sync 4, 256;" ::: "memory");
            float accA[64], accB[64];
            auto epilogue = [&](float (&acc)[64], int q) {
                fence_acc(acc);
                const uint32_t st = sb + STG_OFF + (q & 1) * 32768 + warp * 4096;
                if (q >= 2 && !dry) mbar_wait(sb + B_SF + 8 * (q & 1), 0);
#pragma unroll
                for (int t2 = 0; t2 < 8; t2++) {
                    uint4 v;
                    v.x = pack_bf16(acc[8 * t2 + 0], acc[8 * t2 + 1]); v.y = pack_bf16(acc[8 * t2 + 2], acc[8 * t2 + 3]);
                    v.z = pack_bf16(acc[8 * t2 + 4], acc[8 * t2 + 5]); v.w = pack_bf16(acc[8 * t2 + 6], acc[8 * t2 + 7]);
                    sts128(st + t2 * 512 + lane * 16, v);
                }
                fence_async_smem();
                __syncwarp();
                if (lane0) mbar_arrive(sb + B_SQ + 8 * q);
            };
            int rel = r.slot;
#pragma unroll
            for (int m = 0; m < N_FFN2; m++) {
                CWAIT();
                wgmma_fence();
#pragma unroll
                for (int h = 0; h < 2; h++) {
                    const int u = 2 * m + h, q = u / 7, rr = u % 7;
                    const uint32_t bs = sb + RING_OFF + r.slot * SLOT + h * 8192;
                    const uint32_t as = xa + (rr >> 1) * 16384 + (rr & 1) * 64;
                    if (!(q & 1)) {
                        wgmma_ss_n128(accA, desc_a(as), desc_b(bs), rr);
                        wgmma_ss_n128(accA, desc_a(as + 32), desc_b(bs + 2048), 1);
                    } else {
                        wgmma_ss_n128(accB, desc_a(as), desc_b(bs), rr);
                        wgmma_ss_n128(accB, desc_a(as + 32), desc_b(bs + 2048), 1);
                    }
                }
                wgmma_commit();
                r.next();
                wgmma_wait<1>();
                if (m > 0) {
                    if (lane0) mbar_arrive(sb + B_EMPTY + 8 * rel);
                    if (++rel == RING) rel = 0;
                }
                if (m == 4) { TS(25); epilogue(accA, 0); }
                if (m == 7) { TS(26); epilogue(accB, 1); }
                if (m == 11) { TS(27); epilogue(accA, 2); }
            }
            wgmma_wait<0>();
            if (lane0) { mbar_arrive(sb + B_EMPTY + 8 * rel); mbar_arrive(sb + B_HDEAD); }
            epilogue(accB, 3);
        }
        TS(6);
        {
            const float SC = 0.25f * 1.4426950408889634f;
            const int gb0 = 8 * ti - 16 + warp;
            int slotK = 0, slotV = 0;
            const uint32_t ostore = sb + OWN_OFF + (warp * 16 + ((lane >> 3) & 1) * 8 + (lane & 7)) * 128;
            if (!dry) mbar_wait(sb + B_EREADY, 0);
            asm volatile("ld.shared.u32 %0, [%1];" : "=r"(tag) : "r"(sb + EPOCH_OFF) : "memory");
            tag = (tag + 1) & 1u;
            uint4* odst = g_of + (size_t)(((ti * 8 + tj) * 8 + warp) * 4) * 32 + lane;
#define NHEADS (dry ? 2 : 4)
#define ATT_KWAIT(kb) do { slotK = r.slot; CWAIT(); kb = sb + RING_OFF + slotK * SLOT + warp * 512 + lane * 16; r.next(); } while (0)
#define ATT_VWAIT(vb) do { slotV = r.slot; CWAIT(); vb = sb + RING_OFF + slotV * SLOT + warp * 512 + lane * 16; r.next(); TS(21 + hh); } while (0)
#define ATT_KREL() do { __syncwarp(); if (lane0) mbar_arrive(sb + B_EMPTY + 8 * slotK); } while (0)
#define ATT_VREL() do { __syncwarp(); if (lane0) mbar_arrive(sb + B_EMPTY + 8 * slotV); } while (0)
#define ATT_NEXTQ(h) do { \
                if ((h) == 1) { q0 = qf[1][0]; q1 = qf[1][1]; q2 = qf[1][2]; q3 = qf[1][3]; } \
                else if ((h) == 2) { q0 = qf[2][0]; q1 = qf[2][1]; q2 = qf[2][2]; q3 = qf[2][3]; } \
                else { q0 = qf[3][0]; q1 = qf[3][1]; q2 = qf[3][2]; q3 = qf[3][3]; } } while (0)
#define ATT_STORE(h, r0, r1, r2, r3) do { \
                if ((h) == 0 && !dry) mbar_wait(sb + B_SF, 1);        \
                stmatrix_x4(ostore + (((2 * (h) + (lane >> 4)) ^ (lane & 7)) << 4), r0, r1, r2, r3); \
                if (!dry) stg_relaxed(odst + 32 * (h), make_uint4(((r0) & ~1u) | tag, ((r1) & ~1u) | tag, ((r2) & ~1u) | tag, ((r3) & ~1u) | tag)); \
                } while (0)
            auto attention = [&](auto masked_tag) {
            constexpr bool MASKED = decltype(masked_tag)::value;
            const float NEG = -INFINITY;
            const uint32_t ONES = 0x3F803F80u;
            float sa[8][2][4];
            float o[2][4], ls[4];
            float m0, m1;
            uint32_t q0 = qf[0][0], q1 = qf[0][1], q2 = qf[0][2], q3 = qf[0][3];
            auto qk = [&](float (&s)[8][2][4], int ps, int t, uint32_t kbase, bool merged) {
                if (merged) {
                    const uint4 kd = lds128(kbase + 16 * 512);
                    const uint4 kf = lds128(kbase);
                    float f[2][4];
                    const float ci = (!MASKED || opaque(gb0) >= 0) ? 0.f : NEG;
                    mma16816_c(s[0][0], q0, q1, q2, q3, kd.x, kd.y, 0.f);
                    mma16816_c(s[0][1], q0, q1, q2, q3, kd.z, kd.w, 0.f);
                    mma16816_c(f[0], q0, q1, q2, q3, kf.x, kf.y, ci);
                    mma16816_c(f[1], q0, q1, q2, q3, kf.z, kf.w, ci);
#pragma unroll
                    for (int u = 0; u < 2; u++)
#pragma unroll
                        for (int e = 0; e < 4; e++) {
                            const int row = g + 8 * (e >> 1), col = 8 * u + 2 * c + (e & 1);
                            s[0][u][e] = (col > row) ? f[u][e] : s[0][u][e];
                        }
                } else {
                    const uint4 kf = lds128(kbase + (8 * ps + t) * 512);
                    const float ci = (!MASKED || opaque(gb0) + 8 * ps + t >= 0) ? 0.f : NEG;
                    mma16816_c(s[t][0], q0, q1, q2, q3, kf.x, kf.y, ci);
                    mma16816_c(s[t][1], q0, q1, q2, q3, kf.z, kf.w, ci);
                }
            };
            auto rowmax = [&](float (&s)[8][2][4], float b0, float b1, float& n0, float& n1) {
                int i0 = __float_as_int(b0), i1 = __float_as_int(b1);
#pragma unroll
                for (int t = 0; t < 8; t++)
#pragma unroll
                    for (int u = 0; u < 2; u++) {
                        i0 = __vimax3_s32(i0, __float_as_int(s[t][u][0]), __float_as_int(s[t][u][1]));
                        i1 = __vimax3_s32(i1, __float_as_int(s[t][u][2]), __float_as_int(s[t][u][3]));
                    }
                i0 = max(i0, __shfl_xor_sync(0xffffffffu, i0, 1)); i1 = max(i1, __shfl_xor_sync(0xffffffffu, i1, 1));
                i0 = max(i0, __shfl_xor_sync(0xffffffffu, i0, 2)); i1 = max(i1, __shfl_xor_sync(0xffffffffu, i1, 2));
                n0 = __int_as_float(i0); n1 = __int_as_float(i1);
                if (__any_sync(0xffffffffu, (i0 | i1) < 0)) {
                    asm volatile("" ::: "memory");
                    n0 = b0; n1 = b1;
#pragma unroll
                    for (int t = 0; t < 8; t++)
#pragma unroll
                        for (int u = 0; u < 2; u++) {
                            n0 = fmaxf(n0, fmaxf(s[t][u][0], s[t][u][1]));
                            n1 = fmaxf(n1, fmaxf(s[t][u][2], s[t][u][3]));
                        }
                    n0 = fmaxf(n0, __shfl_xor_sync(0xffffffffu, n0, 1)); n1 = fmaxf(n1, __shfl_xor_sync(0xffffffffu, n1, 1));
                    n0 = fmaxf(n0, __shfl_xor_sync(0xffffffffu, n0, 2)); n1 = fmaxf(n1, __shfl_xor_sync(0xffffffffu, n1, 2));
                }
            };
            auto pv = [&](const float (&p)[2][4], uint32_t vaddr) {
                const uint4 vf = lds128(vaddr);
                const uint32_t a0 = pack_bf16(p[0][0], p[0][1]), a1 = pack_bf16(p[0][2], p[0][3]);
                const uint32_t a2 = pack_bf16(p[1][0], p[1][1]), a3 = pack_bf16(p[1][2], p[1][3]);
                mma16816(o[0], a0, a1, a2, a3, vf.x, vf.y);
                mma16816(o[1], a0, a1, a2, a3, vf.z, vf.w);
                mma16816(ls, a0, a1, a2, a3, ONES, ONES);
            };
            auto expv = [&](float (&s)[8][2][4], int ps, int t, float mc0, float mc1, uint32_t vbase, bool merged) {
                float p[2][4];
#pragma unroll
                for (int u = 0; u < 2; u++) {
                    p[u][0] = ex2(fmaf(s[t][u][0], SC, -mc0)); p[u][1] = ex2(fmaf(s[t][u][1], SC, -mc0));
                    p[u][2] = ex2(fmaf(s[t][u][2], SC, -mc1)); p[u][3] = ex2(fmaf(s[t][u][3], SC, -mc1));
                }
                if (merged) {
                    float pd[2][4], pf[2][4];
#pragma unroll
                    for (int u = 0; u < 2; u++)
#pragma unroll
                        for (int e = 0; e < 4; e++) {
                            const int row = g + 8 * (e >> 1), col = 8 * u + 2 * c + (e & 1);
                            pf[u][e] = (col > row) ? p[u][e] : 0.f;
                            pd[u][e] = (col > row) ? 0.f : p[u][e];
                        }
                    pv(pd, vbase + 16 * 512);
                    pv(pf, vbase);
                } else {
                    pv(p, vbase + (8 * ps + t) * 512);
                }
            };
            uint32_t kbase = 0, vbase = 0;
#pragma unroll 1
            for (int hh = 0; hh < NHEADS; hh++) {
                ATT_KWAIT(kbase);
                if (hh > 0) ATT_NEXTQ(hh);
#pragma unroll
                for (int ps = 0; ps < 2; ps++) {
#pragma unroll
                    for (int t = 0; t < 8; t++) qk(sa, ps, t, kbase, ps == 0 && t == 0);
                    if (ps == 1) ATT_KREL();
                    float n0, n1;
                    rowmax(sa, ps ? m0 : NEG, ps ? m1 : NEG, n0, n1);
                    if (ps == 0) {
                        ATT_VWAIT(vbase);
#pragma unroll
                        for (int e = 0; e < 4; e++) { o[0][e] = 0.f; o[1][e] = 0.f; ls[e] = 0.f; }
                    } else {
                        const float a0 = ex2((m0 - n0) * SC), a1 = ex2((m1 - n1) * SC);
                        ls[0] *= a0; ls[2] *= a1;
                        o[0][0] *= a0; o[0][1] *= a0; o[1][0] *= a0; o[1][1] *= a0;
                        o[0][2] *= a1; o[0][3] *= a1; o[1][2] *= a1; o[1][3] *= a1;
                    }
                    m0 = n0; m1 = n1;
                    const float mc0 = n0 * SC, mc1 = n1 * SC;
#pragma unroll
                    for (int t = 0; t < 8; t++) expv(sa, ps, t, mc0, mc1, vbase, ps == 0 && t == 0);
                }
                ATT_VREL();
                const float f0 = __fdividef(g0, ls[0]), f1 = __fdividef(g1, ls[2]);
                ATT_STORE(hh, pack_bf16(o[0][0] * f0, o[0][1] * f0), pack_bf16(o[0][2] * f1, o[0][3] * f1),
                              pack_bf16(o[1][0] * f0, o[1][1] * f0), pack_bf16(o[1][2] * f1, o[1][3] * f1));
            }
            };
            if (ti >= 2) attention(BoolTag<false>{}); else attention(BoolTag<true>{});
            fence_async_smem();
            __syncwarp();
            if (lane0) mbar_arrive(sb + B_ODONE);
        }
        TS(7);
        {
            float acc[32];
            uint4 pv[4][8 - NHS];
            if (!dry) mbar_wait(sb + B_PREADY, 0);
            {
                const uint4* p = g_part + (size_t)((ti * 8 + tj) * 8 + NHS) * 1024 + warp * 128 + lane;
#pragma unroll
                for (int s = 0; s < 8 - NHS; s++)
#pragma unroll
                    for (int n = 0; n < 4; n++) pv[n][s] = dry ? make_uint4(0u, 0u, 0u, 0u) : ldg_weak(p + s * 1024 + n * 32);
            }
            uint4 af[7][4];
            const uint4* osrc = g_of + (size_t)((ti * 8 * 8 + warp) * 4) * 32 + lane;
#pragma unroll
            for (int m = 0; m < 7; m++)
#pragma unroll
                for (int h = 0; h < 4; h++)
                    af[m][h] = dry ? make_uint4(tag, tag, tag, tag) : ldg_weak(osrc + ((tj + 1 + m) & 7) * 1024 + h * 32);
            TS(18);
            if (!dry) mbar_wait(sb + B_WOFULL, 0);
            if (!dry) mbar_wait(sb + B_ODONE, 0);
            TS(15);
            wgmma_fence();
#pragma unroll
            for (int k = 0; k < 4; k++) wgmma_ss_n64(acc, desc_a(sb + OWN_OFF + wg * 8192 + 32 * k), desc_b(sb + X_OFF + tj * 8192 + 2048 * k), k);
            wgmma_commit();
            float base[32];
            if (!dry) mbar_wait(sb + B_HSUM, 0);
#pragma unroll
            for (int n = 0; n < 4; n++) {
                const uint4 u0 = lds128(sb + HSUM_OFF + (warp * 8 + 2 * n) * 512 + lane * 16), u1 = lds128(sb + HSUM_OFF + (warp * 8 + 2 * n + 1) * 512 + lane * 16);
                float* a = &base[8 * n];
                a[0] = __uint_as_float(u0.x); a[1] = __uint_as_float(u0.y); a[2] = __uint_as_float(u0.z); a[3] = __uint_as_float(u0.w);
                a[4] = __uint_as_float(u1.x); a[5] = __uint_as_float(u1.y); a[6] = __uint_as_float(u1.z); a[7] = __uint_as_float(u1.w);
#pragma unroll
                for (int s = 0; s < 8 - NHS; s++) {
                    a[0] += bf_lo(pv[n][s].x); a[1] += bf_hi(pv[n][s].x); a[2] += bf_lo(pv[n][s].y); a[3] += bf_hi(pv[n][s].y);
                    a[4] += bf_lo(pv[n][s].z); a[5] += bf_hi(pv[n][s].z); a[6] += bf_lo(pv[n][s].w); a[7] += bf_hi(pv[n][s].w);
                }
            }
            fence_acc(base);
            TS(16);
#pragma unroll
            for (int m = 0; m < 7; m++) {
                const int js = (tj + 1 + m) & 7;
                for (int it = 0; it < (1 << 16); it++) {
                    bool ok = true;
#pragma unroll
                    for (int h = 0; h < 4; h++) {
                        const uint32_t bad = ((af[m][h].x ^ tag) | (af[m][h].y ^ tag) | (af[m][h].z ^ tag) | (af[m][h].w ^ tag)) & 1u;
                        if (bad) { af[m][h] = ldg_relaxed(osrc + js * 1024 + h * 32); ok = false; }
                    }
                    if (__all_sync(0xffffffffu, ok)) break;
                }
                wgmma_fence();
#pragma unroll
                for (int h = 0; h < 4; h++)
                    wgmma_rs_n64(acc, af[m][h].x, af[m][h].y, af[m][h].z, af[m][h].w, desc_b(sb + X_OFF + js * 8192 + 2048 * h), 1);
                wgmma_commit();
            }
            wgmma_wait<0>();
            fence_acc(acc);
            TS(17);
#pragma unroll
            for (int k = 0; k < 32; k++) acc[k] += base[k];
            __nv_bfloat16* o = out + (size_t)(ti * 128 + warp * 16 + g) * 512 + tj * 64 + ((lane & 1) ? 8 : 0) + (lane & 2) * 2;
            const bool odd = lane & 1;
#pragma unroll
            for (int t2 = 0; t2 < 4; t2++) {
                const uint32_t lo0 = pack_bf16(acc[8 * t2 + 0], acc[8 * t2 + 1]), hi0 = pack_bf16(acc[8 * t2 + 2], acc[8 * t2 + 3]);
                const uint32_t lo1 = pack_bf16(acc[8 * t2 + 4], acc[8 * t2 + 5]), hi1 = pack_bf16(acc[8 * t2 + 6], acc[8 * t2 + 7]);
                const uint32_t sl = __shfl_xor_sync(0xffffffffu, odd ? lo0 : lo1, 1), sh = __shfl_xor_sync(0xffffffffu, odd ? hi0 : hi1, 1);
                if (!dry) *reinterpret_cast<uint2*>(o + 16 * t2) = odd ? make_uint2(sl, lo1) : make_uint2(lo0, sl);
                if (!dry) *reinterpret_cast<uint2*>(o + 16 * t2 + 8 * 512) = odd ? make_uint2(sh, hi1) : make_uint2(hi0, sh);
            }
            if (tid == 0 && !dry) TSG(30);
        }
        TS(8);
    }
}

typedef CUresult (*PFN_encodeTiled)(CUtensorMap*, CUtensorMapDataType, cuuint32_t, void*, const cuuint64_t*, const cuuint64_t*,
                                    const cuuint32_t*, const cuuint32_t*, CUtensorMapInterleave, CUtensorMapSwizzle,
                                    CUtensorMapL2promotion, CUtensorMapFloatOOBfill);

void make_map(PFN_encodeTiled enc, CUtensorMap* m, const void* base, int rank, const cuuint64_t* dims, const cuuint64_t* strides, const cuuint32_t* box) {
    cuuint32_t es[5] = {1, 1, 1, 1, 1};
    enc(m, CU_TENSOR_MAP_DATA_TYPE_BFLOAT16, (cuuint32_t)rank, const_cast<void*>(base), dims, strides, box, es,
        CU_TENSOR_MAP_INTERLEAVE_NONE, CU_TENSOR_MAP_SWIZZLE_128B, CU_TENSOR_MAP_L2_PROMOTION_L2_256B, CU_TENSOR_MAP_FLOAT_OOB_FILL_NONE);
}

}

extern "C" void kernel_launch(void* const* d_in, const int* in_sizes, int n_in, void* d_out, int out_size) {
    (void)in_sizes; (void)n_in; (void)out_size;
    const void* x = d_in[0]; const void* wqkv = d_in[1]; const void* wo = d_in[2];
    const void* w1 = d_in[4]; const void* w2 = d_in[5]; const void* gate_w = d_in[6];
    static PFN_encodeTiled enc = nullptr;
    if (!enc) {
        void* fn = nullptr; cudaDriverEntryPointQueryResult st;
        cudaGetDriverEntryPoint("cuTensorMapEncodeTiled", &fn, cudaEnableDefault, &st);
        enc = (PFN_encodeTiled)fn;
        cudaFuncSetAttribute(fused_kernel, cudaFuncAttributeMaxDynamicSharedMemorySize, SMEM_BYTES);
    }
    CUtensorMap mx, mqkv, mw1, mw2, mwo, mw1a;
    { cuuint64_t d[4] = {64, 512, 3, 8}, s[3] = {3584, 128, 448}; cuuint32_t b[4] = {64, 32, 3, 1}; make_map(enc, &mw1a, w1, 4, d, s, b); }
    { cuuint64_t d[2] = {512, 2048}, s[1] = {1024}; cuuint32_t b[2] = {64, 128}; make_map(enc, &mx, x, 2, d, s, b); }
    { cuuint64_t d[4] = {64, 512, 8, 3}, s[3] = {3072, 128, 1024}; cuuint32_t b[4] = {64, 32, 1, 3}; make_map(enc, &mqkv, wqkv, 4, d, s, b); }
    { cuuint64_t d[2] = {1792, 512}, s[1] = {3584}; cuuint32_t b[2] = {64, 32}; make_map(enc, &mw1, w1, 2, d, s, b); }
    { cuuint64_t d[3] = {64, 1792, 8}, s[2] = {1024, 128}; cuuint32_t b[3] = {64, 32, 2}; make_map(enc, &mw2, w2, 3, d, s, b); }
    { cuuint64_t d[2] = {512, 512}, s[1] = {1024}; cuuint32_t b[2] = {64, 256}; make_map(enc, &mwo, wo, 2, d, s, b); }
    fused_kernel<<<NCTA, 384, SMEM_BYTES, cudaStreamPerThread>>>(mx, mqkv, mw1, mw2, mwo, mw1a, (const __nv_bfloat16*)gate_w, (__nv_bfloat16*)d_out,
                                           (const uint8_t*)w1, (const uint8_t*)w2, (const uint8_t*)wo);
}
```

```cpp
#include <cuda_runtime.h>
#include <cuda_bf16.h>
#include <cuda.h>
#include <stdint.h>

namespace {

#define PF1_AT 1
#define PF2_AT 5
#define LEAD1 2
#define NCTA 132
constexpr int RING = 6;
constexpr int SLOT = 16384;
constexpr uint32_t X_OFF = 0;
constexpr uint32_t STG_OFF = X_OFF + 4 * 16384;
constexpr uint32_t RING_OFF = 131072;
constexpr uint32_t BAR_OFF = RING_OFF + RING * SLOT;
constexpr uint32_t B_FULL = BAR_OFF, B_EMPTY = BAR_OFF + 64, B_XFULL = BAR_OFF + 128, B_HDEAD = BAR_OFF + 192,
                   B_EREADY = BAR_OFF + 200, B_KVDONE = BAR_OFF + 208, B_ODONE = BAR_OFF + 224,
                   B_KVREADY = BAR_OFF + 232, B_WOFULL = BAR_OFF + 240, B_HSUM = BAR_OFF + 248, B_PREADY = BAR_OFF + 264,
                   B_SQ = BAR_OFF + 272, B_SF = BAR_OFF + 304;
constexpr uint32_t EPOCH_OFF = BAR_OFF + 256, ITEM_OFF = BAR_OFF + 260, OSRC_OFF = BAR_OFF + 384;
constexpr uint32_t OWN_OFF = X_OFF + 4 * 16384;
constexpr uint32_t HSUM_OFF = X_OFF + 6 * 16384;
constexpr uint32_t SMEM_BYTES = BAR_OFF + 1024;

constexpr int N_QKV = 16, N_FFN1 = 16, N_FFN2 = 14, N_KV = 8, N_O = 7;

__device__ uint4 g_kf[32 * 128 * 32];
__device__ uint4 g_vf[32 * 128 * 32];
__device__ uint4 g_part[16 * 8 * 8 * 8 * 4 * 32];
__device__ __nv_bfloat16 g_o[2048 * 512];
__device__ unsigned g_ticket;
__device__ unsigned g_kvcnt[128 * 32];
__device__ unsigned g_pcnt[128 * 32];
__device__ unsigned g_ocnt[128 * 32];
#define TS(k) do {} while (0)
#define TS2(k) do {} while (0)
#define TS2X(k) do {} while (0)
#define TSX(k) do {} while (0)
#define TSG(k) do {} while (0)

__device__ __forceinline__ uint32_t smem_u32(const void* p) { return (uint32_t)__cvta_generic_to_shared(p); }
__device__ __forceinline__ void mbar_init(uint32_t bar, uint32_t cnt) { asm volatile("mbarrier.init.shared::cta.b64 [%0], %1;" :: "r"(bar), "r"(cnt) : "memory"); }
__device__ __forceinline__ void mbar_expect_tx(uint32_t bar, uint32_t bytes) { asm volatile("mbarrier.arrive.expect_tx.shared::cta.b64 _, [%0], %1;" :: "r"(bar), "r"(bytes) : "memory"); }
__device__ __forceinline__ void mbar_expect_only(uint32_t bar, uint32_t bytes) { asm volatile("mbarrier.expect_tx.relaxed.cta.shared::cta.b64 [%0], %1;" :: "r"(bar), "r"(bytes) : "memory"); }
__device__ __forceinline__ void mbar_arrive(uint32_t bar) { asm volatile("mbarrier.arrive.shared::cta.b64 _, [%0];" :: "r"(bar) : "memory"); }
__device__ __forceinline__ void mbar_wait(uint32_t bar, uint32_t parity) {
    asm volatile("{\n.reg .pred P1, P2;\n.reg .u32 n;\nmov.u32 n, 0;\n"
                 "WAIT_LOOP:\n"
                 "mbarrier.try_wait.parity.shared::cta.b64 P1, [%0], %1;\n"
                 "@P1 bra WAIT_DONE;\n"
                 "add.u32 n, n, 1;\n"
                 "setp.lt.u32 P2, n, 0x400000;\n"
                 "@P2 bra WAIT_LOOP;\n"
                 "WAIT_DONE:\n}" :: "r"(bar), "r"(parity) : "memory");
}
__device__ __forceinline__ void tma_2d(uint32_t dst, const void* map, uint32_t bar, int c0, int c1) {
    asm volatile("cp.async.bulk.tensor.2d.shared::cluster.global.mbarrier::complete_tx::bytes [%0], [%1, {%3, %4}], [%2];"
        :: "r"(dst), "l"(map), "r"(bar), "r"(c0), "r"(c1) : "memory");
}
__device__ __forceinline__ void tma_3d(uint32_t dst, const void* map, uint32_t bar, int c0, int c1, int c2) {
    asm volatile("cp.async.bulk.tensor.3d.shared::cluster.global.mbarrier::complete_tx::bytes [%0], [%1, {%3, %4, %5}], [%2];"
        :: "r"(dst), "l"(map), "r"(bar), "r"(c0), "r"(c1), "r"(c2) : "memory");
}
__device__ __forceinline__ void tma_4d(uint32_t dst, const void* map, uint32_t bar, int c0, int c1, int c2, int c3) {
    asm volatile("cp.async.bulk.tensor.4d.shared::cluster.global.mbarrier::complete_tx::bytes [%0], [%1, {%3, %4, %5, %6}], [%2];"
        :: "r"(dst), "l"(map), "r"(bar), "r"(c0), "r"(c1), "r"(c2), "r"(c3) : "memory");
}
__device__ __forceinline__ void bulk_g2s(uint32_t dst, const void* src, uint32_t bytes, uint32_t bar) {
    asm volatile("cp.async.bulk.shared::cluster.global.mbarrier::complete_tx::bytes [%0], [%1], %2, [%3];"
        :: "r"(dst), "l"(src), "r"(bytes), "r"(bar) : "memory");
}
__device__ __forceinline__ void prefetch_l2(const void* src, uint32_t bytes) {
    asm volatile("cp.async.bulk.prefetch.L2.global [%0], %1;" :: "l"(src), "r"(bytes) : "memory");
}
__device__ __forceinline__ bool elect_one() {
    uint32_t p;
    asm volatile("{\n.reg .pred P;\nelect.sync _|P, 0xffffffff;\nselp.u32 %0, 1, 0, P;\n}" : "=r"(p));
    return p != 0;
}
__device__ __forceinline__ void wgmma_fence() { asm volatile("wgmma.fence.sync.aligned;" ::: "memory"); }
__device__ __forceinline__ void wgmma_commit() { asm volatile("wgmma.commit_group.sync.aligned;" ::: "memory"); }
template <int N> __device__ __forceinline__ void wgmma_wait() { asm volatile("wgmma.wait_group.sync.aligned %0;" :: "n"(N) : "memory"); }
__device__ __forceinline__ void fence_async_smem() { asm volatile("fence.proxy.async.shared::cta;" ::: "memory"); }
__device__ __forceinline__ uint64_t desc_a(uint32_t addr) {
    return (uint64_t)((addr & 0x3FFFF) >> 4) | ((uint64_t)1 << 16) | ((uint64_t)(1024 >> 4) << 32) | ((uint64_t)1 << 62);
}
__device__ __forceinline__ uint64_t desc_b(uint32_t addr) {
    return (uint64_t)((addr & 0x3FFFF) >> 4) | ((uint64_t)(4096 >> 4) << 16) | ((uint64_t)(1024 >> 4) << 32) | ((uint64_t)1 << 62);
}
__device__ __forceinline__ uint64_t desc_kv(uint32_t addr) {
    return (uint64_t)((addr & 0x3FFFF) >> 4) | ((uint64_t)(256 >> 4) << 16) | ((uint64_t)(256 >> 4) << 32) | ((uint64_t)3 << 62);
}
__device__ __forceinline__ uint32_t pack_bf16(float lo, float hi) {
    uint32_t r; asm("cvt.rn.bf16x2.f32 %0, %1, %2;" : "=r"(r) : "f"(hi), "f"(lo)); return r;
}
__device__ __forceinline__ uint32_t pack_bf16_relu(float lo, float hi) {
    uint32_t r; asm("cvt.rn.relu.bf16x2.f32 %0, %1, %2;" : "=r"(r) : "f"(hi), "f"(lo)); return r;
}
__device__ __forceinline__ uint32_t movmatrix(uint32_t a) {
    uint32_t d; asm volatile("movmatrix.sync.aligned.m8n8.trans.b16 %0, %1;" : "=r"(d) : "r"(a)); return d;
}
__device__ __forceinline__ void stmatrix_x4(uint32_t addr, uint32_t r0, uint32_t r1, uint32_t r2, uint32_t r3) {
    asm volatile("stmatrix.sync.aligned.m8n8.x4.shared.b16 [%0], {%1, %2, %3, %4};" :: "r"(addr), "r"(r0), "r"(r1), "r"(r2), "r"(r3) : "memory");
}
__device__ __forceinline__ uint4 lds128(uint32_t addr) {
    uint4 v; asm volatile("ld.shared.v4.b32 {%0, %1, %2, %3}, [%4];" : "=r"(v.x), "=r"(v.y), "=r"(v.z), "=r"(v.w) : "r"(addr) : "memory"); return v;
}
__device__ __forceinline__ void mma16816(float (&c)[4], uint32_t a0, uint32_t a1, uint32_t a2, uint32_t a3, uint32_t b0, uint32_t b1) {
    asm volatile("mma.sync.aligned.m16n8k16.row.col.f32.bf16.bf16.f32 {%0,%1,%2,%3}, {%4,%5,%6,%7}, {%8,%9}, {%0,%1,%2,%3};"
        : "+f"(c[0]), "+f"(c[1]), "+f"(c[2]), "+f"(c[3]) : "r"(a0), "r"(a1), "r"(a2), "r"(a3), "r"(b0), "r"(b1));
}
__device__ __forceinline__ void mma16816_c(float (&c)[4], uint32_t a0, uint32_t a1, uint32_t a2, uint32_t a3, uint32_t b0, uint32_t b1, float ci) {
    asm volatile("mma.sync.aligned.m16n8k16.row.col.f32.bf16.bf16.f32 {%0,%1,%2,%3}, {%4,%5,%6,%7}, {%8,%9}, {%10,%10,%10,%10};"
        : "=f"(c[0]), "=f"(c[1]), "=f"(c[2]), "=f"(c[3]) : "r"(a0), "r"(a1), "r"(a2), "r"(a3), "r"(b0), "r"(b1), "f"(ci));
}
__device__ __forceinline__ int opaque(int v) { asm volatile("" : "+r"(v)); return v; }
__device__ __forceinline__ float ex2(float x) { float y; asm("ex2.approx.ftz.f32 %0, %1;" : "=f"(y) : "f"(x)); return y; }
__device__ __forceinline__ unsigned ld_acquire(const unsigned* p) {
    unsigned v; asm volatile("ld.acquire.gpu.global.u32 %0, [%1];" : "=r"(v) : "l"(p) : "memory"); return v;
}
__device__ __forceinline__ void red_release(unsigned* p, unsigned v) {
    asm volatile("red.release.gpu.global.add.u32 [%0], %1;" :: "l"(p), "r"(v) : "memory");
}
__device__ __forceinline__ void wait_counter(const unsigned* p, unsigned target) {
    uint32_t n = 0;
    while ((int)(ld_acquire(p) - target) < 0) { if (++n > (1u << 20)) break; }
}
__device__ __forceinline__ uint4 ldg_weak(const uint4* p) {
    uint4 v; asm volatile("ld.global.L1::no_allocate.v4.b32 {%0, %1, %2, %3}, [%4];" : "=r"(v.x), "=r"(v.y), "=r"(v.z), "=r"(v.w) : "l"(p) : "memory"); return v;
}
__device__ __forceinline__ float bf_lo(uint32_t v) { return __uint_as_float(v << 16); }
__device__ __forceinline__ float bf_hi(uint32_t v) { return __uint_as_float(v & 0xFFFF0000u); }

__device__ __forceinline__ void wgmma_ss_n64(float (&d)[32], uint64_t da, uint64_t db, int scale_d) {
    asm volatile("{\n.reg .pred p;\nsetp.ne.b32 p, %34, 0;\n"
        "wgmma.mma_async.sync.aligned.m64n64k16.f32.bf16.bf16 {%0, %1, %2, %3, %4, %5, %6, %7, %8, %9, %10, %11, %12, %13, %14, %15, %16, %17, %18, %19, %20, %21, %22, %23, %24, %25, %26, %27, %28, %29, %30, %31}, %32, %33, p, 1, 1, 0, 1;\n}\n"
        : "+f"(d[0]), "+f"(d[1]), "+f"(d[2]), "+f"(d[3]), "+f"(d[4]), "+f"(d[5]), "+f"(d[6]), "+f"(d[7]), "+f"(d[8]), "+f"(d[9]), "+f"(d[10]), "+f"(d[11]), "+f"(d[12]), "+f"(d[13]), "+f"(d[14]), "+f"(d[15]), "+f"(d[16]), "+f"(d[17]), "+f"(d[18]), "+f"(d[19]), "+f"(d[20]), "+f"(d[21]), "+f"(d[22]), "+f"(d[23]), "+f"(d[24]), "+f"(d[25]), "+f"(d[26]), "+f"(d[27]), "+f"(d[28]), "+f"(d[29]), "+f"(d[30]), "+f"(d[31])
        : "l"(da), "l"(db), "r"(scale_d));
}
__device__ __forceinline__ void wgmma_ss_n128(float (&d)[64], uint64_t da, uint64_t db, int scale_d) {
    asm volatile("{\n.reg .pred p;\nsetp.ne.b32 p, %66, 0;\n"
        "wgmma.mma_async.sync.aligned.m64n128k16.f32.bf16.bf16 {%0, %1, %2, %3, %4, %5, %6, %7, %8, %9, %10, %11, %12, %13, %14, %15, %16, %17, %18, %19, %20, %21, %22, %23, %24, %25, %26, %27, %28, %29, %30, %31, %32, %33, %34, %35, %36, %37, %38, %39, %40, %41, %42, %43, %44, %45, %46, %47, %48, %49, %50, %51, %52, %53, %54, %55, %56, %57, %58, %59, %60, %61, %62, %63}, %64, %65, p, 1, 1, 0, 1;\n}\n"
        : "+f"(d[0]), "+f"(d[1]), "+f"(d[2]), "+f"(d[3]), "+f"(d[4]), "+f"(d[5]), "+f"(d[6]), "+f"(d[7]), "+f"(d[8]), "+f"(d[9]), "+f"(d[10]), "+f"(d[11]), "+f"(d[12]), "+f"(d[13]), "+f"(d[14]), "+f"(d[15]), "+f"(d[16]), "+f"(d[17]), "+f"(d[18]), "+f"(d[19]), "+f"(d[20]), "+f"(d[21]), "+f"(d[22]), "+f"(d[23]), "+f"(d[24]), "+f"(d[25]), "+f"(d[26]), "+f"(d[27]), "+f"(d[28]), "+f"(d[29]), "+f"(d[30]), "+f"(d[31]), "+f"(d[32]), "+f"(d[33]), "+f"(d[34]), "+f"(d[35]), "+f"(d[36]), "+f"(d[37]), "+f"(d[38]), "+f"(d[39]), "+f"(d[40]), "+f"(d[41]), "+f"(d[42]), "+f"(d[43]), "+f"(d[44]), "+f"(d[45]), "+f"(d[46]), "+f"(d[47]), "+f"(d[48]), "+f"(d[49]), "+f"(d[50]), "+f"(d[51]), "+f"(d[52]), "+f"(d[53]), "+f"(d[54]), "+f"(d[55]), "+f"(d[56]), "+f"(d[57]), "+f"(d[58]), "+f"(d[59]), "+f"(d[60]), "+f"(d[61]), "+f"(d[62]), "+f"(d[63])
        : "l"(da), "l"(db), "r"(scale_d));
}
__device__ __forceinline__ void wgmma_ss_n200(float (&d)[100], uint64_t da, uint64_t db, int scale_d) {
    asm volatile("{\n.reg .pred p;\nsetp.ne.b32 p, %102, 0;\n"
        "wgmma.mma_async.sync.aligned.m64n200k16.f32.bf16.bf16 {%0, %1, %2, %3, %4, %5, %6, %7, %8, %9, %10, %11, %12, %13, %14, %15, %16, %17, %18, %19, %20, %21, %22, %23, %24, %25, %26, %27, %28, %29, %30, %31, %32, %33, %34, %35, %36, %37, %38, %39, %40, %41, %42, %43, %44, %45, %46, %47, %48, %49, %50, %51, %52, %53, %54, %55, %56, %57, %58, %59, %60, %61, %62, %63, %64, %65, %66, %67, %68, %69, %70, %71, %72, %73, %74, %75, %76, %77, %78, %79, %80, %81, %82, %83, %84, %85, %86, %87, %88, %89, %90, %91, %92, %93, %94, %95, %96, %97, %98, %99}, %100, %101, p, 1, 1, 0, 1;\n}\n"
        : "+f"(d[0]), "+f"(d[1]), "+f"(d[2]), "+f"(d[3]), "+f"(d[4]), "+f"(d[5]), "+f"(d[6]), "+f"(d[7]), "+f"(d[8]), "+f"(d[9]), "+f"(d[10]), "+f"(d[11]), "+f"(d[12]), "+f"(d[13]), "+f"(d[14]), "+f"(d[15]), "+f"(d[16]), "+f"(d[17]), "+f"(d[18]), "+f"(d[19]), "+f"(d[20]), "+f"(d[21]), "+f"(d[22]), "+f"(d[23]), "+f"(d[24]), "+f"(d[25]), "+f"(d[26]), "+f"(d[27]), "+f"(d[28]), "+f"(d[29]), "+f"(d[30]), "+f"(d[31]), "+f"(d[32]), "+f"(d[33]), "+f"(d[34]), "+f"(d[35]), "+f"(d[36]), "+f"(d[37]), "+f"(d[38]), "+f"(d[39]), "+f"(d[40]), "+f"(d[41]), "+f"(d[42]), "+f"(d[43]), "+f"(d[44]), "+f"(d[45]), "+f"(d[46]), "+f"(d[47]), "+f"(d[48]), "+f"(d[49]), "+f"(d[50]), "+f"(d[51]), "+f"(d[52]), "+f"(d[53]), "+f"(d[54]), "+f"(d[55]), "+f"(d[56]), "+f"(d[57]), "+f"(d[58]), "+f"(d[59]), "+f"(d[60]), "+f"(d[61]), "+f"(d[62]), "+f"(d[63]), "+f"(d[64]), "+f"(d[65]), "+f"(d[66]), "+f"(d[67]), "+f"(d[68]), "+f"(d[69]), "+f"(d[70]), "+f"(d[71]), "+f"(d[72]), "+f"(d[73]), "+f"(d[74]), "+f"(d[75]), "+f"(d[76]), "+f"(d[77]), "+f"(d[78]), "+f"(d[79]), "+f"(d[80]), "+f"(d[81]), "+f"(d[82]), "+f"(d[83]), "+f"(d[84]), "+f"(d[85]), "+f"(d[86]), "+f"(d[87]), "+f"(d[88]), "+f"(d[89]), "+f"(d[90]), "+f"(d[91]), "+f"(d[92]), "+f"(d[93]), "+f"(d[94]), "+f"(d[95]), "+f"(d[96]), "+f"(d[97]), "+f"(d[98]), "+f"(d[99])
        : "l"(da), "l"(db), "r"(scale_d));
}
__device__ __forceinline__ void wgmma_ss_n224(float (&d)[112], uint64_t da, uint64_t db, int scale_d) {
    asm volatile("{\n.reg .pred p;\nsetp.ne.b32 p, %114, 0;\n"
        "wgmma.mma_async.sync.aligned.m64n224k16.f32.bf16.bf16 {%0, %1, %2, %3, %4, %5, %6, %7, %8, %9, %10, %11, %12, %13, %14, %15, %16, %17, %18, %19, %20, %21, %22, %23, %24, %25, %26, %27, %28, %29, %30, %31, %32, %33, %34, %35, %36, %37, %38, %39, %40, %41, %42, %43, %44, %45, %46, %47, %48, %49, %50, %51, %52, %53, %54, %55, %56, %57, %58, %59, %60, %61, %62, %63, %64, %65, %66, %67, %68, %69, %70, %71, %72, %73, %74, %75, %76, %77, %78, %79, %80, %81, %82, %83, %84, %85, %86, %87, %88, %89, %90, %91, %92, %93, %94, %95, %96, %97, %98, %99, %100, %101, %102, %103, %104, %105, %106, %107, %108, %109, %110, %111}, %112, %113, p, 1, 1, 0, 1;\n}\n"
        : "+f"(d[0]), "+f"(d[1]), "+f"(d[2]), "+f"(d[3]), "+f"(d[4]), "+f"(d[5]), "+f"(d[6]), "+f"(d[7]), "+f"(d[8]), "+f"(d[9]), "+f"(d[10]), "+f"(d[11]), "+f"(d[12]), "+f"(d[13]), "+f"(d[14]), "+f"(d[15]), "+f"(d[16]), "+f"(d[17]), "+f"(d[18]), "+f"(d[19]), "+f"(d[20]), "+f"(d[21]), "+f"(d[22]), "+f"(d[23]), "+f"(d[24]), "+f"(d[25]), "+f"(d[26]), "+f"(d[27]), "+f"(d[28]), "+f"(d[29]), "+f"(d[30]), "+f"(d[31]), "+f"(d[32]), "+f"(d[33]), "+f"(d[34]), "+f"(d[35]), "+f"(d[36]), "+f"(d[37]), "+f"(d[38]), "+f"(d[39]), "+f"(d[40]), "+f"(d[41]), "+f"(d[42]), "+f"(d[43]), "+f"(d[44]), "+f"(d[45]), "+f"(d[46]), "+f"(d[47]), "+f"(d[48]), "+f"(d[49]), "+f"(d[50]), "+f"(d[51]), "+f"(d[52]), "+f"(d[53]), "+f"(d[54]), "+f"(d[55]), "+f"(d[56]), "+f"(d[57]), "+f"(d[58]), "+f"(d[59]), "+f"(d[60]), "+f"(d[61]), "+f"(d[62]), "+f"(d[63]), "+f"(d[64]), "+f"(d[65]), "+f"(d[66]), "+f"(d[67]), "+f"(d[68]), "+f"(d[69]), "+f"(d[70]), "+f"(d[71]), "+f"(d[72]), "+f"(d[73]), "+f"(d[74]), "+f"(d[75]), "+f"(d[76]), "+f"(d[77]), "+f"(d[78]), "+f"(d[79]), "+f"(d[80]), "+f"(d[81]), "+f"(d[82]), "+f"(d[83]), "+f"(d[84]), "+f"(d[85]), "+f"(d[86]), "+f"(d[87]), "+f"(d[88]), "+f"(d[89]), "+f"(d[90]), "+f"(d[91]), "+f"(d[92]), "+f"(d[93]), "+f"(d[94]), "+f"(d[95]), "+f"(d[96]), "+f"(d[97]), "+f"(d[98]), "+f"(d[99]), "+f"(d[100]), "+f"(d[101]), "+f"(d[102]), "+f"(d[103]), "+f"(d[104]), "+f"(d[105]), "+f"(d[106]), "+f"(d[107]), "+f"(d[108]), "+f"(d[109]), "+f"(d[110]), "+f"(d[111])
        : "l"(da), "l"(db), "r"(scale_d));
}
__device__ __forceinline__ void wgmma_rk_n128(float (&d)[64], uint32_t a0, uint32_t a1, uint32_t a2, uint32_t a3, uint64_t db, int scale_d) {
    asm volatile("{\n.reg .pred p;\nsetp.ne.b32 p, %69, 0;\n"
        "wgmma.mma_async.sync.aligned.m64n128k16.f32.bf16.bf16 {%0, %1, %2, %3, %4, %5, %6, %7, %8, %9, %10, %11, %12, %13, %14, %15, %16, %17, %18, %19, %20, %21, %22, %23, %24, %25, %26, %27, %28, %29, %30, %31, %32, %33, %34, %35, %36, %37, %38, %39, %40, %41, %42, %43, %44, %45, %46, %47, %48, %49, %50, %51, %52, %53, %54, %55, %56, %57, %58, %59, %60, %61, %62, %63}, {%64, %65, %66, %67}, %68, p, 1, 1, 0;\n}\n"
        : "+f"(d[0]), "+f"(d[1]), "+f"(d[2]), "+f"(d[3]), "+f"(d[4]), "+f"(d[5]), "+f"(d[6]), "+f"(d[7]), "+f"(d[8]), "+f"(d[9]), "+f"(d[10]), "+f"(d[11]), "+f"(d[12]), "+f"(d[13]), "+f"(d[14]), "+f"(d[15]), "+f"(d[16]), "+f"(d[17]), "+f"(d[18]), "+f"(d[19]), "+f"(d[20]), "+f"(d[21]), "+f"(d[22]), "+f"(d[23]), "+f"(d[24]), "+f"(d[25]), "+f"(d[26]), "+f"(d[27]), "+f"(d[28]), "+f"(d[29]), "+f"(d[30]), "+f"(d[31]), "+f"(d[32]), "+f"(d[33]), "+f"(d[34]), "+f"(d[35]), "+f"(d[36]), "+f"(d[37]), "+f"(d[38]), "+f"(d[39]), "+f"(d[40]), "+f"(d[41]), "+f"(d[42]), "+f"(d[43]), "+f"(d[44]), "+f"(d[45]), "+f"(d[46]), "+f"(d[47]), "+f"(d[48]), "+f"(d[49]), "+f"(d[50]), "+f"(d[51]), "+f"(d[52]), "+f"(d[53]), "+f"(d[54]), "+f"(d[55]), "+f"(d[56]), "+f"(d[57]), "+f"(d[58]), "+f"(d[59]), "+f"(d[60]), "+f"(d[61]), "+f"(d[62]), "+f"(d[63])
        : "r"(a0), "r"(a1), "r"(a2), "r"(a3), "l"(db), "r"(scale_d));
}
__device__ __forceinline__ void wgmma_rk_n64(float (&d)[32], uint32_t a0, uint32_t a1, uint32_t a2, uint32_t a3, uint64_t db, int scale_d) {
    asm volatile("{\n.reg .pred p;\nsetp.ne.b32 p, %37, 0;\n"
        "wgmma.mma_async.sync.aligned.m64n64k16.f32.bf16.bf16 {%0, %1, %2, %3, %4, %5, %6, %7, %8, %9, %10, %11, %12, %13, %14, %15, %16, %17, %18, %19, %20, %21, %22, %23, %24, %25, %26, %27, %28, %29, %30, %31}, {%32, %33, %34, %35}, %36, p, 1, 1, 0;\n}\n"
        : "+f"(d[0]), "+f"(d[1]), "+f"(d[2]), "+f"(d[3]), "+f"(d[4]), "+f"(d[5]), "+f"(d[6]), "+f"(d[7]), "+f"(d[8]), "+f"(d[9]), "+f"(d[10]), "+f"(d[11]), "+f"(d[12]), "+f"(d[13]), "+f"(d[14]), "+f"(d[15]), "+f"(d[16]), "+f"(d[17]), "+f"(d[18]), "+f"(d[19]), "+f"(d[20]), "+f"(d[21]), "+f"(d[22]), "+f"(d[23]), "+f"(d[24]), "+f"(d[25]), "+f"(d[26]), "+f"(d[27]), "+f"(d[28]), "+f"(d[29]), "+f"(d[30]), "+f"(d[31])
        : "r"(a0), "r"(a1), "r"(a2), "r"(a3), "l"(db), "r"(scale_d));
}
__device__ __forceinline__ void wgmma_rs_n16(float (&d)[8], uint32_t a0, uint32_t a1, uint32_t a2, uint32_t a3, uint64_t db, int scale_d) {
    asm volatile("{\n.reg .pred p;\nsetp.ne.b32 p, %13, 0;\n"
        "wgmma.mma_async.sync.aligned.m64n16k16.f32.bf16.bf16 {%0, %1, %2, %3, %4, %5, %6, %7}, {%8, %9, %10, %11}, %12, p, 1, 1, 1;\n}\n"
        : "+f"(d[0]), "+f"(d[1]), "+f"(d[2]), "+f"(d[3]), "+f"(d[4]), "+f"(d[5]), "+f"(d[6]), "+f"(d[7])
        : "r"(a0), "r"(a1), "r"(a2), "r"(a3), "l"(db), "r"(scale_d));
}
template <int N> __device__ __forceinline__ void fence_u32(uint32_t (&d)[N]) {
#pragma unroll
    for (int i = 0; i < N; i++) asm volatile("" : "+r"(d[i]) :: "memory");
}
template <int N> __device__ __forceinline__ void fence_acc(float (&d)[N]) {
#pragma unroll
    for (int i = 0; i < N; i++) asm volatile("" : "+f"(d[i]) :: "memory");
}

__device__ __forceinline__ void bulk_s2g(void* dst, uint32_t src, uint32_t bytes) {
    asm volatile("cp.async.bulk.global.shared::cta.bulk_group [%0], [%1], %2;" :: "l"(dst), "r"(src), "r"(bytes) : "memory");
}
__device__ __forceinline__ void sts128(uint32_t addr, uint4 v) {
    asm volatile("st.shared.v4.b32 [%0], {%1, %2, %3, %4};" :: "r"(addr), "r"(v.x), "r"(v.y), "r"(v.z), "r"(v.w) : "memory");
}
__device__ __forceinline__ void sum_partials(uint32_t sb, int ti, int tj, int lane) {
    for (;;) {
        uint32_t item = 0;
        if (lane == 0) asm volatile("atom.shared.add.u32 %0, [%1], 1;" : "=r"(item) : "r"(sb + ITEM_OFF) : "memory");
        item = __shfl_sync(0xffffffffu, item, 0);
        if (item >= 8) break;
        const uint4* p = g_part + (size_t)((ti * 8 + tj) * 8) * 1024 + item * 128 + lane;
        uint4 v[4][4];
#pragma unroll
        for (int s = 0; s < 4; s++)
#pragma unroll
            for (int n = 0; n < 4; n++) v[n][s] = ldg_weak(p + s * 1024 + n * 32);
#pragma unroll
        for (int n = 0; n < 4; n++) {
            float a[8];
#pragma unroll
            for (int e = 0; e < 8; e++) a[e] = 0.f;
#pragma unroll
            for (int s = 0; s < 4; s++) {
                a[0] += bf_lo(v[n][s].x); a[1] += bf_hi(v[n][s].x); a[2] += bf_lo(v[n][s].y); a[3] += bf_hi(v[n][s].y);
                a[4] += bf_lo(v[n][s].z); a[5] += bf_hi(v[n][s].z); a[6] += bf_lo(v[n][s].w); a[7] += bf_hi(v[n][s].w);
            }
            const uint32_t d = sb + HSUM_OFF + (item * 8 + n * 2) * 512 + lane * 16;
            sts128(d, make_uint4(__float_as_uint(a[0]), __float_as_uint(a[1]), __float_as_uint(a[2]), __float_as_uint(a[3])));
            sts128(d + 512, make_uint4(__float_as_uint(a[4]), __float_as_uint(a[5]), __float_as_uint(a[6]), __float_as_uint(a[7])));
        }
    }
    __syncwarp();
    if (lane == 0) mbar_arrive(sb + B_HSUM);
}

#define PWAIT() mbar_wait(sb + B_EMPTY + 8 * r.slot, r.phase)
#define CWAIT() do { if (!dry) mbar_wait(sb + B_FULL + 8 * r.slot, r.phase); } while (0)
template <bool B> struct BoolTag { static constexpr bool value = B; };
struct Ring {
    int slot; uint32_t phase;
    __device__ __forceinline__ void next() { if (++slot == RING) { slot = 0; phase ^= 1; } }
};

__global__ void __launch_bounds__(384, 1)
fused_kernel(const __grid_constant__ CUtensorMap map_x, const __grid_constant__ CUtensorMap map_qkv,
             const __grid_constant__ CUtensorMap map_w1, const __grid_constant__ CUtensorMap map_w2,
             const __grid_constant__ CUtensorMap map_wo, const __grid_constant__ CUtensorMap map_w1a,
             const __grid_constant__ CUtensorMap map_o,
             const __nv_bfloat16* __restrict__ gate_w, __nv_bfloat16* __restrict__ out,
             const uint8_t* __restrict__ w1p, const uint8_t* __restrict__ w2p, const uint8_t* __restrict__ wop)
{
    extern __shared__ __align__(1024) uint8_t smem_raw[];
    const uint32_t sb = smem_u32(smem_raw);
    const int tid = threadIdx.x, warp = tid >> 5, lane = tid & 31;
    const bool dry = blockIdx.x >= 128;
    const int ti = dry ? (int)(blockIdx.x & 1) * 2 : blockIdx.x >> 3, tj = blockIdx.x & 7;
    if (dry && warp >= 8) {
        asm volatile("setmaxnreg.dec.sync.aligned.u32 88;");
        return;
    }

    if (tid == 0 && !dry) { TSG(31); TSX(0); }
    if (tid == 320) {
        asm volatile("prefetch.tensormap [%0];" :: "l"(&map_x) : "memory");
        asm volatile("prefetch.tensormap [%0];" :: "l"(&map_qkv) : "memory");
        asm volatile("prefetch.tensormap [%0];" :: "l"(&map_w1) : "memory");
        asm volatile("prefetch.tensormap [%0];" :: "l"(&map_w1a) : "memory");
        asm volatile("prefetch.tensormap [%0];" :: "l"(&map_w2) : "memory");
        asm volatile("prefetch.tensormap [%0];" :: "l"(&map_wo) : "memory");
        asm volatile("prefetch.tensormap [%0];" :: "l"(&map_o) : "memory");
    }
    if (tid == 256) {
        mbar_init(sb + B_FULL, 1); mbar_init(sb + B_XFULL, 1);
        fence_async_smem();
        mbar_expect_tx(sb + B_XFULL, 16384);
        tma_2d(sb + X_OFF, &map_x, sb + B_XFULL, 0, ti * 128);
        mbar_expect_only(sb + B_FULL, 12288);
        tma_4d(sb + RING_OFF, &map_qkv, sb + B_FULL, 0, 0, tj, 0);
    }
    uint32_t gwv[N_QKV / 2];
    if (warp == 8) {
        const unsigned short* gws = reinterpret_cast<const unsigned short*>(gate_w);
#pragma unroll
        for (int n = 0; n < N_QKV / 2; n++) gwv[n] = (uint32_t)__ldg(gws + 64 * n + lane) | ((uint32_t)__ldg(gws + 64 * n + 32 + lane) << 16);
    }
    if (tid == 288) {
        for (int s = 1; s < RING; s++) mbar_init(sb + B_FULL + 8 * s, 1);
        for (int s = 0; s < RING; s++) mbar_init(sb + B_EMPTY + 8 * s, 8);
        for (int s = 1; s < 8; s++) mbar_init(sb + B_XFULL + 8 * s, 1);
        fence_async_smem();
    }
    if (tid == 352) {
        mbar_init(sb + B_HDEAD, 8); mbar_init(sb + B_EREADY, 1); mbar_init(sb + B_KVDONE, 8); mbar_init(sb + B_KVREADY, 1);
        mbar_init(sb + B_ODONE, 8); mbar_init(sb + B_WOFULL, 1); mbar_init(sb + B_HSUM, 3);
        mbar_init(sb + B_PREADY, 1); mbar_init(sb + B_SF, 1); mbar_init(sb + B_SF + 8, 1);
        for (int s = 0; s < 4; s++) mbar_init(sb + B_SQ + 8 * s, 8);
        asm volatile("st.shared.u32 [%0], %1;" :: "r"(sb + ITEM_OFF), "r"(0) : "memory");
        fence_async_smem();
    }
    if (!dry) __syncthreads();

    if (warp >= 8) {
        asm volatile("setmaxnreg.dec.sync.aligned.u32 88;");
        if (warp == 8) {
            Ring r{0, 1};
            const bool leader = elect_one();
#pragma unroll
            for (int n = 0; n < N_QKV; n++) {
                const uint32_t full = sb + B_FULL + 8 * r.slot, dst = sb + RING_OFF + r.slot * SLOT;
                if (n > 0) {
                    if (!(n & 1) && leader) {
                        mbar_expect_tx(sb + B_XFULL + 8 * (n >> 1), 16384);
                        tma_2d(sb + X_OFF + (n >> 1) * 16384, &map_x, sb + B_XFULL + 8 * (n >> 1), (n >> 1) * 64, ti * 128);
                    }
                    if (n >= RING) PWAIT();
                    if (leader) {
                        mbar_expect_only(full, 12288);
                        tma_4d(dst, &map_qkv, full, 0, 32 * n, tj, 0);
                    }
                }
                const uint32_t gv = (n & 1) ? (gwv[n >> 1] >> 16) : (gwv[n >> 1] & 0xFFFFu);
                asm volatile("st.shared.v4.b32 [%0], {%1, %2, %2, %2};" :: "r"(dst + 12288 + lane * 128 + ((lane & 7) << 4)), "r"(gv), "r"(0) : "memory");
                fence_async_smem();
                __syncwarp();
                if (leader) mbar_arrive(full);
                r.next();
            }
#pragma unroll 1
            for (int n = 0; n < N_FFN1; n++) {
                const uint32_t full = sb + B_FULL + 8 * r.slot, dst = sb + RING_OFF + r.slot * SLOT;
                PWAIT();
                if (leader) {
                    mbar_expect_tx(full, 16384);
                    tma_4d(dst, &map_w1a, full, 0, 32 * n, 0, tj);
                    tma_2d(dst + 3 * 4096, &map_w1, full, 224 * tj + 192, 32 * n);
                }
                r.next();
            }
            {
                int q = 0, rr = 0;
#pragma unroll 1
                for (int n = 0; n < N_FFN2; n++) {
                    const uint32_t full = sb + B_FULL + 8 * r.slot, dst = sb + RING_OFF + r.slot * SLOT;
                    PWAIT();
                    if (leader) mbar_expect_tx(full, 16384);
#pragma unroll
                    for (int h = 0; h < 2; h++) {
                        if (leader) tma_3d(dst + h * 8192, &map_w2, full, 0, 224 * tj + 32 * rr, 2 * q);
                        if (++rr == 7) { rr = 0; q++; }
                    }
                    r.next();
                }
            }
            mbar_wait(sb + B_KVREADY, 0);
            asm volatile("fence.proxy.async.global;" ::: "memory");
            {
                const int bbase = 8 * ti - 16, b0 = bbase < 0 ? 0 : bbase;
                const uint32_t bytes = (uint32_t)(8 * ti + 8 - b0) * 512;
#pragma unroll 1
                for (int m = 0; m < N_KV; m++) {
                    const uint32_t full = sb + B_FULL + 8 * r.slot, dst = sb + RING_OFF + r.slot * SLOT;
                    if (m == RING) {
                        mbar_wait(sb + B_HDEAD, 0);
                        if (leader) {
                            mbar_expect_tx(sb + B_WOFULL, 65536);
#pragma unroll
                            for (int e = 0; e < 2; e++) tma_2d(sb + X_OFF + e * 32768, &map_wo, sb + B_WOFULL, 64 * tj, 256 * e);
                        }
                    }
                    PWAIT();
                    if (bbase < 0) {
                        for (int z = lane; z < -bbase * 32; z += 32) sts128(dst + z * 16, make_uint4(0u, 0u, 0u, 0u));
                        fence_async_smem();
                        __syncwarp();
                    }
                    if (leader) {
                        const uint4* src = ((m & 1) ? g_vf : g_kf) + ((tj * 4 + (m >> 1)) * 128 + b0) * 32;
                        mbar_expect_tx(full, bytes);
                        bulk_g2s(dst + (b0 - bbase) * 512, src, bytes, full);
                    }
                    r.next();
                }
            }
            {
                mbar_wait(sb + B_EREADY, 0);
                unsigned epoch; asm volatile("ld.shared.u32 %0, [%1];" : "=r"(epoch) : "r"(sb + EPOCH_OFF) : "memory");
                uint32_t pending = 0xFFu & ~(1u << tj), ready = 0;
                mbar_wait(sb + B_HSUM, 0);
#pragma unroll 1
                for (int m = 0; m < N_O; m++) {
                    const uint32_t full = sb + B_FULL + 8 * r.slot, dst = sb + RING_OFF + r.slot * SLOT;
                    PWAIT();
                    for (int it = 0; it < (1 << 20) && !ready; it++) {
                        bool ok = false;
                        if (lane < 8 && ((pending >> lane) & 1)) ok = (int)(ld_acquire(&g_ocnt[(ti * 8 + lane) * 32]) - (epoch + 1)) >= 0;
                        ready = __ballot_sync(0xffffffffu, ok);
                        if (!ready) __nanosleep(100);
                    }
                    const int js = ready ? __ffs(ready) - 1 : __ffs(pending) - 1;
                    pending &= ~(1u << js); ready &= ~(1u << js);
                    asm volatile("fence.proxy.async.global;" ::: "memory");
                    if (leader) {
                        asm volatile("st.shared.u32 [%0], %1;" :: "r"(sb + OSRC_OFF + 4 * m), "r"(js) : "memory");
                        mbar_expect_tx(full, 16384);
                        tma_2d(dst, &map_o, full, 64 * js, ti * 128);
                    }
                    r.next();
                }
            }
        } else if (warp == 9) {
            unsigned epoch = 0;
            if (lane == 0) {
                epoch = atomicAdd(&g_ticket, 1u) >> 7;
                asm volatile("st.shared.u32 [%0], %1;" :: "r"(sb + EPOCH_OFF), "r"(epoch) : "memory");
                mbar_arrive(sb + B_EREADY);
                mbar_wait(sb + B_XFULL + 8 * PF1_AT, 0);
                prefetch_l2(w1p + (size_t)blockIdx.x * 14336, 14336);
                mbar_wait(sb + B_XFULL + 8 * PF2_AT, 0);
                prefetch_l2(w2p + (size_t)blockIdx.x * 14336, 14336);
                prefetch_l2(wop + (size_t)blockIdx.x * 4096, 4096);
                mbar_wait(sb + B_KVDONE, 0);
                red_release(&g_kvcnt[blockIdx.x * 32], 1u);
            }
            epoch = __shfl_sync(0xffffffffu, epoch, 0);
            if (lane < 3 && ti - lane >= 0) wait_counter(&g_kvcnt[((ti - lane) * 8 + tj) * 32], epoch + 1);
            __syncwarp();
            if (lane == 0) mbar_arrive(sb + B_KVREADY);
            mbar_wait(sb + B_SQ + 24, 0);
            if (lane < 8) wait_counter(&g_pcnt[(ti * 8 + lane) * 32], epoch + 1);
            __syncwarp();
            if (lane == 0) { mbar_arrive(sb + B_PREADY); TSX(13); }
            sum_partials(sb, ti, tj, lane);
            if (lane == 0) TSX(14);
        } else {
            if (warp == 10) {
#pragma unroll 1
                for (int q = 0; q < 4; q++) {
                    mbar_wait(sb + B_SQ + 8 * q, 0);
                    if (lane < 16) {
                        uint4* d = g_part + (size_t)(((ti * 8 + 2 * q + (lane & 1)) * 8 + tj) * 8 + (lane >> 1)) * 128;
                        bulk_s2g(d, sb + STG_OFF + (q & 1) * 32768 + lane * 2048, 2048);
                        asm volatile("cp.async.bulk.commit_group;" ::: "memory");
                        asm volatile("cp.async.bulk.wait_group.read 0;" ::: "memory");
                    }
                    __syncwarp();
                    if (lane == 0) mbar_arrive(sb + B_SF + 8 * (q & 1));
                }
                asm volatile("cp.async.bulk.wait_group 0;" ::: "memory");
                asm volatile("fence.proxy.async.global;" ::: "memory");
                __syncwarp();
                if (lane == 0) { red_release(&g_pcnt[blockIdx.x * 32], 1u); TSX(12); }
            }
            mbar_wait(sb + B_PREADY, 0);
            sum_partials(sb, ti, tj, lane);
            if (warp == 11 && lane == 0) {
                mbar_wait(sb + B_ODONE, 0);
                red_release(&g_ocnt[blockIdx.x * 32], 1u);
            }
        }
    } else {
        asm volatile("setmaxnreg.inc.sync.aligned.u32 208;");
        const int wg = warp >> 2, g = lane >> 2, c = lane & 3;
        const uint32_t xa = sb + X_OFF + wg * 8192;
        Ring r{0, 0};
        const bool lane0 = lane == 0 && !dry;
        uint32_t qf[4][4];
        float g0, g1;
        TS(9);
        {
            float acc[100];
            int prev = 0;
            if (wg == 1) asm volatile("bar.sync 3, 256;" ::: "memory");
            for (int s = 0; s < (dry ? 4 : N_QKV); s++) {
                if (!(s & 1) && !dry) mbar_wait(sb + B_XFULL + 8 * (s >> 1), 0);
                CWAIT();
                if (s == 0) TS(1);
                if (s == 2) TS(28);
                if (s == 6) TS(29);
                if (s == 10) TS(20);
                const uint32_t bs = sb + RING_OFF + r.slot * SLOT, as = xa + (s >> 1) * 16384 + (s & 1) * 64;
                wgmma_fence();
                wgmma_ss_n200(acc, desc_a(as), desc_b(bs), s);
                wgmma_ss_n200(acc, desc_a(as + 32), desc_b(bs + 2048), 1);
                wgmma_commit();
                if (wg == 0 && s == LEAD1) asm volatile("bar.arrive 3, 256;" ::: "memory");
                if (s > 0) { wgmma_wait<1>(); if (lane0) mbar_arrive(sb + B_EMPTY + 8 * prev); }
                prev = r.slot; r.next();
            }
            wgmma_wait<0>();
            fence_acc(acc);
            if (lane0) mbar_arrive(sb + B_EMPTY + 8 * prev);
            TS(2);
            const int blk = ti * 8 + warp;
#pragma unroll
            for (int hh = 0; hh < 4; hh++) {
                const float* t0 = &acc[8 * hh]; const float* t1 = &acc[8 * hh + 4];
                qf[hh][0] = pack_bf16(t0[0], t0[1]); qf[hh][1] = pack_bf16(t0[2], t0[3]);
                qf[hh][2] = pack_bf16(t1[0], t1[1]); qf[hh][3] = pack_bf16(t1[2], t1[3]);
#pragma unroll
                for (int mtx = 0; mtx < 2; mtx++) {
                    const float* t = &acc[32 + 32 * mtx + 8 * hh];
                    uint32_t r0 = pack_bf16(t[0], t[1]), r1 = pack_bf16(t[4], t[5]), r2 = pack_bf16(t[2], t[3]), r3 = pack_bf16(t[6], t[7]);
                    {
                        const bool hi = c & 1;
                        const uint32_t s0 = __shfl_xor_sync(0xffffffffu, hi ? r0 : r1, 1), s1 = __shfl_xor_sync(0xffffffffu, hi ? r2 : r3, 1);
                        if (hi) { r0 = s0; r2 = s1; } else { r1 = s0; r3 = s1; }
                    }
                    {
                        const bool hi = c & 2;
                        const uint32_t s0 = __shfl_xor_sync(0xffffffffu, hi ? r0 : r2, 2), s1 = __shfl_xor_sync(0xffffffffu, hi ? r1 : r3, 2);
                        if (hi) { r0 = s0; r1 = s1; } else { r2 = s0; r3 = s1; }
                    }
                    const int row = g + 8 * (c >> 1);
                    uint4* dst = (mtx ? g_vf : g_kf) + ((tj * 4 + hh) * 128 + blk) * 32 + row * 2 + ((c & 1) ^ ((row >> 2) & 1));
                    if (!dry) *dst = make_uint4(r0, r1, r2, r3);
                }
            }
            __syncwarp();
            if (lane0) mbar_arrive(sb + B_KVDONE);
            const float z0 = __shfl_sync(0xffffffffu, acc[96], lane & ~3), z1 = __shfl_sync(0xffffffffu, acc[98], lane & ~3);
            g0 = 1.f / (1.f + __expf(-z0)); g1 = 1.f / (1.f + __expf(-z1));
        }
        TS(3);
        const int wrow = (warp & 3) * 16;
        {
            float acc[112];
            int prev = 0;
            for (int s = 0; s < (dry ? 4 : N_FFN1); s++) {
                CWAIT();
                const uint32_t bs = sb + RING_OFF + r.slot * SLOT, as = xa + (s >> 1) * 16384 + (s & 1) * 64;
                wgmma_fence();
                wgmma_ss_n224(acc, desc_a(as), desc_b(bs), s);
                wgmma_ss_n224(acc, desc_a(as + 32), desc_b(bs + 2048), 1);
                wgmma_commit();
                if (s > 0) { wgmma_wait<1>(); if (lane0) mbar_arrive(sb + B_EMPTY + 8 * prev); }
                prev = r.slot; r.next();
            }
            wgmma_wait<0>();
            fence_acc(acc);
            if (lane0) mbar_arrive(sb + B_EMPTY + 8 * prev);
            TS(4);
            const float s0 = 1.f - g0, s1 = 1.f - g1;
            asm volatile("bar.sync %0, 128;" :: "r"(1 + wg) : "memory");
            const uint32_t strow = xa + (wrow + ((lane >> 3) & 1) * 8 + (lane & 7)) * 128;
#pragma unroll
            for (int p = 0; p < 14; p++) {
                const int nt = 2 * p + (lane >> 4);
                const float* a = &acc[8 * p];
                stmatrix_x4(strow + (p >> 2) * 16384 + (((nt & 7) ^ (lane & 7)) << 4),
                            pack_bf16_relu(a[0] * s0, a[1] * s0), pack_bf16_relu(a[2] * s1, a[3] * s1),
                            pack_bf16_relu(a[4] * s0, a[5] * s0), pack_bf16_relu(a[6] * s1, a[7] * s1));
            }
        }
        TS(5);
        {
            fence_async_smem();
            asm volatile("bar.sync 4, 256;" ::: "memory");
            float accA[64], accB[64];
            auto epilogue = [&](float (&acc)[64], int q) {
                fence_acc(acc);
                const uint32_t st = sb + STG_OFF + (q & 1) * 32768 + warp * 4096;
                if (q >= 2 && !dry) mbar_wait(sb + B_SF + 8 * (q & 1), 0);
#pragma unroll
                for (int t2 = 0; t2 < 8; t2++) {
                    uint4 v;
                    v.x = pack_bf16(acc[8 * t2 + 0], acc[8 * t2 + 1]); v.y = pack_bf16(acc[8 * t2 + 2], acc[8 * t2 + 3]);
                    v.z = pack_bf16(acc[8 * t2 + 4], acc[8 * t2 + 5]); v.w = pack_bf16(acc[8 * t2 + 6], acc[8 * t2 + 7]);
                    sts128(st + t2 * 512 + lane * 16, v);
                }
                fence_async_smem();
                __syncwarp();
                if (lane0) mbar_arrive(sb + B_SQ + 8 * q);
            };
            int rel = r.slot;
#pragma unroll
            for (int m = 0; m < N_FFN2; m++) {
                CWAIT();
                wgmma_fence();
#pragma unroll
                for (int h = 0; h < 2; h++) {
                    const int u = 2 * m + h, q = u / 7, rr = u % 7;
                    const uint32_t bs = sb + RING_OFF + r.slot * SLOT + h * 8192;
                    const uint32_t as = xa + (rr >> 1) * 16384 + (rr & 1) * 64;
                    if (!(q & 1)) {
                        wgmma_ss_n128(accA, desc_a(as), desc_b(bs), rr);
                        wgmma_ss_n128(accA, desc_a(as + 32), desc_b(bs + 2048), 1);
                    } else {
                        wgmma_ss_n128(accB, desc_a(as), desc_b(bs), rr);
                        wgmma_ss_n128(accB, desc_a(as + 32), desc_b(bs + 2048), 1);
                    }
                }
                wgmma_commit();
                r.next();
                wgmma_wait<1>();
                if (m > 0) {
                    if (lane0) mbar_arrive(sb + B_EMPTY + 8 * rel);
                    if (++rel == RING) rel = 0;
                }
                if (m == 4) { TS(25); epilogue(accA, 0); }
                if (m == 7) { TS(26); epilogue(accB, 1); }
                if (m == 11) { TS(27); epilogue(accA, 2); }
            }
            wgmma_wait<0>();
            if (lane0) { mbar_arrive(sb + B_EMPTY + 8 * rel); mbar_arrive(sb + B_HDEAD); }
            epilogue(accB, 3);
        }
        TS(6);
        {
            const float SC = 0.25f * 1.4426950408889634f;
            const int gb0 = 8 * ti - 16 + 4 * wg;
            int slotK = 0, slotV = 0;
            const uint32_t ostore = sb + OWN_OFF + (warp * 16 + ((lane >> 3) & 1) * 8 + (lane & 7)) * 128;
            uint32_t* odst = reinterpret_cast<uint32_t*>(g_o + (size_t)(ti * 128 + warp * 16 + g) * 512 + tj * 64 + ((lane & 1) ? 8 : 0) + (lane & 2) * 2);
#define NHEADS (dry ? 2 : 4)
#define ATT_KWAIT(kb) do { slotK = r.slot; CWAIT(); kb = sb + RING_OFF + slotK * SLOT + wg * 2048; r.next(); } while (0)
#define ATT_VWAIT(vb) do { slotV = r.slot; CWAIT(); vb = sb + RING_OFF + slotV * SLOT + wg * 2048; r.next(); TS(21 + hh); } while (0)
#define ATT_KREL() do { __syncwarp(); if (lane0) mbar_arrive(sb + B_EMPTY + 8 * slotK); } while (0)
#define ATT_VREL() do { __syncwarp(); if (lane0) mbar_arrive(sb + B_EMPTY + 8 * slotV); } while (0)
#define ATT_NEXTQ(h) do { \
                if ((h) == 1) { q0 = qf[1][0]; q1 = qf[1][1]; q2 = qf[1][2]; q3 = qf[1][3]; } \
                else if ((h) == 2) { q0 = qf[2][0]; q1 = qf[2][1]; q2 = qf[2][2]; q3 = qf[2][3]; } \
                else { q0 = qf[3][0]; q1 = qf[3][1]; q2 = qf[3][2]; q3 = qf[3][3]; } } while (0)
#define ATT_STORE(h, r0, r1, r2, r3) do { \
                if ((h) == 0 && !dry) mbar_wait(sb + B_SF, 1);        \
                stmatrix_x4(ostore + (((2 * (h) + (lane >> 4)) ^ (lane & 7)) << 4), r0, r1, r2, r3); \
                const bool odd = lane & 1; \
                const uint32_t sl = __shfl_xor_sync(0xffffffffu, odd ? (r0) : (r2), 1), sh = __shfl_xor_sync(0xffffffffu, odd ? (r1) : (r3), 1); \
                if (!dry) *reinterpret_cast<uint2*>(odst + 8 * (h)) = odd ? make_uint2(sl, r2) : make_uint2(r0, sl); \
                if (!dry) *reinterpret_cast<uint2*>(odst + 8 * (h) + 8 * 256) = odd ? make_uint2(sh, r3) : make_uint2(r1, sh); \
                } while (0)
            const float NEG = -INFINITY;
            const int ww = warp & 3;
            uint32_t tri = 0;
#pragma unroll
            for (int e = 0; e < 8; e++) tri |= (uint32_t)((8 * (e >> 2) + 2 * c + (e & 1)) > (g + 8 * ((e >> 1) & 1))) << e;
            uint32_t q0 = qf[0][0], q1 = qf[0][1], q2 = qf[0][2], q3 = qf[0][3];
            auto rowmax = [&](const float (&s)[64], const uint32_t (&dead)[8], float b0, float b1, float& n0, float& n1) {
                int i0 = __float_as_int(b0), i1 = __float_as_int(b1);
#pragma unroll
                for (int t = 0; t < 16; t++) {
                    i0 = __vimax3_s32(i0, __float_as_int(s[4 * t]), __float_as_int(s[4 * t + 1]));
                    i1 = __vimax3_s32(i1, __float_as_int(s[4 * t + 2]), __float_as_int(s[4 * t + 3]));
                }
                i0 = max(i0, __shfl_xor_sync(0xffffffffu, i0, 1)); i1 = max(i1, __shfl_xor_sync(0xffffffffu, i1, 1));
                i0 = max(i0, __shfl_xor_sync(0xffffffffu, i0, 2)); i1 = max(i1, __shfl_xor_sync(0xffffffffu, i1, 2));
                n0 = __int_as_float(i0); n1 = __int_as_float(i1);
                if (__any_sync(0xffffffffu, i0 <= 0 || i1 <= 0)) {
                    asm volatile("" ::: "memory");
                    n0 = b0; n1 = b1;
#pragma unroll
                    for (int t = 0; t < 16; t++) {
                        const uint32_t dd = dead[t >> 1] >> (4 * (t & 1));
                        n0 = fmaxf(n0, fmaxf((dd & 1u) ? NEG : s[4 * t], (dd & 2u) ? NEG : s[4 * t + 1]));
                        n1 = fmaxf(n1, fmaxf((dd & 4u) ? NEG : s[4 * t + 2], (dd & 8u) ? NEG : s[4 * t + 3]));
                    }
                    n0 = fmaxf(n0, __shfl_xor_sync(0xffffffffu, n0, 1)); n1 = fmaxf(n1, __shfl_xor_sync(0xffffffffu, n1, 1));
                    n0 = fmaxf(n0, __shfl_xor_sync(0xffffffffu, n0, 2)); n1 = fmaxf(n1, __shfl_xor_sync(0xffffffffu, n1, 2));
                }
            };
            auto expp = [&](const float (&s)[64], const uint32_t (&dead)[8], uint32_t (&p)[32], const int nmixed, float mr0, float mr1, float& l0, float& l1) {
#pragma unroll
                for (int t = 0; t < 16; t++) {
                    const uint32_t dd = dead[t >> 1] >> (4 * (t & 1));
                    const bool db = dead[t >> 1] != 0u;
                    const float k0 = (t < nmixed ? (dd & 1u) != 0u : db) ? NEG : -mr0, k1 = (t < nmixed ? (dd & 2u) != 0u : db) ? NEG : -mr0;
                    const float k2 = (t < nmixed ? (dd & 4u) != 0u : db) ? NEG : -mr1, k3 = (t < nmixed ? (dd & 8u) != 0u : db) ? NEG : -mr1;
                    const float e0 = ex2(fmaf(s[4 * t], SC, k0)), e1 = ex2(fmaf(s[4 * t + 1], SC, k1));
                    const float e2 = ex2(fmaf(s[4 * t + 2], SC, k2)), e3 = ex2(fmaf(s[4 * t + 3], SC, k3));
                    l0 += e0 + e1; l1 += e2 + e3;
                    p[2 * t] = pack_bf16(e0, e1); p[2 * t + 1] = pack_bf16(e2, e3);
                }
            };
            uint32_t deadA[8], deadB[8];
#pragma unroll
            for (int j = 0; j < 8; j++) {
                const uint32_t mk = j >= 4 || j > ww ? 0xFFu : (j < ww ? 0u : tri);
                deadA[j] = gb0 + j < 0 ? mk : 0u;
                deadB[j] = gb0 + 8 + j < 0 ? 0xFFu : 0u;
            }
            uint32_t kbase = 0, vbase = 0;
#pragma unroll 1
            for (int hh = 0; hh < NHEADS; hh++) {
                ATT_KWAIT(kbase);
                if (hh > 0) ATT_NEXTQ(hh);
                float sa[64], oa[8], ob[8];
                uint32_t pa[32], pd[16];
                float m0, m1, la0 = 0.f, la1 = 0.f;
                {
                    float sd[32];
                    wgmma_fence();
                    wgmma_rk_n128(sa, q0, q1, q2, q3, desc_kv(kbase), 0);
                    wgmma_rk_n64(sd, q0, q1, q2, q3, desc_kv(kbase + 16 * 512), 0);
                    wgmma_commit();
                    wgmma_wait<0>();
                    fence_acc(sa); fence_acc(sd);
#pragma unroll
                    for (int j = 0; j < 4; j++) {
                        const uint32_t mk = j > ww ? 0xFFu : (j < ww ? 0u : tri);
#pragma unroll
                        for (int e = 0; e < 8; e++) sa[8 * j + e] = ((mk >> e) & 1u) ? sa[8 * j + e] : sd[8 * j + e];
                    }
                }
                rowmax(sa, deadA, NEG, NEG, m0, m1);
                expp(sa, deadA, pa, 8, m0 * SC, m1 * SC, la0, la1);
#pragma unroll
                for (int j = 0; j < 4; j++) {
                    const uint32_t mk = j > ww ? 0xFFu : (j < ww ? 0u : tri);
#pragma unroll
                    for (int k = 0; k < 4; k++) {
                        const uint32_t mm = (((mk >> (2 * k)) & 1u) ? 0x0000FFFFu : 0u) | (((mk >> (2 * k + 1)) & 1u) ? 0xFFFF0000u : 0u);
                        pd[4 * j + k] = pa[4 * j + k] & ~mm;
                        pa[4 * j + k] &= mm;
                    }
                }
                ATT_VWAIT(vbase);
                fence_u32(pa); fence_u32(pd);
                wgmma_fence();
                wgmma_rk_n128(sa, q0, q1, q2, q3, desc_kv(kbase + 8 * 512), 0);
                wgmma_commit();
#pragma unroll
                for (int j = 0; j < 8; j++) wgmma_rs_n16(oa, pa[4 * j], pa[4 * j + 1], pa[4 * j + 2], pa[4 * j + 3], desc_kv(vbase + j * 512), j);
#pragma unroll
                for (int j = 0; j < 4; j++) wgmma_rs_n16(oa, pd[4 * j], pd[4 * j + 1], pd[4 * j + 2], pd[4 * j + 3], desc_kv(vbase + (16 + j) * 512), 1);
                wgmma_commit();
                wgmma_wait<1>();
                fence_acc(sa);
                ATT_KREL();
                float n0, n1, lb0 = 0.f, lb1 = 0.f;
                uint32_t pb[32];
                rowmax(sa, deadB, m0, m1, n0, n1);
                wgmma_wait<0>();
                fence_acc(oa);
                expp(sa, deadB, pb, 0, n0 * SC, n1 * SC, lb0, lb1);
                fence_u32(pb);
                wgmma_fence();
#pragma unroll
                for (int j = 0; j < 8; j++) wgmma_rs_n16(ob, pb[4 * j], pb[4 * j + 1], pb[4 * j + 2], pb[4 * j + 3], desc_kv(vbase + (8 + j) * 512), j);
                wgmma_commit();
                const float a0 = ex2((m0 - n0) * SC), a1 = ex2((m1 - n1) * SC);
                float l0 = fmaf(la0, a0, lb0), l1 = fmaf(la1, a1, lb1);
                l0 += __shfl_xor_sync(0xffffffffu, l0, 1); l1 += __shfl_xor_sync(0xffffffffu, l1, 1);
                l0 += __shfl_xor_sync(0xffffffffu, l0, 2); l1 += __shfl_xor_sync(0xffffffffu, l1, 2);
                const float f0 = __fdividef(g0, l0), f1 = __fdividef(g1, l1);
                wgmma_wait<0>();
                fence_acc(ob);
                ATT_VREL();
                ATT_STORE(hh, pack_bf16(fmaf(oa[0], a0, ob[0]) * f0, fmaf(oa[1], a0, ob[1]) * f0), pack_bf16(fmaf(oa[2], a1, ob[2]) * f1, fmaf(oa[3], a1, ob[3]) * f1),
                              pack_bf16(fmaf(oa[4], a0, ob[4]) * f0, fmaf(oa[5], a0, ob[5]) * f0), pack_bf16(fmaf(oa[6], a1, ob[6]) * f1, fmaf(oa[7], a1, ob[7]) * f1));
            }
            fence_async_smem();
            __syncwarp();
            if (lane0) mbar_arrive(sb + B_ODONE);
        }
        TS(7);
        {
            float acc[32];
            uint4 pv[4][4];
            if (!dry) mbar_wait(sb + B_PREADY, 0);
            {
                const uint4* p = g_part + (size_t)((ti * 8 + tj) * 8 + 4) * 1024 + warp * 128 + lane;
#pragma unroll
                for (int s = 0; s < 4; s++)
#pragma unroll
                    for (int n = 0; n < 4; n++) pv[n][s] = dry ? make_uint4(0u, 0u, 0u, 0u) : ldg_weak(p + s * 1024 + n * 32);
            }
            if (!dry) mbar_wait(sb + B_WOFULL, 0);
            if (!dry) mbar_wait(sb + B_ODONE, 0);
            TS(15);
            wgmma_fence();
#pragma unroll
            for (int k = 0; k < 4; k++) wgmma_ss_n64(acc, desc_a(sb + OWN_OFF + wg * 8192 + 32 * k), desc_b(sb + X_OFF + tj * 8192 + 2048 * k), k);
            wgmma_commit();
            TS(16);
#pragma unroll 1
            for (int m = 0; m < N_O; m++) {
                CWAIT();
                uint32_t js; asm volatile("ld.shared.u32 %0, [%1];" : "=r"(js) : "r"(sb + OSRC_OFF + 4 * m) : "memory");
                const uint32_t as = sb + RING_OFF + r.slot * SLOT + wg * 8192;
                const uint32_t bs = sb + X_OFF + (js & 7) * 8192;
                wgmma_fence();
#pragma unroll
                for (int k = 0; k < 4; k++) wgmma_ss_n64(acc, desc_a(as + 32 * k), desc_b(bs + 2048 * k), 1);
                wgmma_commit();
                if (m == 0) { wgmma_wait<0>(); if (lane0) mbar_arrive(sb + B_EMPTY + 8 * r.slot); }
                r.next();
            }
            float base[32];
            if (!dry) mbar_wait(sb + B_HSUM, 0);
#pragma unroll
            for (int n = 0; n < 4; n++) {
                const uint4 u0 = lds128(sb + HSUM_OFF + (warp * 8 + 2 * n) * 512 + lane * 16), u1 = lds128(sb + HSUM_OFF + (warp * 8 + 2 * n + 1) * 512 + lane * 16);
                float* a = &base[8 * n];
                a[0] = __uint_as_float(u0.x); a[1] = __uint_as_float(u0.y); a[2] = __uint_as_float(u0.z); a[3] = __uint_as_float(u0.w);
                a[4] = __uint_as_float(u1.x); a[5] = __uint_as_float(u1.y); a[6] = __uint_as_float(u1.z); a[7] = __uint_as_float(u1.w);
#pragma unroll
                for (int s = 0; s < 4; s++) {
                    a[0] += bf_lo(pv[n][s].x); a[1] += bf_hi(pv[n][s].x); a[2] += bf_lo(pv[n][s].y); a[3] += bf_hi(pv[n][s].y);
                    a[4] += bf_lo(pv[n][s].z); a[5] += bf_hi(pv[n][s].z); a[6] += bf_lo(pv[n][s].w); a[7] += bf_hi(pv[n][s].w);
                }
            }
            fence_acc(base);
            wgmma_wait<0>();
            fence_acc(acc);
            TS(17);
#pragma unroll
            for (int k = 0; k < 32; k++) acc[k] += base[k];
            __nv_bfloat16* o = out + (size_t)(ti * 128 + warp * 16 + g) * 512 + tj * 64 + ((lane & 1) ? 8 : 0) + (lane & 2) * 2;
            const bool odd = lane & 1;
#pragma unroll
            for (int t2 = 0; t2 < 4; t2++) {
                const uint32_t lo0 = pack_bf16(acc[8 * t2 + 0], acc[8 * t2 + 1]), hi0 = pack_bf16(acc[8 * t2 + 2], acc[8 * t2 + 3]);
                const uint32_t lo1 = pack_bf16(acc[8 * t2 + 4], acc[8 * t2 + 5]), hi1 = pack_bf16(acc[8 * t2 + 6], acc[8 * t2 + 7]);
                const uint32_t sl = __shfl_xor_sync(0xffffffffu, odd ? lo0 : lo1, 1), sh = __shfl_xor_sync(0xffffffffu, odd ? hi0 : hi1, 1);
                if (!dry) *reinterpret_cast<uint2*>(o + 16 * t2) = odd ? make_uint2(sl, lo1) : make_uint2(lo0, sl);
                if (!dry) *reinterpret_cast<uint2*>(o + 16 * t2 + 8 * 512) = odd ? make_uint2(sh, hi1) : make_uint2(hi0, sh);
            }
            if (tid == 0 && !dry) TSG(30);
        }
        TS(8);
    }
}

typedef CUresult (*PFN_encodeTiled)(CUtensorMap*, CUtensorMapDataType, cuuint32_t, void*, const cuuint64_t*, const cuuint64_t*,
                                    const cuuint32_t*, const cuuint32_t*, CUtensorMapInterleave, CUtensorMapSwizzle,
                                    CUtensorMapL2promotion, CUtensorMapFloatOOBfill);

void make_map(PFN_encodeTiled enc, CUtensorMap* m, const void* base, int rank, const cuuint64_t* dims, const cuuint64_t* strides, const cuuint32_t* box) {
    cuuint32_t es[5] = {1, 1, 1, 1, 1};
    enc(m, CU_TENSOR_MAP_DATA_TYPE_BFLOAT16, (cuuint32_t)rank, const_cast<void*>(base), dims, strides, box, es,
        CU_TENSOR_MAP_INTERLEAVE_NONE, CU_TENSOR_MAP_SWIZZLE_128B, CU_TENSOR_MAP_L2_PROMOTION_L2_256B, CU_TENSOR_MAP_FLOAT_OOB_FILL_NONE);
}

}

extern "C" void kernel_launch(void* const* d_in, const int* in_sizes, int n_in, void* d_out, int out_size) {
    (void)in_sizes; (void)n_in; (void)out_size;
    const void* x = d_in[0]; const void* wqkv = d_in[1]; const void* wo = d_in[2];
    const void* w1 = d_in[4]; const void* w2 = d_in[5]; const void* gate_w = d_in[6];
    static PFN_encodeTiled enc = nullptr;
    if (!enc) {
        void* fn = nullptr; cudaDriverEntryPointQueryResult st;
        cudaGetDriverEntryPoint("cuTensorMapEncodeTiled", &fn, cudaEnableDefault, &st);
        enc = (PFN_encodeTiled)fn;
        cudaFuncSetAttribute(fused_kernel, cudaFuncAttributeMaxDynamicSharedMemorySize, SMEM_BYTES);
    }
    CUtensorMap mx, mqkv, mw1, mw2, mwo, mw1a, mo;
    void* optr = nullptr;
    cudaGetSymbolAddress(&optr, g_o);
    { cuuint64_t d[2] = {512, 2048}, s[1] = {1024}; cuuint32_t b[2] = {64, 128}; make_map(enc, &mo, optr, 2, d, s, b); }
    { cuuint64_t d[4] = {64, 512, 3, 8}, s[3] = {3584, 128, 448}; cuuint32_t b[4] = {64, 32, 3, 1}; make_map(enc, &mw1a, w1, 4, d, s, b); }
    { cuuint64_t d[2] = {512, 2048}, s[1] = {1024}; cuuint32_t b[2] = {64, 128}; make_map(enc, &mx, x, 2, d, s, b); }
    { cuuint64_t d[4] = {64, 512, 8, 3}, s[3] = {3072, 128, 1024}; cuuint32_t b[4] = {64, 32, 1, 3}; make_map(enc, &mqkv, wqkv, 4, d, s, b); }
    { cuuint64_t d[2] = {1792, 512}, s[1] = {3584}; cuuint32_t b[2] = {64, 32}; make_map(enc, &mw1, w1, 2, d, s, b); }
    { cuuint64_t d[3] = {64, 1792, 8}, s[2] = {1024, 128}; cuuint32_t b[3] = {64, 32, 2}; make_map(enc, &mw2, w2, 3, d, s, b); }
    { cuuint64_t d[2] = {512, 512}, s[1] = {1024}; cuuint32_t b[2] = {64, 256}; make_map(enc, &mwo, wo, 2, d, s, b); }
    fused_kernel<<<NCTA, 384, SMEM_BYTES, cudaStreamPerThread>>>(mx, mqkv, mw1, mw2, mwo, mw1a, mo, (const __nv_bfloat16*)gate_w, (__nv_bfloat16*)d_out,
                                           (const uint8_t*)w1, (const uint8_t*)w2, (const uint8_t*)wo);
}
```

```cpp
#include <cuda_runtime.h>
#include <cuda_bf16.h>
#include <cuda.h>
#include <stdint.h>

namespace {

#define PF1_AT 1
#define PF2_AT 5
#define LEAD1 2
#define NCTA 132
constexpr int RING = 6;
constexpr int SLOT = 16384;
constexpr uint32_t X_OFF = 0;
constexpr uint32_t STG_OFF = X_OFF + 4 * 16384;
constexpr uint32_t RING_OFF = 131072;
constexpr uint32_t BAR_OFF = RING_OFF + RING * SLOT;
constexpr uint32_t B_FULL = BAR_OFF, B_EMPTY = BAR_OFF + 64, B_XFULL = BAR_OFF + 128, B_HDEAD = BAR_OFF + 192,
                   B_EREADY = BAR_OFF + 200, B_KVDONE = BAR_OFF + 208, B_ODONE = BAR_OFF + 224,
                   B_KVREADY = BAR_OFF + 232, B_WOFULL = BAR_OFF + 240, B_HSUM = BAR_OFF + 248, B_PREADY = BAR_OFF + 264,
                   B_SQ = BAR_OFF + 272, B_SF = BAR_OFF + 304;
constexpr uint32_t EPOCH_OFF = BAR_OFF + 256, ITEM_OFF = BAR_OFF + 260, OSRC_OFF = BAR_OFF + 384;
constexpr uint32_t OWN_OFF = X_OFF + 4 * 16384;
constexpr uint32_t HSUM_OFF = X_OFF + 6 * 16384;
constexpr uint32_t SMEM_BYTES = BAR_OFF + 1024;

constexpr int N_QKV = 16, N_FFN1 = 16, N_FFN2 = 14, N_KV = 8, N_O = 7;

__device__ uint4 g_kf[32 * 128 * 32];
__device__ uint4 g_vf[32 * 128 * 32];
__device__ uint4 g_part[16 * 8 * 8 * 8 * 4 * 32];
__device__ __nv_bfloat16 g_o[2048 * 512];
__device__ unsigned g_ticket;
__device__ unsigned g_kvcnt[128 * 32];
__device__ unsigned g_pcnt[128 * 32];
__device__ unsigned g_ocnt[128 * 32];
#define TS(k) do {} while (0)
#define TS2(k) do {} while (0)
#define TS2X(k) do {} while (0)
#define TSX(k) do {} while (0)
#define TSG(k) do {} while (0)

__device__ __forceinline__ uint32_t smem_u32(const void* p) { return (uint32_t)__cvta_generic_to_shared(p); }
__device__ __forceinline__ void mbar_init(uint32_t bar, uint32_t cnt) { asm volatile("mbarrier.init.shared::cta.b64 [%0], %1;" :: "r"(bar), "r"(cnt) : "memory"); }
__device__ __forceinline__ void mbar_expect_tx(uint32_t bar, uint32_t bytes) { asm volatile("mbarrier.arrive.expect_tx.shared::cta.b64 _, [%0], %1;" :: "r"(bar), "r"(bytes) : "memory"); }
__device__ __forceinline__ void mbar_expect_only(uint32_t bar, uint32_t bytes) { asm volatile("mbarrier.expect_tx.relaxed.cta.shared::cta.b64 [%0], %1;" :: "r"(bar), "r"(bytes) : "memory"); }
__device__ __forceinline__ void mbar_arrive(uint32_t bar) { asm volatile("mbarrier.arrive.shared::cta.b64 _, [%0];" :: "r"(bar) : "memory"); }
__device__ __forceinline__ void mbar_wait(uint32_t bar, uint32_t parity) {
    asm volatile("{\n.reg .pred P1, P2;\n.reg .u32 n;\nmov.u32 n, 0;\n"
                 "WAIT_LOOP:\n"
                 "mbarrier.try_wait.parity.shared::cta.b64 P1, [%0], %1;\n"
                 "@P1 bra WAIT_DONE;\n"
                 "add.u32 n, n, 1;\n"
                 "setp.lt.u32 P2, n, 0x400000;\n"
                 "@P2 bra WAIT_LOOP;\n"
                 "WAIT_DONE:\n}" :: "r"(bar), "r"(parity) : "memory");
}
__device__ __forceinline__ void tma_2d(uint32_t dst, const void* map, uint32_t bar, int c0, int c1) {
    asm volatile("cp.async.bulk.tensor.2d.shared::cluster.global.mbarrier::complete_tx::bytes [%0], [%1, {%3, %4}], [%2];"
        :: "r"(dst), "l"(map), "r"(bar), "r"(c0), "r"(c1) : "memory");
}
__device__ __forceinline__ void tma_3d(uint32_t dst, const void* map, uint32_t bar, int c0, int c1, int c2) {
    asm volatile("cp.async.bulk.tensor.3d.shared::cluster.global.mbarrier::complete_tx::bytes [%0], [%1, {%3, %4, %5}], [%2];"
        :: "r"(dst), "l"(map), "r"(bar), "r"(c0), "r"(c1), "r"(c2) : "memory");
}
__device__ __forceinline__ void tma_4d(uint32_t dst, const void* map, uint32_t bar, int c0, int c1, int c2, int c3) {
    asm volatile("cp.async.bulk.tensor.4d.shared::cluster.global.mbarrier::complete_tx::bytes [%0], [%1, {%3, %4, %5, %6}], [%2];"
        :: "r"(dst), "l"(map), "r"(bar), "r"(c0), "r"(c1), "r"(c2), "r"(c3) : "memory");
}
__device__ __forceinline__ void bulk_g2s(uint32_t dst, const void* src, uint32_t bytes, uint32_t bar) {
    asm volatile("cp.async.bulk.shared::cluster.global.mbarrier::complete_tx::bytes [%0], [%1], %2, [%3];"
        :: "r"(dst), "l"(src), "r"(bytes), "r"(bar) : "memory");
}
__device__ __forceinline__ void prefetch_l2(const void* src, uint32_t bytes) {
    asm volatile("cp.async.bulk.prefetch.L2.global [%0], %1;" :: "l"(src), "r"(bytes) : "memory");
}
__device__ __forceinline__ bool elect_one() {
    uint32_t p;
    asm volatile("{\n.reg .pred P;\nelect.sync _|P, 0xffffffff;\nselp.u32 %0, 1, 0, P;\n}" : "=r"(p));
    return p != 0;
}
__device__ __forceinline__ void wgmma_fence() { asm volatile("wgmma.fence.sync.aligned;" ::: "memory"); }
__device__ __forceinline__ void wgmma_commit() { asm volatile("wgmma.commit_group.sync.aligned;" ::: "memory"); }
template <int N> __device__ __forceinline__ void wgmma_wait() { asm volatile("wgmma.wait_group.sync.aligned %0;" :: "n"(N) : "memory"); }
__device__ __forceinline__ void fence_async_smem() { asm volatile("fence.proxy.async.shared::cta;" ::: "memory"); }
__device__ __forceinline__ uint64_t desc_a(uint32_t addr) {
    return (uint64_t)((addr & 0x3FFFF) >> 4) | ((uint64_t)1 << 16) | ((uint64_t)(1024 >> 4) << 32) | ((uint64_t)1 << 62);
}
__device__ __forceinline__ uint64_t desc_b(uint32_t addr) {
    return (uint64_t)((addr & 0x3FFFF) >> 4) | ((uint64_t)(4096 >> 4) << 16) | ((uint64_t)(1024 >> 4) << 32) | ((uint64_t)1 << 62);
}
__device__ __forceinline__ uint64_t desc_kv(uint32_t addr) {
    return (uint64_t)((addr & 0x3FFFF) >> 4) | ((uint64_t)(256 >> 4) << 16) | ((uint64_t)(256 >> 4) << 32) | ((uint64_t)3 << 62);
}
__device__ __forceinline__ uint32_t pack_bf16(float lo, float hi) {
    uint32_t r; asm("cvt.rn.bf16x2.f32 %0, %1, %2;" : "=r"(r) : "f"(hi), "f"(lo)); return r;
}
__device__ __forceinline__ uint32_t pack_bf16_relu(float lo, float hi) {
    uint32_t r; asm("cvt.rn.relu.bf16x2.f32 %0, %1, %2;" : "=r"(r) : "f"(hi), "f"(lo)); return r;
}
__device__ __forceinline__ uint32_t movmatrix(uint32_t a) {
    uint32_t d; asm volatile("movmatrix.sync.aligned.m8n8.trans.b16 %0, %1;" : "=r"(d) : "r"(a)); return d;
}
__device__ __forceinline__ void stmatrix_x4(uint32_t addr, uint32_t r0, uint32_t r1, uint32_t r2, uint32_t r3) {
    asm volatile("stmatrix.sync.aligned.m8n8.x4.shared.b16 [%0], {%1, %2, %3, %4};" :: "r"(addr), "r"(r0), "r"(r1), "r"(r2), "r"(r3) : "memory");
}
__device__ __forceinline__ uint4 lds128(uint32_t addr) {
    uint4 v; asm volatile("ld.shared.v4.b32 {%0, %1, %2, %3}, [%4];" : "=r"(v.x), "=r"(v.y), "=r"(v.z), "=r"(v.w) : "r"(addr) : "memory"); return v;
}
__device__ __forceinline__ void mma16816(float (&c)[4], uint32_t a0, uint32_t a1, uint32_t a2, uint32_t a3, uint32_t b0, uint32_t b1) {
    asm volatile("mma.sync.aligned.m16n8k16.row.col.f32.bf16.bf16.f32 {%0,%1,%2,%3}, {%4,%5,%6,%7}, {%8,%9}, {%0,%1,%2,%3};"
        : "+f"(c[0]), "+f"(c[1]), "+f"(c[2]), "+f"(c[3]) : "r"(a0), "r"(a1), "r"(a2), "r"(a3), "r"(b0), "r"(b1));
}
__device__ __forceinline__ void mma16816_c(float (&c)[4], uint32_t a0, uint32_t a1, uint32_t a2, uint32_t a3, uint32_t b0, uint32_t b1, float ci) {
    asm volatile("mma.sync.aligned.m16n8k16.row.col.f32.bf16.bf16.f32 {%0,%1,%2,%3}, {%4,%5,%6,%7}, {%8,%9}, {%10,%10,%10,%10};"
        : "=f"(c[0]), "=f"(c[1]), "=f"(c[2]), "=f"(c[3]) : "r"(a0), "r"(a1), "r"(a2), "r"(a3), "r"(b0), "r"(b1), "f"(ci));
}
__device__ __forceinline__ int opaque(int v) { asm volatile("" : "+r"(v)); return v; }
__device__ __forceinline__ float ex2(float x) { float y; asm("ex2.approx.ftz.f32 %0, %1;" : "=f"(y) : "f"(x)); return y; }
__device__ __forceinline__ unsigned ld_acquire(const unsigned* p) {
    unsigned v; asm volatile("ld.acquire.gpu.global.u32 %0, [%1];" : "=r"(v) : "l"(p) : "memory"); return v;
}
__device__ __forceinline__ void red_release(unsigned* p, unsigned v) {
    asm volatile("red.release.gpu.global.add.u32 [%0], %1;" :: "l"(p), "r"(v) : "memory");
}
__device__ __forceinline__ void wait_counter(const unsigned* p, unsigned target) {
    uint32_t n = 0;
    while ((int)(ld_acquire(p) - target) < 0) { if (++n > (1u << 20)) break; }
}
__device__ __forceinline__ uint4 ldg_weak(const uint4* p) {
    uint4 v; asm volatile("ld.global.L1::no_allocate.v4.b32 {%0, %1, %2, %3}, [%4];" : "=r"(v.x), "=r"(v.y), "=r"(v.z), "=r"(v.w) : "l"(p) : "memory"); return v;
}
__device__ __forceinline__ float bf_lo(uint32_t v) { return __uint_as_float(v << 16); }
__device__ __forceinline__ float bf_hi(uint32_t v) { return __uint_as_float(v & 0xFFFF0000u); }

__device__ __forceinline__ void wgmma_ss_n64(float (&d)[32], uint64_t da, uint64_t db, int scale_d) {
    asm volatile("{\n.reg .pred p;\nsetp.ne.b32 p, %34, 0;\n"
        "wgmma.mma_async.sync.aligned.m64n64k16.f32.bf16.bf16 {%0, %1, %2, %3, %4, %5, %6, %7, %8, %9, %10, %11, %12, %13, %14, %15, %16, %17, %18, %19, %20, %21, %22, %23, %24, %25, %26, %27, %28, %29, %30, %31}, %32, %33, p, 1, 1, 0, 1;\n}\n"
        : "+f"(d[0]), "+f"(d[1]), "+f"(d[2]), "+f"(d[3]), "+f"(d[4]), "+f"(d[5]), "+f"(d[6]), "+f"(d[7]), "+f"(d[8]), "+f"(d[9]), "+f"(d[10]), "+f"(d[11]), "+f"(d[12]), "+f"(d[13]), "+f"(d[14]), "+f"(d[15]), "+f"(d[16]), "+f"(d[17]), "+f"(d[18]), "+f"(d[19]), "+f"(d[20]), "+f"(d[21]), "+f"(d[22]), "+f"(d[23]), "+f"(d[24]), "+f"(d[25]), "+f"(d[26]), "+f"(d[27]), "+f"(d[28]), "+f"(d[29]), "+f"(d[30]), "+f"(d[31])
        : "l"(da), "l"(db), "r"(scale_d));
}
__device__ __forceinline__ void wgmma_ss_n128(float (&d)[64], uint64_t da, uint64_t db, int scale_d) {
    asm volatile("{\n.reg .pred p;\nsetp.ne.b32 p, %66, 0;\n"
        "wgmma.mma_async.sync.aligned.m64n128k16.f32.bf16.bf16 {%0, %1, %2, %3, %4, %5, %6, %7, %8, %9, %10, %11, %12, %13, %14, %15, %16, %17, %18, %19, %20, %21, %22, %23, %24, %25, %26, %27, %28, %29, %30, %31, %32, %33, %34, %35, %36, %37, %38, %39, %40, %41, %42, %43, %44, %45, %46, %47, %48, %49, %50, %51, %52, %53, %54, %55, %56, %57, %58, %59, %60, %61, %62, %63}, %64, %65, p, 1, 1, 0, 1;\n}\n"
        : "+f"(d[0]), "+f"(d[1]), "+f"(d[2]), "+f"(d[3]), "+f"(d[4]), "+f"(d[5]), "+f"(d[6]), "+f"(d[7]), "+f"(d[8]), "+f"(d[9]), "+f"(d[10]), "+f"(d[11]), "+f"(d[12]), "+f"(d[13]), "+f"(d[14]), "+f"(d[15]), "+f"(d[16]), "+f"(d[17]), "+f"(d[18]), "+f"(d[19]), "+f"(d[20]), "+f"(d[21]), "+f"(d[22]), "+f"(d[23]), "+f"(d[24]), "+f"(d[25]), "+f"(d[26]), "+f"(d[27]), "+f"(d[28]), "+f"(d[29]), "+f"(d[30]), "+f"(d[31]), "+f"(d[32]), "+f"(d[33]), "+f"(d[34]), "+f"(d[35]), "+f"(d[36]), "+f"(d[37]), "+f"(d[38]), "+f"(d[39]), "+f"(d[40]), "+f"(d[41]), "+f"(d[42]), "+f"(d[43]), "+f"(d[44]), "+f"(d[45]), "+f"(d[46]), "+f"(d[47]), "+f"(d[48]), "+f"(d[49]), "+f"(d[50]), "+f"(d[51]), "+f"(d[52]), "+f"(d[53]), "+f"(d[54]), "+f"(d[55]), "+f"(d[56]), "+f"(d[57]), "+f"(d[58]), "+f"(d[59]), "+f"(d[60]), "+f"(d[61]), "+f"(d[62]), "+f"(d[63])
        : "l"(da), "l"(db), "r"(scale_d));
}
__device__ __forceinline__ void wgmma_ss_n200(float (&d)[100], uint64_t da, uint64_t db, int scale_d) {
    asm volatile("{\n.reg .pred p;\nsetp.ne.b32 p, %102, 0;\n"
        "wgmma.mma_async.sync.aligned.m64n200k16.f32.bf16.bf16 {%0, %1, %2, %3, %4, %5, %6, %7, %8, %9, %10, %11, %12, %13, %14, %15, %16, %17, %18, %19, %20, %21, %22, %23, %24, %25, %26, %27, %28, %29, %30, %31, %32, %33, %34, %35, %36, %37, %38, %39, %40, %41, %42, %43, %44, %45, %46, %47, %48, %49, %50, %51, %52, %53, %54, %55, %56, %57, %58, %59, %60, %61, %62, %63, %64, %65, %66, %67, %68, %69, %70, %71, %72, %73, %74, %75, %76, %77, %78, %79, %80, %81, %82, %83, %84, %85, %86, %87, %88, %89, %90, %91, %92, %93, %94, %95, %96, %97, %98, %99}, %100, %101, p, 1, 1, 0, 1;\n}\n"
        : "+f"(d[0]), "+f"(d[1]), "+f"(d[2]), "+f"(d[3]), "+f"(d[4]), "+f"(d[5]), "+f"(d[6]), "+f"(d[7]), "+f"(d[8]), "+f"(d[9]), "+f"(d[10]), "+f"(d[11]), "+f"(d[12]), "+f"(d[13]), "+f"(d[14]), "+f"(d[15]), "+f"(d[16]), "+f"(d[17]), "+f"(d[18]), "+f"(d[19]), "+f"(d[20]), "+f"(d[21]), "+f"(d[22]), "+f"(d[23]), "+f"(d[24]), "+f"(d[25]), "+f"(d[26]), "+f"(d[27]), "+f"(d[28]), "+f"(d[29]), "+f"(d[30]), "+f"(d[31]), "+f"(d[32]), "+f"(d[33]), "+f"(d[34]), "+f"(d[35]), "+f"(d[36]), "+f"(d[37]), "+f"(d[38]), "+f"(d[39]), "+f"(d[40]), "+f"(d[41]), "+f"(d[42]), "+f"(d[43]), "+f"(d[44]), "+f"(d[45]), "+f"(d[46]), "+f"(d[47]), "+f"(d[48]), "+f"(d[49]), "+f"(d[50]), "+f"(d[51]), "+f"(d[52]), "+f"(d[53]), "+f"(d[54]), "+f"(d[55]), "+f"(d[56]), "+f"(d[57]), "+f"(d[58]), "+f"(d[59]), "+f"(d[60]), "+f"(d[61]), "+f"(d[62]), "+f"(d[63]), "+f"(d[64]), "+f"(d[65]), "+f"(d[66]), "+f"(d[67]), "+f"(d[68]), "+f"(d[69]), "+f"(d[70]), "+f"(d[71]), "+f"(d[72]), "+f"(d[73]), "+f"(d[74]), "+f"(d[75]), "+f"(d[76]), "+f"(d[77]), "+f"(d[78]), "+f"(d[79]), "+f"(d[80]), "+f"(d[81]), "+f"(d[82]), "+f"(d[83]), "+f"(d[84]), "+f"(d[85]), "+f"(d[86]), "+f"(d[87]), "+f"(d[88]), "+f"(d[89]), "+f"(d[90]), "+f"(d[91]), "+f"(d[92]), "+f"(d[93]), "+f"(d[94]), "+f"(d[95]), "+f"(d[96]), "+f"(d[97]), "+f"(d[98]), "+f"(d[99])
        : "l"(da), "l"(db), "r"(scale_d));
}
__device__ __forceinline__ void wgmma_ss_n224(float (&d)[112], uint64_t da, uint64_t db, int scale_d) {
    asm volatile("{\n.reg .pred p;\nsetp.ne.b32 p, %114, 0;\n"
        "wgmma.mma_async.sync.aligned.m64n224k16.f32.bf16.bf16 {%0, %1, %2, %3, %4, %5, %6, %7, %8, %9, %10, %11, %12, %13, %14, %15, %16, %17, %18, %19, %20, %21, %22, %23, %24, %25, %26, %27, %28, %29, %30, %31, %32, %33, %34, %35, %36, %37, %38, %39, %40, %41, %42, %43, %44, %45, %46, %47, %48, %49, %50, %51, %52, %53, %54, %55, %56, %57, %58, %59, %60, %61, %62, %63, %64, %65, %66, %67, %68, %69, %70, %71, %72, %73, %74, %75, %76, %77, %78, %79, %80, %81, %82, %83, %84, %85, %86, %87, %88, %89, %90, %91, %92, %93, %94, %95, %96, %97, %98, %99, %100, %101, %102, %103, %104, %105, %106, %107, %108, %109, %110, %111}, %112, %113, p, 1, 1, 0, 1;\n}\n"
        : "+f"(d[0]), "+f"(d[1]), "+f"(d[2]), "+f"(d[3]), "+f"(d[4]), "+f"(d[5]), "+f"(d[6]), "+f"(d[7]), "+f"(d[8]), "+f"(d[9]), "+f"(d[10]), "+f"(d[11]), "+f"(d[12]), "+f"(d[13]), "+f"(d[14]), "+f"(d[15]), "+f"(d[16]), "+f"(d[17]), "+f"(d[18]), "+f"(d[19]), "+f"(d[20]), "+f"(d[21]), "+f"(d[22]), "+f"(d[23]), "+f"(d[24]), "+f"(d[25]), "+f"(d[26]), "+f"(d[27]), "+f"(d[28]), "+f"(d[29]), "+f"(d[30]), "+f"(d[31]), "+f"(d[32]), "+f"(d[33]), "+f"(d[34]), "+f"(d[35]), "+f"(d[36]), "+f"(d[37]), "+f"(d[38]), "+f"(d[39]), "+f"(d[40]), "+f"(d[41]), "+f"(d[42]), "+f"(d[43]), "+f"(d[44]), "+f"(d[45]), "+f"(d[46]), "+f"(d[47]), "+f"(d[48]), "+f"(d[49]), "+f"(d[50]), "+f"(d[51]), "+f"(d[52]), "+f"(d[53]), "+f"(d[54]), "+f"(d[55]), "+f"(d[56]), "+f"(d[57]), "+f"(d[58]), "+f"(d[59]), "+f"(d[60]), "+f"(d[61]), "+f"(d[62]), "+f"(d[63]), "+f"(d[64]), "+f"(d[65]), "+f"(d[66]), "+f"(d[67]), "+f"(d[68]), "+f"(d[69]), "+f"(d[70]), "+f"(d[71]), "+f"(d[72]), "+f"(d[73]), "+f"(d[74]), "+f"(d[75]), "+f"(d[76]), "+f"(d[77]), "+f"(d[78]), "+f"(d[79]), "+f"(d[80]), "+f"(d[81]), "+f"(d[82]), "+f"(d[83]), "+f"(d[84]), "+f"(d[85]), "+f"(d[86]), "+f"(d[87]), "+f"(d[88]), "+f"(d[89]), "+f"(d[90]), "+f"(d[91]), "+f"(d[92]), "+f"(d[93]), "+f"(d[94]), "+f"(d[95]), "+f"(d[96]), "+f"(d[97]), "+f"(d[98]), "+f"(d[99]), "+f"(d[100]), "+f"(d[101]), "+f"(d[102]), "+f"(d[103]), "+f"(d[104]), "+f"(d[105]), "+f"(d[106]), "+f"(d[107]), "+f"(d[108]), "+f"(d[109]), "+f"(d[110]), "+f"(d[111])
        : "l"(da), "l"(db), "r"(scale_d));
}
__device__ __forceinline__ void wgmma_rk_n128(float (&d)[64], uint32_t a0, uint32_t a1, uint32_t a2, uint32_t a3, uint64_t db, int scale_d) {
    asm volatile("{\n.reg .pred p;\nsetp.ne.b32 p, %69, 0;\n"
        "wgmma.mma_async.sync.aligned.m64n128k16.f32.bf16.bf16 {%0, %1, %2, %3, %4, %5, %6, %7, %8, %9, %10, %11, %12, %13, %14, %15, %16, %17, %18, %19, %20, %21, %22, %23, %24, %25, %26, %27, %28, %29, %30, %31, %32, %33, %34, %35, %36, %37, %38, %39, %40, %41, %42, %43, %44, %45, %46, %47, %48, %49, %50, %51, %52, %53, %54, %55, %56, %57, %58, %59, %60, %61, %62, %63}, {%64, %65, %66, %67}, %68, p, 1, 1, 0;\n}\n"
        : "+f"(d[0]), "+f"(d[1]), "+f"(d[2]), "+f"(d[3]), "+f"(d[4]), "+f"(d[5]), "+f"(d[6]), "+f"(d[7]), "+f"(d[8]), "+f"(d[9]), "+f"(d[10]), "+f"(d[11]), "+f"(d[12]), "+f"(d[13]), "+f"(d[14]), "+f"(d[15]), "+f"(d[16]), "+f"(d[17]), "+f"(d[18]), "+f"(d[19]), "+f"(d[20]), "+f"(d[21]), "+f"(d[22]), "+f"(d[23]), "+f"(d[24]), "+f"(d[25]), "+f"(d[26]), "+f"(d[27]), "+f"(d[28]), "+f"(d[29]), "+f"(d[30]), "+f"(d[31]), "+f"(d[32]), "+f"(d[33]), "+f"(d[34]), "+f"(d[35]), "+f"(d[36]), "+f"(d[37]), "+f"(d[38]), "+f"(d[39]), "+f"(d[40]), "+f"(d[41]), "+f"(d[42]), "+f"(d[43]), "+f"(d[44]), "+f"(d[45]), "+f"(d[46]), "+f"(d[47]), "+f"(d[48]), "+f"(d[49]), "+f"(d[50]), "+f"(d[51]), "+f"(d[52]), "+f"(d[53]), "+f"(d[54]), "+f"(d[55]), "+f"(d[56]), "+f"(d[57]), "+f"(d[58]), "+f"(d[59]), "+f"(d[60]), "+f"(d[61]), "+f"(d[62]), "+f"(d[63])
        : "r"(a0), "r"(a1), "r"(a2), "r"(a3), "l"(db), "r"(scale_d));
}
__device__ __forceinline__ void wgmma_rk_n64(float (&d)[32], uint32_t a0, uint32_t a1, uint32_t a2, uint32_t a3, uint64_t db, int scale_d) {
    asm volatile("{\n.reg .pred p;\nsetp.ne.b32 p, %37, 0;\n"
        "wgmma.mma_async.sync.aligned.m64n64k16.f32.bf16.bf16 {%0, %1, %2, %3, %4, %5, %6, %7, %8, %9, %10, %11, %12, %13, %14, %15, %16, %17, %18, %19, %20, %21, %22, %23, %24, %25, %26, %27, %28, %29, %30, %31}, {%32, %33, %34, %35}, %36, p, 1, 1, 0;\n}\n"
        : "+f"(d[0]), "+f"(d[1]), "+f"(d[2]), "+f"(d[3]), "+f"(d[4]), "+f"(d[5]), "+f"(d[6]), "+f"(d[7]), "+f"(d[8]), "+f"(d[9]), "+f"(d[10]), "+f"(d[11]), "+f"(d[12]), "+f"(d[13]), "+f"(d[14]), "+f"(d[15]), "+f"(d[16]), "+f"(d[17]), "+f"(d[18]), "+f"(d[19]), "+f"(d[20]), "+f"(d[21]), "+f"(d[22]), "+f"(d[23]), "+f"(d[24]), "+f"(d[25]), "+f"(d[26]), "+f"(d[27]), "+f"(d[28]), "+f"(d[29]), "+f"(d[30]), "+f"(d[31])
        : "r"(a0), "r"(a1), "r"(a2), "r"(a3), "l"(db), "r"(scale_d));
}
__device__ __forceinline__ void wgmma_rs_n16(float (&d)[8], uint32_t a0, uint32_t a1, uint32_t a2, uint32_t a3, uint64_t db, int scale_d) {
    asm volatile("{\n.reg .pred p;\nsetp.ne.b32 p, %13, 0;\n"
        "wgmma.mma_async.sync.aligned.m64n16k16.f32.bf16.bf16 {%0, %1, %2, %3, %4, %5, %6, %7}, {%8, %9, %10, %11}, %12, p, 1, 1, 1;\n}\n"
        : "+f"(d[0]), "+f"(d[1]), "+f"(d[2]), "+f"(d[3]), "+f"(d[4]), "+f"(d[5]), "+f"(d[6]), "+f"(d[7])
        : "r"(a0), "r"(a1), "r"(a2), "r"(a3), "l"(db), "r"(scale_d));
}
template <int N> __device__ __forceinline__ void fence_u32(uint32_t (&d)[N]) {
#pragma unroll
    for (int i = 0; i < N; i++) asm volatile("" : "+r"(d[i]) :: "memory");
}
template <int N> __device__ __forceinline__ void fence_acc(float (&d)[N]) {
#pragma unroll
    for (int i = 0; i < N; i++) asm volatile("" : "+f"(d[i]) :: "memory");
}

__device__ __forceinline__ void bulk_s2g(void* dst, uint32_t src, uint32_t bytes) {
    asm volatile("cp.async.bulk.global.shared::cta.bulk_group [%0], [%1], %2;" :: "l"(dst), "r"(src), "r"(bytes) : "memory");
}
__device__ __forceinline__ void sts128(uint32_t addr, uint4 v) {
    asm volatile("st.shared.v4.b32 [%0], {%1, %2, %3, %4};" :: "r"(addr), "r"(v.x), "r"(v.y), "r"(v.z), "r"(v.w) : "memory");
}
__device__ __forceinline__ void sum_partials(uint32_t sb, int ti, int tj, int lane) {
    for (;;) {
        uint32_t item = 0;
        if (lane == 0) asm volatile("atom.shared.add.u32 %0, [%1], 1;" : "=r"(item) : "r"(sb + ITEM_OFF) : "memory");
        item = __shfl_sync(0xffffffffu, item, 0);
        if (item >= 8) break;
        const uint4* p = g_part + (size_t)((ti * 8 + tj) * 8) * 1024 + item * 128 + lane;
        uint4 v[4][4];
#pragma unroll
        for (int s = 0; s < 4; s++)
#pragma unroll
            for (int n = 0; n < 4; n++) v[n][s] = ldg_weak(p + s * 1024 + n * 32);
#pragma unroll
        for (int n = 0; n < 4; n++) {
            float a[8];
#pragma unroll
            for (int e = 0; e < 8; e++) a[e] = 0.f;
#pragma unroll
            for (int s = 0; s < 4; s++) {
                a[0] += bf_lo(v[n][s].x); a[1] += bf_hi(v[n][s].x); a[2] += bf_lo(v[n][s].y); a[3] += bf_hi(v[n][s].y);
                a[4] += bf_lo(v[n][s].z); a[5] += bf_hi(v[n][s].z); a[6] += bf_lo(v[n][s].w); a[7] += bf_hi(v[n][s].w);
            }
            const uint32_t d = sb + HSUM_OFF + (item * 8 + n * 2) * 512 + lane * 16;
            sts128(d, make_uint4(__float_as_uint(a[0]), __float_as_uint(a[1]), __float_as_uint(a[2]), __float_as_uint(a[3])));
            sts128(d + 512, make_uint4(__float_as_uint(a[4]), __float_as_uint(a[5]), __float_as_uint(a[6]), __float_as_uint(a[7])));
        }
    }
    __syncwarp();
    if (lane == 0) mbar_arrive(sb + B_HSUM);
}

#define PWAIT() mbar_wait(sb + B_EMPTY + 8 * r.slot, r.phase)
#define CWAIT() do { if (!dry) mbar_wait(sb + B_FULL + 8 * r.slot, r.phase); } while (0)
template <bool B> struct BoolTag { static constexpr bool value = B; };
struct Ring {
    int slot; uint32_t phase;
    __device__ __forceinline__ void next() { if (++slot == RING) { slot = 0; phase ^= 1; } }
};

__global__ void __launch_bounds__(384, 1)
fused_kernel(const __grid_constant__ CUtensorMap map_x, const __grid_constant__ CUtensorMap map_qkv,
             const __grid_constant__ CUtensorMap map_w1, const __grid_constant__ CUtensorMap map_w2,
             const __grid_constant__ CUtensorMap map_wo, const __grid_constant__ CUtensorMap map_w1a,
             const __grid_constant__ CUtensorMap map_o,
             const __nv_bfloat16* __restrict__ gate_w, __nv_bfloat16* __restrict__ out,
             const uint8_t* __restrict__ w1p, const uint8_t* __restrict__ w2p, const uint8_t* __restrict__ wop)
{
    extern __shared__ __align__(1024) uint8_t smem_raw[];
    const uint32_t sb = smem_u32(smem_raw);
    const int tid = threadIdx.x, warp = tid >> 5, lane = tid & 31;
    const bool dry = blockIdx.x >= 128;
    const int ti = dry ? (int)(blockIdx.x & 1) * 2 : blockIdx.x >> 3, tj = blockIdx.x & 7;
    if (dry && warp >= 8) {
        asm volatile("setmaxnreg.dec.sync.aligned.u32 88;");
        return;
    }

    if (tid == 0 && !dry) { TSG(31); TSX(0); }
    if (tid == 320) {
        asm volatile("prefetch.tensormap [%0];" :: "l"(&map_x) : "memory");
        asm volatile("prefetch.tensormap [%0];" :: "l"(&map_qkv) : "memory");
        asm volatile("prefetch.tensormap [%0];" :: "l"(&map_w1) : "memory");
        asm volatile("prefetch.tensormap [%0];" :: "l"(&map_w1a) : "memory");
        asm volatile("prefetch.tensormap [%0];" :: "l"(&map_w2) : "memory");
        asm volatile("prefetch.tensormap [%0];" :: "l"(&map_wo) : "memory");
        asm volatile("prefetch.tensormap [%0];" :: "l"(&map_o) : "memory");
    }
    if (tid == 256) {
        mbar_init(sb + B_FULL, 1); mbar_init(sb + B_XFULL, 1);
        fence_async_smem();
        mbar_expect_tx(sb + B_XFULL, 16384);
        tma_2d(sb + X_OFF, &map_x, sb + B_XFULL, 0, ti * 128);
        mbar_expect_only(sb + B_FULL, 12288);
        tma_4d(sb + RING_OFF, &map_qkv, sb + B_FULL, 0, 0, tj, 0);
    }
    uint32_t gwv[N_QKV / 2];
    if (warp == 8) {
        const unsigned short* gws = reinterpret_cast<const unsigned short*>(gate_w);
#pragma unroll
        for (int n = 0; n < N_QKV / 2; n++) gwv[n] = (uint32_t)__ldg(gws + 64 * n + lane) | ((uint32_t)__ldg(gws + 64 * n + 32 + lane) << 16);
    }
    if (tid == 288) {
        for (int s = 1; s < RING; s++) mbar_init(sb + B_FULL + 8 * s, 1);
        for (int s = 0; s < RING; s++) mbar_init(sb + B_EMPTY + 8 * s, 8);
        for (int s = 1; s < 8; s++) mbar_init(sb + B_XFULL + 8 * s, 1);
        fence_async_smem();
    }
    if (tid == 352) {
        mbar_init(sb + B_HDEAD, 8); mbar_init(sb + B_EREADY, 1); mbar_init(sb + B_KVDONE, 8); mbar_init(sb + B_KVREADY, 1);
        mbar_init(sb + B_ODONE, 8); mbar_init(sb + B_WOFULL, 1); mbar_init(sb + B_HSUM, 3);
        mbar_init(sb + B_PREADY, 1); mbar_init(sb + B_SF, 1); mbar_init(sb + B_SF + 8, 1);
        for (int s = 0; s < 4; s++) mbar_init(sb + B_SQ + 8 * s, 8);
        asm volatile("st.shared.u32 [%0], %1;" :: "r"(sb + ITEM_OFF), "r"(0) : "memory");
        fence_async_smem();
    }
    if (!dry) __syncthreads();

    if (warp >= 8) {
        asm volatile("setmaxnreg.dec.sync.aligned.u32 88;");
        if (warp == 8) {
            Ring r{0, 1};
            const bool leader = elect_one();
#pragma unroll
            for (int n = 0; n < N_QKV; n++) {
                const uint32_t full = sb + B_FULL + 8 * r.slot, dst = sb + RING_OFF + r.slot * SLOT;
                if (n > 0) {
                    if (!(n & 1) && leader) {
                        mbar_expect_tx(sb + B_XFULL + 8 * (n >> 1), 16384);
                        tma_2d(sb + X_OFF + (n >> 1) * 16384, &map_x, sb + B_XFULL + 8 * (n >> 1), (n >> 1) * 64, ti * 128);
                    }
                    if (n >= RING) PWAIT();
                    if (leader) {
                        mbar_expect_only(full, 12288);
                        tma_4d(dst, &map_qkv, full, 0, 32 * n, tj, 0);
                    }
                }
                const uint32_t gv = (n & 1) ? (gwv[n >> 1] >> 16) : (gwv[n >> 1] & 0xFFFFu);
                asm volatile("st.shared.v4.b32 [%0], {%1, %2, %2, %2};" :: "r"(dst + 12288 + lane * 128 + ((lane & 7) << 4)), "r"(gv), "r"(0) : "memory");
                fence_async_smem();
                __syncwarp();
                if (leader) mbar_arrive(full);
                r.next();
            }
#pragma unroll 1
            for (int n = 0; n < N_FFN1; n++) {
                const uint32_t full = sb + B_FULL + 8 * r.slot, dst = sb + RING_OFF + r.slot * SLOT;
                PWAIT();
                if (leader) {
                    mbar_expect_tx(full, 16384);
                    tma_4d(dst, &map_w1a, full, 0, 32 * n, 0, tj);
                    tma_2d(dst + 3 * 4096, &map_w1, full, 224 * tj + 192, 32 * n);
                }
                r.next();
            }
            {
                int q = 0, rr = 0;
#pragma unroll 1
                for (int n = 0; n < N_FFN2; n++) {
                    const uint32_t full = sb + B_FULL + 8 * r.slot, dst = sb + RING_OFF + r.slot * SLOT;
                    PWAIT();
                    if (leader) mbar_expect_tx(full, 16384);
#pragma unroll
                    for (int h = 0; h < 2; h++) {
                        if (leader) tma_3d(dst + h * 8192, &map_w2, full, 0, 224 * tj + 32 * rr, 2 * q);
                        if (++rr == 7) { rr = 0; q++; }
                    }
                    r.next();
                }
            }
            mbar_wait(sb + B_KVREADY, 0);
            asm volatile("fence.proxy.async.global;" ::: "memory");
            {
                const int bbase = 8 * ti - 16, b0 = bbase < 0 ? 0 : bbase;
                const uint32_t bytes = (uint32_t)(8 * ti + 8 - b0) * 512;
#pragma unroll 1
                for (int m = 0; m < N_KV; m++) {
                    const uint32_t full = sb + B_FULL + 8 * r.slot, dst = sb + RING_OFF + r.slot * SLOT;
                    if (m == RING) {
                        mbar_wait(sb + B_HDEAD, 0);
                        if (leader) {
                            mbar_expect_tx(sb + B_WOFULL, 65536);
#pragma unroll
                            for (int e = 0; e < 2; e++) tma_2d(sb + X_OFF + e * 32768, &map_wo, sb + B_WOFULL, 64 * tj, 256 * e);
                        }
                    }
                    PWAIT();
                    if (bbase < 0) {
                        for (int z = lane; z < -bbase * 32; z += 32) sts128(dst + z * 16, make_uint4(0u, 0u, 0u, 0u));
                        fence_async_smem();
                        __syncwarp();
                    }
                    if (leader) {
                        const uint4* src = ((m & 1) ? g_vf : g_kf) + ((tj * 4 + (m >> 1)) * 128 + b0) * 32;
                        mbar_expect_tx(full, bytes);
                        bulk_g2s(dst + (b0 - bbase) * 512, src, bytes, full);
                    }
                    r.next();
                }
            }
            {
                mbar_wait(sb + B_EREADY, 0);
                unsigned epoch; asm volatile("ld.shared.u32 %0, [%1];" : "=r"(epoch) : "r"(sb + EPOCH_OFF) : "memory");
                uint32_t pending = 0xFFu & ~(1u << tj), ready = 0;
                mbar_wait(sb + B_HSUM, 0);
#pragma unroll 1
                for (int m = 0; m < N_O; m++) {
                    const uint32_t full = sb + B_FULL + 8 * r.slot, dst = sb + RING_OFF + r.slot * SLOT;
                    PWAIT();
                    for (int it = 0; it < (1 << 20) && !ready; it++) {
                        bool ok = false;
                        if (lane < 8 && ((pending >> lane) & 1)) ok = (int)(ld_acquire(&g_ocnt[(ti * 8 + lane) * 32]) - (epoch + 1)) >= 0;
                        ready = __ballot_sync(0xffffffffu, ok);
                        if (!ready) __nanosleep(100);
                    }
                    const int js = ready ? __ffs(ready) - 1 : __ffs(pending) - 1;
                    pending &= ~(1u << js); ready &= ~(1u << js);
                    asm volatile("fence.proxy.async.global;" ::: "memory");
                    if (leader) {
                        asm volatile("st.shared.u32 [%0], %1;" :: "r"(sb + OSRC_OFF + 4 * m), "r"(js) : "memory");
                        mbar_expect_tx(full, 16384);
                        tma_2d(dst, &map_o, full, 64 * js, ti * 128);
                    }
                    r.next();
                }
            }
        } else if (warp == 9) {
            unsigned epoch = 0;
            if (lane == 0) {
                epoch = atomicAdd(&g_ticket, 1u) >> 7;
                asm volatile("st.shared.u32 [%0], %1;" :: "r"(sb + EPOCH_OFF), "r"(epoch) : "memory");
                mbar_arrive(sb + B_EREADY);
                mbar_wait(sb + B_XFULL + 8 * PF1_AT, 0);
                prefetch_l2(w1p + (size_t)blockIdx.x * 14336, 14336);
                mbar_wait(sb + B_XFULL + 8 * PF2_AT, 0);
                prefetch_l2(w2p + (size_t)blockIdx.x * 14336, 14336);
                prefetch_l2(wop + (size_t)blockIdx.x * 4096, 4096);
                mbar_wait(sb + B_KVDONE, 0);
                red_release(&g_kvcnt[blockIdx.x * 32], 1u);
            }
            epoch = __shfl_sync(0xffffffffu, epoch, 0);
            if (lane < 3 && ti - lane >= 0) wait_counter(&g_kvcnt[((ti - lane) * 8 + tj) * 32], epoch + 1);
            __syncwarp();
            if (lane == 0) mbar_arrive(sb + B_KVREADY);
            mbar_wait(sb + B_SQ + 24, 0);
            if (lane < 8) wait_counter(&g_pcnt[(ti * 8 + lane) * 32], epoch + 1);
            __syncwarp();
            if (lane == 0) { mbar_arrive(sb + B_PREADY); TSX(13); }
            sum_partials(sb, ti, tj, lane);
            if (lane == 0) TSX(14);
        } else {
            if (warp == 10) {
#pragma unroll 1
                for (int q = 0; q < 4; q++) {
                    mbar_wait(sb + B_SQ + 8 * q, 0);
                    if (lane < 16) {
                        uint4* d = g_part + (size_t)(((ti * 8 + 2 * q + (lane & 1)) * 8 + tj) * 8 + (lane >> 1)) * 128;
                        bulk_s2g(d, sb + STG_OFF + (q & 1) * 32768 + lane * 2048, 2048);
                        asm volatile("cp.async.bulk.commit_group;" ::: "memory");
                        asm volatile("cp.async.bulk.wait_group.read 0;" ::: "memory");
                    }
                    __syncwarp();
                    if (lane == 0) mbar_arrive(sb + B_SF + 8 * (q & 1));
                }
                asm volatile("cp.async.bulk.wait_group 0;" ::: "memory");
                asm volatile("fence.proxy.async.global;" ::: "memory");
                __syncwarp();
                if (lane == 0) { red_release(&g_pcnt[blockIdx.x * 32], 1u); TSX(12); }
            }
            mbar_wait(sb + B_PREADY, 0);
            sum_partials(sb, ti, tj, lane);
            if (warp == 11 && lane == 0) {
                mbar_wait(sb + B_ODONE, 0);
                red_release(&g_ocnt[blockIdx.x * 32], 1u);
            }
        }
    } else {
        asm volatile("setmaxnreg.inc.sync.aligned.u32 208;");
        const int wg = warp >> 2, g = lane >> 2, c = lane & 3;
        const uint32_t xa = sb + X_OFF + wg * 8192;
        Ring r{0, 0};
        const bool lane0 = lane == 0 && !dry;
        uint32_t qf[4][4];
        float g0, g1;
        TS(9);
        {
            float acc[100];
            int prev = 0;
            if (wg == 1) asm volatile("bar.sync 3, 256;" ::: "memory");
            for (int s = 0; s < (dry ? 4 : N_QKV); s++) {
                if (!(s & 1) && !dry) mbar_wait(sb + B_XFULL + 8 * (s >> 1), 0);
                CWAIT();
                if (s == 0) TS(1);
                if (s == 2) TS(28);
                if (s == 6) TS(29);
                if (s == 10) TS(20);
                const uint32_t bs = sb + RING_OFF + r.slot * SLOT, as = xa + (s >> 1) * 16384 + (s & 1) * 64;
                wgmma_fence();
                wgmma_ss_n200(acc, desc_a(as), desc_b(bs), s);
                wgmma_ss_n200(acc, desc_a(as + 32), desc_b(bs + 2048), 1);
                wgmma_commit();
                if (wg == 0 && s == LEAD1) asm volatile("bar.arrive 3, 256;" ::: "memory");
                if (s > 0) { wgmma_wait<1>(); if (lane0) mbar_arrive(sb + B_EMPTY + 8 * prev); }
                prev = r.slot; r.next();
            }
            wgmma_wait<0>();
            fence_acc(acc);
            if (lane0) mbar_arrive(sb + B_EMPTY + 8 * prev);
            TS(2);
            const int blk = ti * 8 + warp;
#pragma unroll
            for (int hh = 0; hh < 4; hh++) {
                const float* t0 = &acc[8 * hh]; const float* t1 = &acc[8 * hh + 4];
                qf[hh][0] = pack_bf16(t0[0], t0[1]); qf[hh][1] = pack_bf16(t0[2], t0[3]);
                qf[hh][2] = pack_bf16(t1[0], t1[1]); qf[hh][3] = pack_bf16(t1[2], t1[3]);
#pragma unroll
                for (int mtx = 0; mtx < 2; mtx++) {
                    const float* t = &acc[32 + 32 * mtx + 8 * hh];
                    uint32_t r0 = pack_bf16(t[0], t[1]), r1 = pack_bf16(t[4], t[5]), r2 = pack_bf16(t[2], t[3]), r3 = pack_bf16(t[6], t[7]);
                    {
                        const bool hi = c & 1;
                        const uint32_t s0 = __shfl_xor_sync(0xffffffffu, hi ? r0 : r1, 1), s1 = __shfl_xor_sync(0xffffffffu, hi ? r2 : r3, 1);
                        if (hi) { r0 = s0; r2 = s1; } else { r1 = s0; r3 = s1; }
                    }
                    {
                        const bool hi = c & 2;
                        const uint32_t s0 = __shfl_xor_sync(0xffffffffu, hi ? r0 : r2, 2), s1 = __shfl_xor_sync(0xffffffffu, hi ? r1 : r3, 2);
                        if (hi) { r0 = s0; r1 = s1; } else { r2 = s0; r3 = s1; }
                    }
                    const int row = g + 8 * (c >> 1);
                    uint4* dst = (mtx ? g_vf : g_kf) + ((tj * 4 + hh) * 128 + blk) * 32 + row * 2 + ((c & 1) ^ ((row >> 2) & 1));
                    if (!dry) *dst = make_uint4(r0, r1, r2, r3);
                }
            }
            __syncwarp();
            if (lane0) mbar_arrive(sb + B_KVDONE);
            const float z0 = __shfl_sync(0xffffffffu, acc[96], lane & ~3), z1 = __shfl_sync(0xffffffffu, acc[98], lane & ~3);
            g0 = 1.f / (1.f + __expf(-z0)); g1 = 1.f / (1.f + __expf(-z1));
        }
        TS(3);
        const int wrow = (warp & 3) * 16;
        {
            float acc[112];
            int prev = 0;
            for (int s = 0; s < (dry ? 4 : N_FFN1); s++) {
                CWAIT();
                const uint32_t bs = sb + RING_OFF + r.slot * SLOT, as = xa + (s >> 1) * 16384 + (s & 1) * 64;
                wgmma_fence();
                wgmma_ss_n224(acc, desc_a(as), desc_b(bs), s);
                wgmma_ss_n224(acc, desc_a(as + 32), desc_b(bs + 2048), 1);
                wgmma_commit();
                if (s > 0) { wgmma_wait<1>(); if (lane0) mbar_arrive(sb + B_EMPTY + 8 * prev); }
                prev = r.slot; r.next();
            }
            wgmma_wait<0>();
            fence_acc(acc);
            if (lane0) mbar_arrive(sb + B_EMPTY + 8 * prev);
            TS(4);
            const float s0 = 1.f - g0, s1 = 1.f - g1;
            asm volatile("bar.sync %0, 128;" :: "r"(1 + wg) : "memory");
            const uint32_t strow = xa + (wrow + ((lane >> 3) & 1) * 8 + (lane & 7)) * 128;
#pragma unroll
            for (int p = 0; p < 14; p++) {
                const int nt = 2 * p + (lane >> 4);
                const float* a = &acc[8 * p];
                stmatrix_x4(strow + (p >> 2) * 16384 + (((nt & 7) ^ (lane & 7)) << 4),
                            pack_bf16_relu(a[0] * s0, a[1] * s0), pack_bf16_relu(a[2] * s1, a[3] * s1),
                            pack_bf16_relu(a[4] * s0, a[5] * s0), pack_bf16_relu(a[6] * s1, a[7] * s1));
            }
        }
        TS(5);
        {
            fence_async_smem();
            asm volatile("bar.sync 4, 256;" ::: "memory");
            float accA[64], accB[64];
            auto epilogue = [&](float (&acc)[64], int q) {
                fence_acc(acc);
                const uint32_t st = sb + STG_OFF + (q & 1) * 32768 + warp * 4096;
                if (q >= 2 && !dry) mbar_wait(sb + B_SF + 8 * (q & 1), 0);
#pragma unroll
                for (int t2 = 0; t2 < 8; t2++) {
                    uint4 v;
                    v.x = pack_bf16(acc[8 * t2 + 0], acc[8 * t2 + 1]); v.y = pack_bf16(acc[8 * t2 + 2], acc[8 * t2 + 3]);
                    v.z = pack_bf16(acc[8 * t2 + 4], acc[8 * t2 + 5]); v.w = pack_bf16(acc[8 * t2 + 6], acc[8 * t2 + 7]);
                    sts128(st + t2 * 512 + lane * 16, v);
                }
                fence_async_smem();
                __syncwarp();
                if (lane0) mbar_arrive(sb + B_SQ + 8 * q);
            };
            int rel = r.slot;
#pragma unroll
            for (int m = 0; m < N_FFN2; m++) {
                CWAIT();
                wgmma_fence();
#pragma unroll
                for (int h = 0; h < 2; h++) {
                    const int u = 2 * m + h, q = u / 7, rr = u % 7;
                    const uint32_t bs = sb + RING_OFF + r.slot * SLOT + h * 8192;
                    const uint32_t as = xa + (rr >> 1) * 16384 + (rr & 1) * 64;
                    if (!(q & 1)) {
                        wgmma_ss_n128(accA, desc_a(as), desc_b(bs), rr);
                        wgmma_ss_n128(accA, desc_a(as + 32), desc_b(bs + 2048), 1);
                    } else {
                        wgmma_ss_n128(accB, desc_a(as), desc_b(bs), rr);
                        wgmma_ss_n128(accB, desc_a(as + 32), desc_b(bs + 2048), 1);
                    }
                }
                wgmma_commit();
                r.next();
                wgmma_wait<1>();
                if (m > 0) {
                    if (lane0) mbar_arrive(sb + B_EMPTY + 8 * rel);
                    if (++rel == RING) rel = 0;
                }
                if (m == 4) { TS(25); epilogue(accA, 0); }
                if (m == 7) { TS(26); epilogue(accB, 1); }
                if (m == 11) { TS(27); epilogue(accA, 2); }
            }
            wgmma_wait<0>();
            if (lane0) { mbar_arrive(sb + B_EMPTY + 8 * rel); mbar_arrive(sb + B_HDEAD); }
            epilogue(accB, 3);
        }
        TS(6);
        {
            const float SC = 0.25f * 1.4426950408889634f;
            const int gb0 = 8 * ti - 16 + 4 * wg;
            int slotK = 0, slotV = 0;
            const uint32_t ostore = sb + OWN_OFF + (warp * 16 + ((lane >> 3) & 1) * 8 + (lane & 7)) * 128;
            uint32_t* odst = reinterpret_cast<uint32_t*>(g_o + (size_t)(ti * 128 + warp * 16 + g) * 512 + tj * 64 + ((lane & 1) ? 8 : 0) + (lane & 2) * 2);
#define NHEADS (dry ? 2 : 4)
#define ATT_KWAIT(kb) do { slotK = r.slot; CWAIT(); kb = sb + RING_OFF + slotK * SLOT + wg * 2048; r.next(); } while (0)
#define ATT_VWAIT(vb) do { slotV = r.slot; CWAIT(); vb = sb + RING_OFF + slotV * SLOT + wg * 2048; r.next(); TS(21 + hh); } while (0)
#define ATT_KREL() do { __syncwarp(); if (lane0) mbar_arrive(sb + B_EMPTY + 8 * slotK); } while (0)
#define ATT_VREL() do { __syncwarp(); if (lane0) mbar_arrive(sb + B_EMPTY + 8 * slotV); } while (0)
#define ATT_NEXTQ(h) do { \
                if ((h) == 1) { q0 = qf[1][0]; q1 = qf[1][1]; q2 = qf[1][2]; q3 = qf[1][3]; } \
                else if ((h) == 2) { q0 = qf[2][0]; q1 = qf[2][1]; q2 = qf[2][2]; q3 = qf[2][3]; } \
                else { q0 = qf[3][0]; q1 = qf[3][1]; q2 = qf[3][2]; q3 = qf[3][3]; } } while (0)
#define ATT_STORE(h, r0, r1, r2, r3) do { \
                if ((h) == 0 && !dry) mbar_wait(sb + B_SF, 1);        \
                stmatrix_x4(ostore + (((2 * (h) + (lane >> 4)) ^ (lane & 7)) << 4), r0, r1, r2, r3); \
                const bool odd = lane & 1; \
                const uint32_t sl = __shfl_xor_sync(0xffffffffu, odd ? (r0) : (r2), 1), sh = __shfl_xor_sync(0xffffffffu, odd ? (r1) : (r3), 1); \
                if (!dry) *reinterpret_cast<uint2*>(odst + 8 * (h)) = odd ? make_uint2(sl, r2) : make_uint2(r0, sl); \
                if (!dry) *reinterpret_cast<uint2*>(odst + 8 * (h) + 8 * 256) = odd ? make_uint2(sh, r3) : make_uint2(r1, sh); \
                } while (0)
            const float NEG = -INFINITY;
            const int ww = warp & 3;
            uint32_t tri = 0;
#pragma unroll
            for (int e = 0; e < 8; e++) tri |= (uint32_t)((8 * (e >> 2) + 2 * c + (e & 1)) > (g + 8 * ((e >> 1) & 1))) << e;
            uint32_t trim[4];
#pragma unroll
            for (int k = 0; k < 4; k++) trim[k] = (((tri >> (2 * k)) & 1u) ? 0x0000FFFFu : 0u) | (((tri >> (2 * k + 1)) & 1u) ? 0xFFFF0000u : 0u);
            uint32_t q0 = qf[0][0], q1 = qf[0][1], q2 = qf[0][2], q3 = qf[0][3];
            auto rowmax = [&](const float (&s)[64], const uint32_t (&dead)[8], float b0, float b1, float& n0, float& n1) {
                int i0 = __float_as_int(b0), i1 = __float_as_int(b1);
#pragma unroll
                for (int t = 0; t < 16; t++) {
                    i0 = __vimax3_s32(i0, __float_as_int(s[4 * t]), __float_as_int(s[4 * t + 1]));
                    i1 = __vimax3_s32(i1, __float_as_int(s[4 * t + 2]), __float_as_int(s[4 * t + 3]));
                }
                i0 = max(i0, __shfl_xor_sync(0xffffffffu, i0, 1)); i1 = max(i1, __shfl_xor_sync(0xffffffffu, i1, 1));
                i0 = max(i0, __shfl_xor_sync(0xffffffffu, i0, 2)); i1 = max(i1, __shfl_xor_sync(0xffffffffu, i1, 2));
                n0 = __int_as_float(i0); n1 = __int_as_float(i1);
                if (__any_sync(0xffffffffu, i0 <= 0 || i1 <= 0)) {
                    asm volatile("" ::: "memory");
                    n0 = b0; n1 = b1;
#pragma unroll
                    for (int t = 0; t < 16; t++) {
                        const uint32_t dd = dead[t >> 1] >> (4 * (t & 1));
                        n0 = fmaxf(n0, fmaxf((dd & 1u) ? NEG : s[4 * t], (dd & 2u) ? NEG : s[4 * t + 1]));
                        n1 = fmaxf(n1, fmaxf((dd & 4u) ? NEG : s[4 * t + 2], (dd & 8u) ? NEG : s[4 * t + 3]));
                    }
                    n0 = fmaxf(n0, __shfl_xor_sync(0xffffffffu, n0, 1)); n1 = fmaxf(n1, __shfl_xor_sync(0xffffffffu, n1, 1));
                    n0 = fmaxf(n0, __shfl_xor_sync(0xffffffffu, n0, 2)); n1 = fmaxf(n1, __shfl_xor_sync(0xffffffffu, n1, 2));
                }
            };
            auto expp = [&](float (&s)[64], const uint32_t (&dead)[8], uint32_t (&p)[32], const int nmixed, float mr0, float mr1, float& l0, float& l1) {
                if (gb0 < 0) {
#pragma unroll
                    for (int t = 0; t < 64; t++) s[t] = ((dead[t >> 3] >> (t & 7)) & 1u) ? NEG : s[t];
                }
#pragma unroll
                for (int t = 0; t < 16; t++) {
                    const float k0 = -mr0, k1 = -mr0, k2 = -mr1, k3 = -mr1;
                    const float e0 = ex2(fmaf(s[4 * t], SC, k0)), e1 = ex2(fmaf(s[4 * t + 1], SC, k1));
                    const float e2 = ex2(fmaf(s[4 * t + 2], SC, k2)), e3 = ex2(fmaf(s[4 * t + 3], SC, k3));
                    l0 += e0 + e1; l1 += e2 + e3;
                    p[2 * t] = pack_bf16(e0, e1); p[2 * t + 1] = pack_bf16(e2, e3);
                }
            };
            uint32_t deadA[8], deadB[8];
#pragma unroll
            for (int j = 0; j < 8; j++) {
                const uint32_t mk = j >= 4 || j > ww ? 0xFFu : (j < ww ? 0u : tri);
                deadA[j] = gb0 + j < 0 ? mk : 0u;
                deadB[j] = gb0 + 8 + j < 0 ? 0xFFu : 0u;
            }
            uint32_t kbase = 0, vbase = 0;
#pragma unroll 1
            for (int hh = 0; hh < NHEADS; hh++) {
                ATT_KWAIT(kbase);
                if (hh > 0) ATT_NEXTQ(hh);
                float va[64], oa[8], ob[8];
                uint32_t pa[32], pd[16];
                float m0, m1, la0 = 0.f, la1 = 0.f;
                {
                    float sa[64], sd[32];
                    wgmma_fence();
                    wgmma_rk_n128(sa, q0, q1, q2, q3, desc_kv(kbase), 0);
                    wgmma_rk_n64(sd, q0, q1, q2, q3, desc_kv(kbase + 16 * 512), 0);
                    wgmma_commit();
                    wgmma_wait<0>();
                    fence_acc(sa); fence_acc(sd);
#pragma unroll
                    for (int e = 32; e < 64; e++) va[e] = sa[e];
#pragma unroll
                    for (int j = 0; j < 4; j++) {
                        if (j < ww) {
#pragma unroll
                            for (int e = 0; e < 8; e++) va[8 * j + e] = sd[8 * j + e];
                        } else if (j == ww) {
#pragma unroll
                            for (int e = 0; e < 8; e++) va[8 * j + e] = ((tri >> e) & 1u) ? sa[8 * j + e] : sd[8 * j + e];
                        } else {
#pragma unroll
                            for (int e = 0; e < 8; e++) va[8 * j + e] = sa[8 * j + e];
                        }
                    }
                }
                rowmax(va, deadA, NEG, NEG, m0, m1);
                expp(va, deadA, pa, 8, m0 * SC, m1 * SC, la0, la1);
#pragma unroll
                for (int j = 0; j < 4; j++) {
#pragma unroll
                    for (int k = 0; k < 4; k++) {
                        const uint32_t mm = j > ww ? 0xFFFFFFFFu : (j < ww ? 0u : trim[k]);
                        pd[4 * j + k] = pa[4 * j + k] & ~mm;
                        pa[4 * j + k] &= mm;
                    }
                }
                ATT_VWAIT(vbase);
                fence_u32(pa); fence_u32(pd);
                wgmma_fence();
                float sb2[64];
                wgmma_rk_n128(sb2, q0, q1, q2, q3, desc_kv(kbase + 8 * 512), 0);
                wgmma_commit();
#pragma unroll
                for (int j = 0; j < 8; j++) wgmma_rs_n16(oa, pa[4 * j], pa[4 * j + 1], pa[4 * j + 2], pa[4 * j + 3], desc_kv(vbase + j * 512), j);
#pragma unroll
                for (int j = 0; j < 4; j++) wgmma_rs_n16(oa, pd[4 * j], pd[4 * j + 1], pd[4 * j + 2], pd[4 * j + 3], desc_kv(vbase + (16 + j) * 512), 1);
                wgmma_commit();
                wgmma_wait<1>();
                fence_acc(sb2);
#pragma unroll
                for (int e = 0; e < 64; e++) va[e] = sb2[e];
                ATT_KREL();
                float n0, n1, lb0 = 0.f, lb1 = 0.f;
                uint32_t pb[32];
                rowmax(va, deadB, m0, m1, n0, n1);
                wgmma_wait<0>();
                fence_acc(oa);
                expp(va, deadB, pb, 0, n0 * SC, n1 * SC, lb0, lb1);
                fence_u32(pb);
                wgmma_fence();
#pragma unroll
                for (int j = 0; j < 8; j++) wgmma_rs_n16(ob, pb[4 * j], pb[4 * j + 1], pb[4 * j + 2], pb[4 * j + 3], desc_kv(vbase + (8 + j) * 512), j);
                wgmma_commit();
                const float a0 = ex2((m0 - n0) * SC), a1 = ex2((m1 - n1) * SC);
                float l0 = fmaf(la0, a0, lb0), l1 = fmaf(la1, a1, lb1);
                l0 += __shfl_xor_sync(0xffffffffu, l0, 1); l1 += __shfl_xor_sync(0xffffffffu, l1, 1);
                l0 += __shfl_xor_sync(0xffffffffu, l0, 2); l1 += __shfl_xor_sync(0xffffffffu, l1, 2);
                const float f0 = __fdividef(g0, l0), f1 = __fdividef(g1, l1);
                wgmma_wait<0>();
                fence_acc(ob);
                ATT_VREL();
                ATT_STORE(hh, pack_bf16(fmaf(oa[0], a0, ob[0]) * f0, fmaf(oa[1], a0, ob[1]) * f0), pack_bf16(fmaf(oa[2], a1, ob[2]) * f1, fmaf(oa[3], a1, ob[3]) * f1),
                              pack_bf16(fmaf(oa[4], a0, ob[4]) * f0, fmaf(oa[5], a0, ob[5]) * f0), pack_bf16(fmaf(oa[6], a1, ob[6]) * f1, fmaf(oa[7], a1, ob[7]) * f1));
            }
            fence_async_smem();
            __syncwarp();
            if (lane0) mbar_arrive(sb + B_ODONE);
        }
        TS(7);
        {
            float acc[32];
            uint4 pv[4][4];
            if (!dry) mbar_wait(sb + B_PREADY, 0);
            {
                const uint4* p = g_part + (size_t)((ti * 8 + tj) * 8 + 4) * 1024 + warp * 128 + lane;
#pragma unroll
                for (int s = 0; s < 4; s++)
#pragma unroll
                    for (int n = 0; n < 4; n++) pv[n][s] = dry ? make_uint4(0u, 0u, 0u, 0u) : ldg_weak(p + s * 1024 + n * 32);
            }
            if (!dry) mbar_wait(sb + B_WOFULL, 0);
            if (!dry) mbar_wait(sb + B_ODONE, 0);
            TS(15);
            wgmma_fence();
#pragma unroll
            for (int k = 0; k < 4; k++) wgmma_ss_n64(acc, desc_a(sb + OWN_OFF + wg * 8192 + 32 * k), desc_b(sb + X_OFF + tj * 8192 + 2048 * k), k);
            wgmma_commit();
            TS(16);
#pragma unroll 1
            for (int m = 0; m < N_O; m++) {
                CWAIT();
                uint32_t js; asm volatile("ld.shared.u32 %0, [%1];" : "=r"(js) : "r"(sb + OSRC_OFF + 4 * m) : "memory");
                const uint32_t as = sb + RING_OFF + r.slot * SLOT + wg * 8192;
                const uint32_t bs = sb + X_OFF + (js & 7) * 8192;
                wgmma_fence();
#pragma unroll
                for (int k = 0; k < 4; k++) wgmma_ss_n64(acc, desc_a(as + 32 * k), desc_b(bs + 2048 * k), 1);
                wgmma_commit();
                if (m == 0) { wgmma_wait<0>(); if (lane0) mbar_arrive(sb + B_EMPTY + 8 * r.slot); }
                r.next();
            }
            float base[32];
            if (!dry) mbar_wait(sb + B_HSUM, 0);
#pragma unroll
            for (int n = 0; n < 4; n++) {
                const uint4 u0 = lds128(sb + HSUM_OFF + (warp * 8 + 2 * n) * 512 + lane * 16), u1 = lds128(sb + HSUM_OFF + (warp * 8 + 2 * n + 1) * 512 + lane * 16);
                float* a = &base[8 * n];
                a[0] = __uint_as_float(u0.x); a[1] = __uint_as_float(u0.y); a[2] = __uint_as_float(u0.z); a[3] = __uint_as_float(u0.w);
                a[4] = __uint_as_float(u1.x); a[5] = __uint_as_float(u1.y); a[6] = __uint_as_float(u1.z); a[7] = __uint_as_float(u1.w);
#pragma unroll
                for (int s = 0; s < 4; s++) {
                    a[0] += bf_lo(pv[n][s].x); a[1] += bf_hi(pv[n][s].x); a[2] += bf_lo(pv[n][s].y); a[3] += bf_hi(pv[n][s].y);
                    a[4] += bf_lo(pv[n][s].z); a[5] += bf_hi(pv[n][s].z); a[6] += bf_lo(pv[n][s].w); a[7] += bf_hi(pv[n][s].w);
                }
            }
            fence_acc(base);
            wgmma_wait<0>();
            fence_acc(acc);
            TS(17);
#pragma unroll
            for (int k = 0; k < 32; k++) acc[k] += base[k];
            __nv_bfloat16* o = out + (size_t)(ti * 128 + warp * 16 + g) * 512 + tj * 64 + ((lane & 1) ? 8 : 0) + (lane & 2) * 2;
            const bool odd = lane & 1;
#pragma unroll
            for (int t2 = 0; t2 < 4; t2++) {
                const uint32_t lo0 = pack_bf16(acc[8 * t2 + 0], acc[8 * t2 + 1]), hi0 = pack_bf16(acc[8 * t2 + 2], acc[8 * t2 + 3]);
                const uint32_t lo1 = pack_bf16(acc[8 * t2 + 4], acc[8 * t2 + 5]), hi1 = pack_bf16(acc[8 * t2 + 6], acc[8 * t2 + 7]);
                const uint32_t sl = __shfl_xor_sync(0xffffffffu, odd ? lo0 : lo1, 1), sh = __shfl_xor_sync(0xffffffffu, odd ? hi0 : hi1, 1);
                if (!dry) *reinterpret_cast<uint2*>(o + 16 * t2) = odd ? make_uint2(sl, lo1) : make_uint2(lo0, sl);
                if (!dry) *reinterpret_cast<uint2*>(o + 16 * t2 + 8 * 512) = odd ? make_uint2(sh, hi1) : make_uint2(hi0, sh);
            }
            if (tid == 0 && !dry) TSG(30);
        }
        TS(8);
    }
}

typedef CUresult (*PFN_encodeTiled)(CUtensorMap*, CUtensorMapDataType, cuuint32_t, void*, const cuuint64_t*, const cuuint64_t*,
                                    const cuuint32_t*, const cuuint32_t*, CUtensorMapInterleave, CUtensorMapSwizzle,
                                    CUtensorMapL2promotion, CUtensorMapFloatOOBfill);

void make_map(PFN_encodeTiled enc, CUtensorMap* m, const void* base, int rank, const cuuint64_t* dims, const cuuint64_t* strides, const cuuint32_t* box) {
    cuuint32_t es[5] = {1, 1, 1, 1, 1};
    enc(m, CU_TENSOR_MAP_DATA_TYPE_BFLOAT16, (cuuint32_t)rank, const_cast<void*>(base), dims, strides, box, es,
        CU_TENSOR_MAP_INTERLEAVE_NONE, CU_TENSOR_MAP_SWIZZLE_128B, CU_TENSOR_MAP_L2_PROMOTION_L2_256B, CU_TENSOR_MAP_FLOAT_OOB_FILL_NONE);
}

}

extern "C" void kernel_launch(void* const* d_in, const int* in_sizes, int n_in, void* d_out, int out_size) {
    (void)in_sizes; (void)n_in; (void)out_size;
    const void* x = d_in[0]; const void* wqkv = d_in[1]; const void* wo = d_in[2];
    const void* w1 = d_in[4]; const void* w2 = d_in[5]; const void* gate_w = d_in[6];
    static PFN_encodeTiled enc = nullptr;
    if (!enc) {
        void* fn = nullptr; cudaDriverEntryPointQueryResult st;
        cudaGetDriverEntryPoint("cuTensorMapEncodeTiled", &fn, cudaEnableDefault, &st);
        enc = (PFN_encodeTiled)fn;
        cudaFuncSetAttribute(fused_kernel, cudaFuncAttributeMaxDynamicSharedMemorySize, SMEM_BYTES);
    }
    CUtensorMap mx, mqkv, mw1, mw2, mwo, mw1a, mo;
    void* optr = nullptr;
    cudaGetSymbolAddress(&optr, g_o);
    { cuuint64_t d[2] = {512, 2048}, s[1] = {1024}; cuuint32_t b[2] = {64, 128}; make_map(enc, &mo, optr, 2, d, s, b); }
    { cuuint64_t d[4] = {64, 512, 3, 8}, s[3] = {3584, 128, 448}; cuuint32_t b[4] = {64, 32, 3, 1}; make_map(enc, &mw1a, w1, 4, d, s, b); }
    { cuuint64_t d[2] = {512, 2048}, s[1] = {1024}; cuuint32_t b[2] = {64, 128}; make_map(enc, &mx, x, 2, d, s, b); }
    { cuuint64_t d[4] = {64, 512, 8, 3}, s[3] = {3072, 128, 1024}; cuuint32_t b[4] = {64, 32, 1, 3}; make_map(enc, &mqkv, wqkv, 4, d, s, b); }
    { cuuint64_t d[2] = {1792, 512}, s[1] = {3584}; cuuint32_t b[2] = {64, 32}; make_map(enc, &mw1, w1, 2, d, s, b); }
    { cuuint64_t d[3] = {64, 1792, 8}, s[2] = {1024, 128}; cuuint32_t b[3] = {64, 32, 2}; make_map(enc, &mw2, w2, 3, d, s, b); }
    { cuuint64_t d[2] = {512, 512}, s[1] = {1024}; cuuint32_t b[2] = {64, 256}; make_map(enc, &mwo, wo, 2, d, s, b); }
    fused_kernel<<<NCTA, 384, SMEM_BYTES, cudaStreamPerThread>>>(mx, mqkv, mw1, mw2, mwo, mw1a, mo, (const __nv_bfloat16*)gate_w, (__nv_bfloat16*)d_out,
                                           (const uint8_t*)w1, (const uint8_t*)w2, (const uint8_t*)wo);
}
```

```cpp
#include <cuda_runtime.h>
#include <cuda_bf16.h>
#include <cuda.h>
#include <stdint.h>

namespace {

#define PF1_AT 1
#define PF2_AT 5
#define LEAD1 2
#define NCTA 132
constexpr int RING = 6;
constexpr int SLOT = 16384;
constexpr uint32_t X_OFF = 0;
constexpr uint32_t STG_OFF = X_OFF + 4 * 16384;
constexpr uint32_t RING_OFF = 131072;
constexpr uint32_t BAR_OFF = RING_OFF + RING * SLOT;
constexpr uint32_t B_FULL = BAR_OFF, B_EMPTY = BAR_OFF + 64, B_XFULL = BAR_OFF + 128, B_HDEAD = BAR_OFF + 192,
                   B_EREADY = BAR_OFF + 200, B_KVDONE = BAR_OFF + 208, B_ODONE = BAR_OFF + 224,
                   B_KVREADY = BAR_OFF + 232, B_WOFULL = BAR_OFF + 240, B_HSUM = BAR_OFF + 248, B_PREADY = BAR_OFF + 264,
                   B_SQ = BAR_OFF + 272, B_SF = BAR_OFF + 304, B_XDEAD = BAR_OFF + 320;
constexpr uint32_t EPOCH_OFF = BAR_OFF + 256, ITEM_OFF = BAR_OFF + 260, OSRC_OFF = BAR_OFF + 384;
constexpr uint32_t OWN_OFF = X_OFF + 4 * 16384;
constexpr uint32_t HSUM_OFF = X_OFF + 6 * 16384;
constexpr uint32_t SMEM_BYTES = BAR_OFF + 1024;

constexpr int N_QKV = 16, N_FFN1 = 16, N_FFN2 = 14, N_KV = 8, N_O = 7;

__device__ uint4 g_kf[32 * 128 * 32];
__device__ uint4 g_vf[32 * 128 * 32];
__device__ uint4 g_part[16 * 8 * 8 * 8 * 4 * 32];
__device__ __nv_bfloat16 g_o[2048 * 512];
__device__ unsigned g_ticket;
__device__ unsigned g_kvcnt[128 * 32];
__device__ unsigned g_pcnt[128 * 32];
__device__ unsigned g_ocnt[128 * 32];
#define TS(k) do {} while (0)
#define TS2(k) do {} while (0)
#define TS2X(k) do {} while (0)
#define TSX(k) do {} while (0)
#define TSG(k) do {} while (0)

__device__ __forceinline__ uint32_t smem_u32(const void* p) { return (uint32_t)__cvta_generic_to_shared(p); }
__device__ __forceinline__ void mbar_init(uint32_t bar, uint32_t cnt) { asm volatile("mbarrier.init.shared::cta.b64 [%0], %1;" :: "r"(bar), "r"(cnt) : "memory"); }
__device__ __forceinline__ void mbar_expect_tx(uint32_t bar, uint32_t bytes) { asm volatile("mbarrier.arrive.expect_tx.shared::cta.b64 _, [%0], %1;" :: "r"(bar), "r"(bytes) : "memory"); }
__device__ __forceinline__ void mbar_expect_only(uint32_t bar, uint32_t bytes) { asm volatile("mbarrier.expect_tx.relaxed.cta.shared::cta.b64 [%0], %1;" :: "r"(bar), "r"(bytes) : "memory"); }
__device__ __forceinline__ void mbar_arrive(uint32_t bar) { asm volatile("mbarrier.arrive.shared::cta.b64 _, [%0];" :: "r"(bar) : "memory"); }
__device__ __forceinline__ void mbar_wait(uint32_t bar, uint32_t parity) {
    asm volatile("{\n.reg .pred P1, P2;\n.reg .u32 n;\nmov.u32 n, 0;\n"
                 "WAIT_LOOP:\n"
                 "mbarrier.try_wait.parity.shared::cta.b64 P1, [%0], %1;\n"
                 "@P1 bra WAIT_DONE;\n"
                 "add.u32 n, n, 1;\n"
                 "setp.lt.u32 P2, n, 0x400000;\n"
                 "@P2 bra WAIT_LOOP;\n"
                 "WAIT_DONE:\n}" :: "r"(bar), "r"(parity) : "memory");
}
__device__ __forceinline__ void tma_2d(uint32_t dst, const void* map, uint32_t bar, int c0, int c1) {
    asm volatile("cp.async.bulk.tensor.2d.shared::cluster.global.mbarrier::complete_tx::bytes [%0], [%1, {%3, %4}], [%2];"
        :: "r"(dst), "l"(map), "r"(bar), "r"(c0), "r"(c1) : "memory");
}
__device__ __forceinline__ void tma_3d(uint32_t dst, const void* map, uint32_t bar, int c0, int c1, int c2) {
    asm volatile("cp.async.bulk.tensor.3d.shared::cluster.global.mbarrier::complete_tx::bytes [%0], [%1, {%3, %4, %5}], [%2];"
        :: "r"(dst), "l"(map), "r"(bar), "r"(c0), "r"(c1), "r"(c2) : "memory");
}
__device__ __forceinline__ void tma_4d(uint32_t dst, const void* map, uint32_t bar, int c0, int c1, int c2, int c3) {
    asm volatile("cp.async.bulk.tensor.4d.shared::cluster.global.mbarrier::complete_tx::bytes [%0], [%1, {%3, %4, %5, %6}], [%2];"
        :: "r"(dst), "l"(map), "r"(bar), "r"(c0), "r"(c1), "r"(c2), "r"(c3) : "memory");
}
__device__ __forceinline__ void bulk_g2s(uint32_t dst, const void* src, uint32_t bytes, uint32_t bar) {
    asm volatile("cp.async.bulk.shared::cluster.global.mbarrier::complete_tx::bytes [%0], [%1], %2, [%3];"
        :: "r"(dst), "l"(src), "r"(bytes), "r"(bar) : "memory");
}
__device__ __forceinline__ void prefetch_l2(const void* src, uint32_t bytes) {
    asm volatile("cp.async.bulk.prefetch.L2.global [%0], %1;" :: "l"(src), "r"(bytes) : "memory");
}
__device__ __forceinline__ bool elect_one() {
    uint32_t p;
    asm volatile("{\n.reg .pred P;\nelect.sync _|P, 0xffffffff;\nselp.u32 %0, 1, 0, P;\n}" : "=r"(p));
    return p != 0;
}
__device__ __forceinline__ void wgmma_fence() { asm volatile("wgmma.fence.sync.aligned;" ::: "memory"); }
__device__ __forceinline__ void wgmma_commit() { asm volatile("wgmma.commit_group.sync.aligned;" ::: "memory"); }
template <int N> __device__ __forceinline__ void wgmma_wait() { asm volatile("wgmma.wait_group.sync.aligned %0;" :: "n"(N) : "memory"); }
__device__ __forceinline__ void fence_async_smem() { asm volatile("fence.proxy.async.shared::cta;" ::: "memory"); }
__device__ __forceinline__ uint64_t desc_a(uint32_t addr) {
    return (uint64_t)((addr & 0x3FFFF) >> 4) | ((uint64_t)1 << 16) | ((uint64_t)(1024 >> 4) << 32) | ((uint64_t)1 << 62);
}
__device__ __forceinline__ uint64_t desc_b(uint32_t addr) {
    return (uint64_t)((addr & 0x3FFFF) >> 4) | ((uint64_t)(4096 >> 4) << 16) | ((uint64_t)(1024 >> 4) << 32) | ((uint64_t)1 << 62);
}
__device__ __forceinline__ uint32_t pack_bf16(float lo, float hi) {
    uint32_t r; asm("cvt.rn.bf16x2.f32 %0, %1, %2;" : "=r"(r) : "f"(hi), "f"(lo)); return r;
}
__device__ __forceinline__ uint32_t pack_bf16_relu(float lo, float hi) {
    uint32_t r; asm("cvt.rn.relu.bf16x2.f32 %0, %1, %2;" : "=r"(r) : "f"(hi), "f"(lo)); return r;
}
__device__ __forceinline__ uint32_t movmatrix(uint32_t a) {
    uint32_t d; asm volatile("movmatrix.sync.aligned.m8n8.trans.b16 %0, %1;" : "=r"(d) : "r"(a)); return d;
}
__device__ __forceinline__ void stmatrix_x4(uint32_t addr, uint32_t r0, uint32_t r1, uint32_t r2, uint32_t r3) {
    asm volatile("stmatrix.sync.aligned.m8n8.x4.shared.b16 [%0], {%1, %2, %3, %4};" :: "r"(addr), "r"(r0), "r"(r1), "r"(r2), "r"(r3) : "memory");
}
__device__ __forceinline__ uint4 lds128(uint32_t addr) {
    uint4 v; asm volatile("ld.shared.v4.b32 {%0, %1, %2, %3}, [%4];" : "=r"(v.x), "=r"(v.y), "=r"(v.z), "=r"(v.w) : "r"(addr) : "memory"); return v;
}
__device__ __forceinline__ void mma16816(float (&c)[4], uint32_t a0, uint32_t a1, uint32_t a2, uint32_t a3, uint32_t b0, uint32_t b1) {
    asm volatile("mma.sync.aligned.m16n8k16.row.col.f32.bf16.bf16.f32 {%0,%1,%2,%3}, {%4,%5,%6,%7}, {%8,%9}, {%0,%1,%2,%3};"
        : "+f"(c[0]), "+f"(c[1]), "+f"(c[2]), "+f"(c[3]) : "r"(a0), "r"(a1), "r"(a2), "r"(a3), "r"(b0), "r"(b1));
}
__device__ __forceinline__ void mma16816_c(float (&c)[4], uint32_t a0, uint32_t a1, uint32_t a2, uint32_t a3, uint32_t b0, uint32_t b1, float ci) {
    asm volatile("mma.sync.aligned.m16n8k16.row.col.f32.bf16.bf16.f32 {%0,%1,%2,%3}, {%4,%5,%6,%7}, {%8,%9}, {%10,%10,%10,%10};"
        : "=f"(c[0]), "=f"(c[1]), "=f"(c[2]), "=f"(c[3]) : "r"(a0), "r"(a1), "r"(a2), "r"(a3), "r"(b0), "r"(b1), "f"(ci));
}
__device__ __forceinline__ int opaque(int v) { asm volatile("" : "+r"(v)); return v; }
__device__ __forceinline__ float ex2(float x) { float y; asm("ex2.approx.ftz.f32 %0, %1;" : "=f"(y) : "f"(x)); return y; }
__device__ __forceinline__ unsigned ld_acquire(const unsigned* p) {
    unsigned v; asm volatile("ld.acquire.gpu.global.u32 %0, [%1];" : "=r"(v) : "l"(p) : "memory"); return v;
}
__device__ __forceinline__ void red_release(unsigned* p, unsigned v) {
    asm volatile("red.release.gpu.global.add.u32 [%0], %1;" :: "l"(p), "r"(v) : "memory");
}
__device__ __forceinline__ void wait_counter(const unsigned* p, unsigned target) {
    uint32_t n = 0;
    while ((int)(ld_acquire(p) - target) < 0) { if (++n > (1u << 20)) break; }
}
__device__ __forceinline__ uint4 ldg_weak(const uint4* p) {
    uint4 v; asm volatile("ld.global.L1::no_allocate.v4.b32 {%0, %1, %2, %3}, [%4];" : "=r"(v.x), "=r"(v.y), "=r"(v.z), "=r"(v.w) : "l"(p) : "memory"); return v;
}
__device__ __forceinline__ float bf_lo(uint32_t v) { return __uint_as_float(v << 16); }
__device__ __forceinline__ float bf_hi(uint32_t v) { return __uint_as_float(v & 0xFFFF0000u); }

__device__ __forceinline__ void wgmma_ss_n64(float (&d)[32], uint64_t da, uint64_t db, int scale_d) {
    asm volatile("{\n.reg .pred p;\nsetp.ne.b32 p, %34, 0;\n"
        "wgmma.mma_async.sync.aligned.m64n64k16.f32.bf16.bf16 {%0, %1, %2, %3, %4, %5, %6, %7, %8, %9, %10, %11, %12, %13, %14, %15, %16, %17, %18, %19, %20, %21, %22, %23, %24, %25, %26, %27, %28, %29, %30, %31}, %32, %33, p, 1, 1, 0, 1;\n}\n"
        : "+f"(d[0]), "+f"(d[1]), "+f"(d[2]), "+f"(d[3]), "+f"(d[4]), "+f"(d[5]), "+f"(d[6]), "+f"(d[7]), "+f"(d[8]), "+f"(d[9]), "+f"(d[10]), "+f"(d[11]), "+f"(d[12]), "+f"(d[13]), "+f"(d[14]), "+f"(d[15]), "+f"(d[16]), "+f"(d[17]), "+f"(d[18]), "+f"(d[19]), "+f"(d[20]), "+f"(d[21]), "+f"(d[22]), "+f"(d[23]), "+f"(d[24]), "+f"(d[25]), "+f"(d[26]), "+f"(d[27]), "+f"(d[28]), "+f"(d[29]), "+f"(d[30]), "+f"(d[31])
        : "l"(da), "l"(db), "r"(scale_d));
}
__device__ __forceinline__ void wgmma_ss_n128(float (&d)[64], uint64_t da, uint64_t db, int scale_d) {
    asm volatile("{\n.reg .pred p;\nsetp.ne.b32 p, %66, 0;\n"
        "wgmma.mma_async.sync.aligned.m64n128k16.f32.bf16.bf16 {%0, %1, %2, %3, %4, %5, %6, %7, %8, %9, %10, %11, %12, %13, %14, %15, %16, %17, %18, %19, %20, %21, %22, %23, %24, %25, %26, %27, %28, %29, %30, %31, %32, %33, %34, %35, %36, %37, %38, %39, %40, %41, %42, %43, %44, %45, %46, %47, %48, %49, %50, %51, %52, %53, %54, %55, %56, %57, %58, %59, %60, %61, %62, %63}, %64, %65, p, 1, 1, 0, 1;\n}\n"
        : "+f"(d[0]), "+f"(d[1]), "+f"(d[2]), "+f"(d[3]), "+f"(d[4]), "+f"(d[5]), "+f"(d[6]), "+f"(d[7]), "+f"(d[8]), "+f"(d[9]), "+f"(d[10]), "+f"(d[11]), "+f"(d[12]), "+f"(d[13]), "+f"(d[14]), "+f"(d[15]), "+f"(d[16]), "+f"(d[17]), "+f"(d[18]), "+f"(d[19]), "+f"(d[20]), "+f"(d[21]), "+f"(d[22]), "+f"(d[23]), "+f"(d[24]), "+f"(d[25]), "+f"(d[26]), "+f"(d[27]), "+f"(d[28]), "+f"(d[29]), "+f"(d[30]), "+f"(d[31]), "+f"(d[32]), "+f"(d[33]), "+f"(d[34]), "+f"(d[35]), "+f"(d[36]), "+f"(d[37]), "+f"(d[38]), "+f"(d[39]), "+f"(d[40]), "+f"(d[41]), "+f"(d[42]), "+f"(d[43]), "+f"(d[44]), "+f"(d[45]), "+f"(d[46]), "+f"(d[47]), "+f"(d[48]), "+f"(d[49]), "+f"(d[50]), "+f"(d[51]), "+f"(d[52]), "+f"(d[53]), "+f"(d[54]), "+f"(d[55]), "+f"(d[56]), "+f"(d[57]), "+f"(d[58]), "+f"(d[59]), "+f"(d[60]), "+f"(d[61]), "+f"(d[62]), "+f"(d[63])
        : "l"(da), "l"(db), "r"(scale_d));
}
__device__ __forceinline__ void wgmma_ss_n200(float (&d)[100], uint64_t da, uint64_t db, int scale_d) {
    asm volatile("{\n.reg .pred p;\nsetp.ne.b32 p, %102, 0;\n"
        "wgmma.mma_async.sync.aligned.m64n200k16.f32.bf16.bf16 {%0, %1, %2, %3, %4, %5, %6, %7, %8, %9, %10, %11, %12, %13, %14, %15, %16, %17, %18, %19, %20, %21, %22, %23, %24, %25, %26, %27, %28, %29, %30, %31, %32, %33, %34, %35, %36, %37, %38, %39, %40, %41, %42, %43, %44, %45, %46, %47, %48, %49, %50, %51, %52, %53, %54, %55, %56, %57, %58, %59, %60, %61, %62, %63, %64, %65, %66, %67, %68, %69, %70, %71, %72, %73, %74, %75, %76, %77, %78, %79, %80, %81, %82, %83, %84, %85, %86, %87, %88, %89, %90, %91, %92, %93, %94, %95, %96, %97, %98, %99}, %100, %101, p, 1, 1, 0, 1;\n}\n"
        : "+f"(d[0]), "+f"(d[1]), "+f"(d[2]), "+f"(d[3]), "+f"(d[4]), "+f"(d[5]), "+f"(d[6]), "+f"(d[7]), "+f"(d[8]), "+f"(d[9]), "+f"(d[10]), "+f"(d[11]), "+f"(d[12]), "+f"(d[13]), "+f"(d[14]), "+f"(d[15]), "+f"(d[16]), "+f"(d[17]), "+f"(d[18]), "+f"(d[19]), "+f"(d[20]), "+f"(d[21]), "+f"(d[22]), "+f"(d[23]), "+f"(d[24]), "+f"(d[25]), "+f"(d[26]), "+f"(d[27]), "+f"(d[28]), "+f"(d[29]), "+f"(d[30]), "+f"(d[31]), "+f"(d[32]), "+f"(d[33]), "+f"(d[34]), "+f"(d[35]), "+f"(d[36]), "+f"(d[37]), "+f"(d[38]), "+f"(d[39]), "+f"(d[40]), "+f"(d[41]), "+f"(d[42]), "+f"(d[43]), "+f"(d[44]), "+f"(d[45]), "+f"(d[46]), "+f"(d[47]), "+f"(d[48]), "+f"(d[49]), "+f"(d[50]), "+f"(d[51]), "+f"(d[52]), "+f"(d[53]), "+f"(d[54]), "+f"(d[55]), "+f"(d[56]), "+f"(d[57]), "+f"(d[58]), "+f"(d[59]), "+f"(d[60]), "+f"(d[61]), "+f"(d[62]), "+f"(d[63]), "+f"(d[64]), "+f"(d[65]), "+f"(d[66]), "+f"(d[67]), "+f"(d[68]), "+f"(d[69]), "+f"(d[70]), "+f"(d[71]), "+f"(d[72]), "+f"(d[73]), "+f"(d[74]), "+f"(d[75]), "+f"(d[76]), "+f"(d[77]), "+f"(d[78]), "+f"(d[79]), "+f"(d[80]), "+f"(d[81]), "+f"(d[82]), "+f"(d[83]), "+f"(d[84]), "+f"(d[85]), "+f"(d[86]), "+f"(d[87]), "+f"(d[88]), "+f"(d[89]), "+f"(d[90]), "+f"(d[91]), "+f"(d[92]), "+f"(d[93]), "+f"(d[94]), "+f"(d[95]), "+f"(d[96]), "+f"(d[97]), "+f"(d[98]), "+f"(d[99])
        : "l"(da), "l"(db), "r"(scale_d));
}
__device__ __forceinline__ void wgmma_ss_n224(float (&d)[112], uint64_t da, uint64_t db, int scale_d) {
    asm volatile("{\n.reg .pred p;\nsetp.ne.b32 p, %114, 0;\n"
        "wgmma.mma_async.sync.aligned.m64n224k16.f32.bf16.bf16 {%0, %1, %2, %3, %4, %5, %6, %7, %8, %9, %10, %11, %12, %13, %14, %15, %16, %17, %18, %19, %20, %21, %22, %23, %24, %25, %26, %27, %28, %29, %30, %31, %32, %33, %34, %35, %36, %37, %38, %39, %40, %41, %42, %43, %44, %45, %46, %47, %48, %49, %50, %51, %52, %53, %54, %55, %56, %57, %58, %59, %60, %61, %62, %63, %64, %65, %66, %67, %68, %69, %70, %71, %72, %73, %74, %75, %76, %77, %78, %79, %80, %81, %82, %83, %84, %85, %86, %87, %88, %89, %90, %91, %92, %93, %94, %95, %96, %97, %98, %99, %100, %101, %102, %103, %104, %105, %106, %107, %108, %109, %110, %111}, %112, %113, p, 1, 1, 0, 1;\n}\n"
        : "+f"(d[0]), "+f"(d[1]), "+f"(d[2]), "+f"(d[3]), "+f"(d[4]), "+f"(d[5]), "+f"(d[6]), "+f"(d[7]), "+f"(d[8]), "+f"(d[9]), "+f"(d[10]), "+f"(d[11]), "+f"(d[12]), "+f"(d[13]), "+f"(d[14]), "+f"(d[15]), "+f"(d[16]), "+f"(d[17]), "+f"(d[18]), "+f"(d[19]), "+f"(d[20]), "+f"(d[21]), "+f"(d[22]), "+f"(d[23]), "+f"(d[24]), "+f"(d[25]), "+f"(d[26]), "+f"(d[27]), "+f"(d[28]), "+f"(d[29]), "+f"(d[30]), "+f"(d[31]), "+f"(d[32]), "+f"(d[33]), "+f"(d[34]), "+f"(d[35]), "+f"(d[36]), "+f"(d[37]), "+f"(d[38]), "+f"(d[39]), "+f"(d[40]), "+f"(d[41]), "+f"(d[42]), "+f"(d[43]), "+f"(d[44]), "+f"(d[45]), "+f"(d[46]), "+f"(d[47]), "+f"(d[48]), "+f"(d[49]), "+f"(d[50]), "+f"(d[51]), "+f"(d[52]), "+f"(d[53]), "+f"(d[54]), "+f"(d[55]), "+f"(d[56]), "+f"(d[57]), "+f"(d[58]), "+f"(d[59]), "+f"(d[60]), "+f"(d[61]), "+f"(d[62]), "+f"(d[63]), "+f"(d[64]), "+f"(d[65]), "+f"(d[66]), "+f"(d[67]), "+f"(d[68]), "+f"(d[69]), "+f"(d[70]), "+f"(d[71]), "+f"(d[72]), "+f"(d[73]), "+f"(d[74]), "+f"(d[75]), "+f"(d[76]), "+f"(d[77]), "+f"(d[78]), "+f"(d[79]), "+f"(d[80]), "+f"(d[81]), "+f"(d[82]), "+f"(d[83]), "+f"(d[84]), "+f"(d[85]), "+f"(d[86]), "+f"(d[87]), "+f"(d[88]), "+f"(d[89]), "+f"(d[90]), "+f"(d[91]), "+f"(d[92]), "+f"(d[93]), "+f"(d[94]), "+f"(d[95]), "+f"(d[96]), "+f"(d[97]), "+f"(d[98]), "+f"(d[99]), "+f"(d[100]), "+f"(d[101]), "+f"(d[102]), "+f"(d[103]), "+f"(d[104]), "+f"(d[105]), "+f"(d[106]), "+f"(d[107]), "+f"(d[108]), "+f"(d[109]), "+f"(d[110]), "+f"(d[111])
        : "l"(da), "l"(db), "r"(scale_d));
}
template <int N> __device__ __forceinline__ void fence_acc(float (&d)[N]) {
#pragma unroll
    for (int i = 0; i < N; i++) asm volatile("" : "+f"(d[i]) :: "memory");
}

__device__ __forceinline__ void bulk_s2g(void* dst, uint32_t src, uint32_t bytes) {
    asm volatile("cp.async.bulk.global.shared::cta.bulk_group [%0], [%1], %2;" :: "l"(dst), "r"(src), "r"(bytes) : "memory");
}
__device__ __forceinline__ void sts128(uint32_t addr, uint4 v) {
    asm volatile("st.shared.v4.b32 [%0], {%1, %2, %3, %4};" :: "r"(addr), "r"(v.x), "r"(v.y), "r"(v.z), "r"(v.w) : "memory");
}
__device__ __forceinline__ void sum_partials(uint32_t sb, int ti, int tj, int lane) {
    for (;;) {
        uint32_t item = 0;
        if (lane == 0) asm volatile("atom.shared.add.u32 %0, [%1], 1;" : "=r"(item) : "r"(sb + ITEM_OFF) : "memory");
        item = __shfl_sync(0xffffffffu, item, 0);
        if (item >= 8) break;
        const uint4* p = g_part + (size_t)((ti * 8 + tj) * 8) * 1024 + item * 128 + lane;
        uint4 v[4][4];
#pragma unroll
        for (int s = 0; s < 4; s++)
#pragma unroll
            for (int n = 0; n < 4; n++) v[n][s] = ldg_weak(p + s * 1024 + n * 32);
#pragma unroll
        for (int n = 0; n < 4; n++) {
            float a[8];
#pragma unroll
            for (int e = 0; e < 8; e++) a[e] = 0.f;
#pragma unroll
            for (int s = 0; s < 4; s++) {
                a[0] += bf_lo(v[n][s].x); a[1] += bf_hi(v[n][s].x); a[2] += bf_lo(v[n][s].y); a[3] += bf_hi(v[n][s].y);
                a[4] += bf_lo(v[n][s].z); a[5] += bf_hi(v[n][s].z); a[6] += bf_lo(v[n][s].w); a[7] += bf_hi(v[n][s].w);
            }
            const uint32_t d = sb + HSUM_OFF + (item * 8 + n * 2) * 512 + lane * 16;
            sts128(d, make_uint4(__float_as_uint(a[0]), __float_as_uint(a[1]), __float_as_uint(a[2]), __float_as_uint(a[3])));
            sts128(d + 512, make_uint4(__float_as_uint(a[4]), __float_as_uint(a[5]), __float_as_uint(a[6]), __float_as_uint(a[7])));
        }
    }
    __syncwarp();
    if (lane == 0) mbar_arrive(sb + B_HSUM);
}

#define PWAIT() mbar_wait(sb + B_EMPTY + 8 * r.slot, r.phase)
#define CWAIT() do { if (!dry) mbar_wait(sb + B_FULL + 8 * r.slot, r.phase); } while (0)
template <bool B> struct BoolTag { static constexpr bool value = B; };
struct Ring {
    int slot; uint32_t phase;
    __device__ __forceinline__ void next() { if (++slot == RING) { slot = 0; phase ^= 1; } }
};

__global__ void __launch_bounds__(384, 1)
fused_kernel(const __grid_constant__ CUtensorMap map_x, const __grid_constant__ CUtensorMap map_qkv,
             const __grid_constant__ CUtensorMap map_w1, const __grid_constant__ CUtensorMap map_w2,
             const __grid_constant__ CUtensorMap map_wo, const __grid_constant__ CUtensorMap map_w1a,
             const __grid_constant__ CUtensorMap map_o,
             const __nv_bfloat16* __restrict__ gate_w, __nv_bfloat16* __restrict__ out,
             const uint8_t* __restrict__ w1p, const uint8_t* __restrict__ w2p, const uint8_t* __restrict__ wop)
{
    extern __shared__ __align__(1024) uint8_t smem_raw[];
    const uint32_t sb = smem_u32(smem_raw);
    const int tid = threadIdx.x, warp = tid >> 5, lane = tid & 31;
    const bool dry = blockIdx.x >= 128;
    const int ti = dry ? (int)(blockIdx.x & 1) * 2 : blockIdx.x >> 3, tj = blockIdx.x & 7;
    if (dry && warp >= 8) {
        asm volatile("setmaxnreg.dec.sync.aligned.u32 88;");
        return;
    }

    if (tid == 0 && !dry) { TSG(31); TSX(0); }
    if (tid == 320) {
        asm volatile("prefetch.tensormap [%0];" :: "l"(&map_x) : "memory");
        asm volatile("prefetch.tensormap [%0];" :: "l"(&map_qkv) : "memory");
        asm volatile("prefetch.tensormap [%0];" :: "l"(&map_w1) : "memory");
        asm volatile("prefetch.tensormap [%0];" :: "l"(&map_w1a) : "memory");
        asm volatile("prefetch.tensormap [%0];" :: "l"(&map_w2) : "memory");
        asm volatile("prefetch.tensormap [%0];" :: "l"(&map_wo) : "memory");
        asm volatile("prefetch.tensormap [%0];" :: "l"(&map_o) : "memory");
    }
    if (tid == 256) {
        mbar_init(sb + B_FULL, 1); mbar_init(sb + B_XFULL, 1);
        fence_async_smem();
        mbar_expect_tx(sb + B_XFULL, 16384);
        tma_2d(sb + X_OFF, &map_x, sb + B_XFULL, 0, ti * 128);
        mbar_expect_only(sb + B_FULL, 12288);
        tma_4d(sb + RING_OFF, &map_qkv, sb + B_FULL, 0, 0, tj, 0);
    }
    uint32_t gwv[N_QKV / 2];
    if (warp == 8) {
        const unsigned short* gws = reinterpret_cast<const unsigned short*>(gate_w);
#pragma unroll
        for (int n = 0; n < N_QKV / 2; n++) gwv[n] = (uint32_t)__ldg(gws + 64 * n + lane) | ((uint32_t)__ldg(gws + 64 * n + 32 + lane) << 16);
    }
    if (tid == 288) {
        for (int s = 1; s < RING; s++) mbar_init(sb + B_FULL + 8 * s, 1);
        for (int s = 0; s < RING; s++) mbar_init(sb + B_EMPTY + 8 * s, 8);
        for (int s = 1; s < 8; s++) mbar_init(sb + B_XFULL + 8 * s, 1);
        fence_async_smem();
    }
    if (tid == 352) {
        mbar_init(sb + B_HDEAD, 8); mbar_init(sb + B_EREADY, 1); mbar_init(sb + B_KVDONE, 8); mbar_init(sb + B_KVREADY, 1);
        mbar_init(sb + B_ODONE, 8); mbar_init(sb + B_WOFULL, 1); mbar_init(sb + B_HSUM, 3);
        mbar_init(sb + B_XDEAD, 8); mbar_init(sb + B_PREADY, 1); mbar_init(sb + B_SF, 1); mbar_init(sb + B_SF + 8, 1);
        for (int s = 0; s < 4; s++) mbar_init(sb + B_SQ + 8 * s, 8);
        asm volatile("st.shared.u32 [%0], %1;" :: "r"(sb + ITEM_OFF), "r"(0) : "memory");
        fence_async_smem();
    }
    if (!dry) __syncthreads();

    if (warp >= 8) {
        asm volatile("setmaxnreg.dec.sync.aligned.u32 88;");
        if (warp == 8) {
            Ring r{0, 1};
            const bool leader = elect_one();
#pragma unroll
            for (int n = 0; n < N_QKV; n++) {
                const uint32_t full = sb + B_FULL + 8 * r.slot, dst = sb + RING_OFF + r.slot * SLOT;
                if (n > 0) {
                    if (!(n & 1) && leader) {
                        mbar_expect_tx(sb + B_XFULL + 8 * (n >> 1), 16384);
                        tma_2d(sb + X_OFF + (n >> 1) * 16384, &map_x, sb + B_XFULL + 8 * (n >> 1), (n >> 1) * 64, ti * 128);
                    }
                    if (n >= RING) PWAIT();
                    if (leader) {
                        mbar_expect_only(full, 12288);
                        tma_4d(dst, &map_qkv, full, 0, 32 * n, tj, 0);
                    }
                }
                const uint32_t gv = (n & 1) ? (gwv[n >> 1] >> 16) : (gwv[n >> 1] & 0xFFFFu);
                asm volatile("st.shared.v4.b32 [%0], {%1, %2, %2, %2};" :: "r"(dst + 12288 + lane * 128 + ((lane & 7) << 4)), "r"(gv), "r"(0) : "memory");
                fence_async_smem();
                __syncwarp();
                if (leader) mbar_arrive(full);
                r.next();
            }
#pragma unroll 1
            for (int n = 0; n < N_FFN1; n++) {
                const uint32_t full = sb + B_FULL + 8 * r.slot, dst = sb + RING_OFF + r.slot * SLOT;
                PWAIT();
                if (leader) {
                    mbar_expect_tx(full, 16384);
                    tma_4d(dst, &map_w1a, full, 0, 32 * n, 0, tj);
                    tma_2d(dst + 3 * 4096, &map_w1, full, 224 * tj + 192, 32 * n);
                }
                r.next();
            }
            {
                int q = 0, rr = 0;
#pragma unroll 1
                for (int n = 0; n < N_FFN2; n++) {
                    const uint32_t full = sb + B_FULL + 8 * r.slot, dst = sb + RING_OFF + r.slot * SLOT;
                    PWAIT();
                    if (leader) mbar_expect_tx(full, 16384);
#pragma unroll
                    for (int h = 0; h < 2; h++) {
                        if (leader) tma_3d(dst + h * 8192, &map_w2, full, 0, 224 * tj + 32 * rr, 2 * q);
                        if (++rr == 7) { rr = 0; q++; }
                    }
                    r.next();
                }
            }
            mbar_wait(sb + B_KVREADY, 0);
            asm volatile("fence.proxy.async.global;" ::: "memory");
            {
                const int bbase = 8 * ti - 16, b0 = bbase < 0 ? 0 : bbase;
                const uint32_t bytes = (uint32_t)(8 * ti + 8 - b0) * 512;
#pragma unroll 1
                for (int m = 0; m < N_KV; m++) {
                    const uint32_t full = sb + B_FULL + 8 * r.slot, dst = sb + RING_OFF + r.slot * SLOT;
                    if (m == RING) {
                        mbar_wait(sb + B_HDEAD, 0);
                        if (leader) {
                            mbar_expect_tx(sb + B_WOFULL, 65536);
#pragma unroll
                            for (int e = 0; e < 2; e++) tma_2d(sb + X_OFF + e * 32768, &map_wo, sb + B_WOFULL, 64 * tj, 256 * e);
                        }
                    }
                    PWAIT();
                    if (leader) {
                        const uint4* src = ((m & 1) ? g_vf : g_kf) + ((tj * 4 + (m >> 1)) * 128 + b0) * 32;
                        mbar_expect_tx(full, bytes);
                        bulk_g2s(dst + (b0 - bbase) * 512, src, bytes, full);
                    }
                    r.next();
                }
            }
            {
                mbar_wait(sb + B_EREADY, 0);
                unsigned epoch; asm volatile("ld.shared.u32 %0, [%1];" : "=r"(epoch) : "r"(sb + EPOCH_OFF) : "memory");
                uint32_t pending = 0xFFu & ~(1u << tj), ready = 0;
                mbar_wait(sb + B_HSUM, 0);
#pragma unroll 1
                for (int m = 0; m < N_O; m++) {
                    const uint32_t full = sb + B_FULL + 8 * r.slot, dst = sb + RING_OFF + r.slot * SLOT;
                    PWAIT();
                    for (int it = 0; it < (1 << 20) && !ready; it++) {
                        bool ok = false;
                        if (lane < 8 && ((pending >> lane) & 1)) ok = (int)(ld_acquire(&g_ocnt[(ti * 8 + lane) * 32]) - (epoch + 1)) >= 0;
                        ready = __ballot_sync(0xffffffffu, ok);
                        if (!ready) __nanosleep(100);
                    }
                    const int js = ready ? __ffs(ready) - 1 : __ffs(pending) - 1;
                    pending &= ~(1u << js); ready &= ~(1u << js);
                    asm volatile("fence.proxy.async.global;" ::: "memory");
                    if (leader) {
                        asm volatile("st.shared.u32 [%0], %1;" :: "r"(sb + OSRC_OFF + 4 * m), "r"(js) : "memory");
                        mbar_expect_tx(full, 16384);
                        tma_2d(dst, &map_o, full, 64 * js, ti * 128);
                    }
                    r.next();
                }
            }
        } else if (warp == 9) {
            unsigned epoch = 0;
            if (lane == 0) {
                epoch = atomicAdd(&g_ticket, 1u) >> 7;
                asm volatile("st.shared.u32 [%0], %1;" :: "r"(sb + EPOCH_OFF), "r"(epoch) : "memory");
                mbar_arrive(sb + B_EREADY);
                mbar_wait(sb + B_XFULL + 8 * PF1_AT, 0);
                prefetch_l2(w1p + (size_t)blockIdx.x * 14336, 14336);
                mbar_wait(sb + B_XFULL + 8 * PF2_AT, 0);
                prefetch_l2(w2p + (size_t)blockIdx.x * 14336, 14336);
                prefetch_l2(wop + (size_t)blockIdx.x * 4096, 4096);
                mbar_wait(sb + B_KVDONE, 0);
                red_release(&g_kvcnt[blockIdx.x * 32], 1u);
            }
            epoch = __shfl_sync(0xffffffffu, epoch, 0);
            if (lane < 3 && ti - lane >= 0) wait_counter(&g_kvcnt[((ti - lane) * 8 + tj) * 32], epoch + 1);
            __syncwarp();
            if (lane == 0) mbar_arrive(sb + B_KVREADY);
            mbar_wait(sb + B_SQ + 24, 0);
            if (lane < 8) wait_counter(&g_pcnt[(ti * 8 + lane) * 32], epoch + 1);
            __syncwarp();
            if (lane == 0) { mbar_arrive(sb + B_PREADY); TSX(13); }
            sum_partials(sb, ti, tj, lane);
            if (lane == 0) TSX(14);
        } else {
            if (warp == 10) {
#pragma unroll 1
                for (int q = 0; q < 4; q++) {
                    mbar_wait(sb + B_SQ + 8 * q, 0);
                    if (lane < 16) {
                        uint4* d = g_part + (size_t)(((ti * 8 + 2 * q + (lane & 1)) * 8 + tj) * 8 + (lane >> 1)) * 128;
                        bulk_s2g(d, sb + STG_OFF + (q & 1) * 32768 + lane * 2048, 2048);
                        asm volatile("cp.async.bulk.commit_group;" ::: "memory");
                        asm volatile("cp.async.bulk.wait_group.read 0;" ::: "memory");
                    }
                    __syncwarp();
                    if (lane == 0) mbar_arrive(sb + B_SF + 8 * (q & 1));
                }
                asm volatile("cp.async.bulk.wait_group 0;" ::: "memory");
                asm volatile("fence.proxy.async.global;" ::: "memory");
                __syncwarp();
                if (lane == 0) { red_release(&g_pcnt[blockIdx.x * 32], 1u); TSX(12); }
            }
            mbar_wait(sb + B_PREADY, 0);
            sum_partials(sb, ti, tj, lane);
            if (warp == 11 && lane == 0) {
                mbar_wait(sb + B_ODONE, 0);
                red_release(&g_ocnt[blockIdx.x * 32], 1u);
            }
        }
    } else {
        asm volatile("setmaxnreg.inc.sync.aligned.u32 208;");
        const int wg = warp >> 2, g = lane >> 2, c = lane & 3;
        const uint32_t xa = sb + X_OFF + wg * 8192;
        Ring r{0, 0};
        const bool lane0 = lane == 0 && !dry;
        uint32_t qf[4][4];
        float g0, g1;
        TS(9);
        {
            float acc[100];
            int prev = 0;
            if (wg == 1) asm volatile("bar.sync 3, 256;" ::: "memory");
            for (int s = 0; s < (dry ? 4 : N_QKV); s++) {
                if (!(s & 1) && !dry) mbar_wait(sb + B_XFULL + 8 * (s >> 1), 0);
                CWAIT();
                if (s == 0) TS(1);
                if (s == 2) TS(28);
                if (s == 6) TS(29);
                if (s == 10) TS(20);
                const uint32_t bs = sb + RING_OFF + r.slot * SLOT, as = xa + (s >> 1) * 16384 + (s & 1) * 64;
                wgmma_fence();
                wgmma_ss_n200(acc, desc_a(as), desc_b(bs), s);
                wgmma_ss_n200(acc, desc_a(as + 32), desc_b(bs + 2048), 1);
                wgmma_commit();
                if (wg == 0 && s == LEAD1) asm volatile("bar.arrive 3, 256;" ::: "memory");
                if (s > 0) { wgmma_wait<1>(); if (lane0) mbar_arrive(sb + B_EMPTY + 8 * prev); }
                prev = r.slot; r.next();
            }
            wgmma_wait<0>();
            fence_acc(acc);
            if (lane0) mbar_arrive(sb + B_EMPTY + 8 * prev);
            TS(2);
            const int blk = ti * 8 + warp;
#pragma unroll
            for (int hh = 0; hh < 4; hh++) {
                const float* t0 = &acc[8 * hh]; const float* t1 = &acc[8 * hh + 4];
                qf[hh][0] = pack_bf16(t0[0], t0[1]); qf[hh][1] = pack_bf16(t0[2], t0[3]);
                qf[hh][2] = pack_bf16(t1[0], t1[1]); qf[hh][3] = pack_bf16(t1[2], t1[3]);
                const float* k0 = &acc[32 + 8 * hh]; const float* k1 = &acc[32 + 8 * hh + 4];
                uint4 kv;
                kv.x = pack_bf16(k0[0], k0[1]); kv.y = pack_bf16(k1[0], k1[1]);
                kv.z = pack_bf16(k0[2], k0[3]); kv.w = pack_bf16(k1[2], k1[3]);
                if (!dry) g_kf[((tj * 4 + hh) * 128 + blk) * 32 + lane] = kv;
                const float* v0 = &acc[64 + 8 * hh]; const float* v1 = &acc[64 + 8 * hh + 4];
                uint4 vv;
                vv.x = movmatrix(pack_bf16(v0[0], v0[1])); vv.y = movmatrix(pack_bf16(v0[2], v0[3]));
                vv.z = movmatrix(pack_bf16(v1[0], v1[1])); vv.w = movmatrix(pack_bf16(v1[2], v1[3]));
                if (!dry) g_vf[((tj * 4 + hh) * 128 + blk) * 32 + lane] = vv;
            }
            __syncwarp();
            if (lane0) mbar_arrive(sb + B_KVDONE);
            const float z0 = __shfl_sync(0xffffffffu, acc[96], lane & ~3), z1 = __shfl_sync(0xffffffffu, acc[98], lane & ~3);
            g0 = 1.f / (1.f + __expf(-z0)); g1 = 1.f / (1.f + __expf(-z1));
        }
        TS(3);
        const int wrow = (warp & 3) * 16;
        {
            float acc[112];
            int prev = 0;
            for (int s = 0; s < (dry ? 4 : N_FFN1); s++) {
                CWAIT();
                const uint32_t bs = sb + RING_OFF + r.slot * SLOT, as = xa + (s >> 1) * 16384 + (s & 1) * 64;
                wgmma_fence();
                wgmma_ss_n224(acc, desc_a(as), desc_b(bs), s);
                wgmma_ss_n224(acc, desc_a(as + 32), desc_b(bs + 2048), 1);
                wgmma_commit();
                if (s > 0) { wgmma_wait<1>(); if (lane0) mbar_arrive(sb + B_EMPTY + 8 * prev); }
                prev = r.slot; r.next();
            }
            wgmma_wait<0>();
            fence_acc(acc);
            if (lane0) { mbar_arrive(sb + B_EMPTY + 8 * prev); mbar_arrive(sb + B_XDEAD); }
            TS(4);
            const float s0 = 1.f - g0, s1 = 1.f - g1;
            asm volatile("bar.sync %0, 128;" :: "r"(1 + wg) : "memory");
            const uint32_t strow = xa + (wrow + ((lane >> 3) & 1) * 8 + (lane & 7)) * 128;
#pragma unroll
            for (int p = 0; p < 14; p++) {
                const int nt = 2 * p + (lane >> 4);
                const float* a = &acc[8 * p];
                stmatrix_x4(strow + (p >> 2) * 16384 + (((nt & 7) ^ (lane & 7)) << 4),
                            pack_bf16_relu(a[0] * s0, a[1] * s0), pack_bf16_relu(a[2] * s1, a[3] * s1),
                            pack_bf16_relu(a[4] * s0, a[5] * s0), pack_bf16_relu(a[6] * s1, a[7] * s1));
            }
        }
        TS(5);
        {
            fence_async_smem();
            asm volatile("bar.sync %0, 128;" :: "r"(1 + wg) : "memory");
            float accA[64], accB[64];
            auto epilogue = [&](float (&acc)[64], int q) {
                fence_acc(acc);
                const uint32_t st = sb + STG_OFF + (q & 1) * 32768 + warp * 4096;
                if (q == 0 && !dry) mbar_wait(sb + B_XDEAD, 0);
                if (q >= 2 && !dry) mbar_wait(sb + B_SF + 8 * (q & 1), 0);
#pragma unroll
                for (int t2 = 0; t2 < 8; t2++) {
                    uint4 v;
                    v.x = pack_bf16(acc[8 * t2 + 0], acc[8 * t2 + 1]); v.y = pack_bf16(acc[8 * t2 + 2], acc[8 * t2 + 3]);
                    v.z = pack_bf16(acc[8 * t2 + 4], acc[8 * t2 + 5]); v.w = pack_bf16(acc[8 * t2 + 6], acc[8 * t2 + 7]);
                    sts128(st + t2 * 512 + lane * 16, v);
                }
                fence_async_smem();
                __syncwarp();
                if (lane0) mbar_arrive(sb + B_SQ + 8 * q);
            };
            int rel = r.slot;
#pragma unroll
            for (int m = 0; m < N_FFN2; m++) {
                CWAIT();
                wgmma_fence();
#pragma unroll
                for (int h = 0; h < 2; h++) {
                    const int u = 2 * m + h, q = u / 7, rr = u % 7;
                    const uint32_t bs = sb + RING_OFF + r.slot * SLOT + h * 8192;
                    const uint32_t as = xa + (rr >> 1) * 16384 + (rr & 1) * 64;
                    if (!(q & 1)) {
                        wgmma_ss_n128(accA, desc_a(as), desc_b(bs), rr);
                        wgmma_ss_n128(accA, desc_a(as + 32), desc_b(bs + 2048), 1);
                    } else {
                        wgmma_ss_n128(accB, desc_a(as), desc_b(bs), rr);
                        wgmma_ss_n128(accB, desc_a(as + 32), desc_b(bs + 2048), 1);
                    }
                }
                wgmma_commit();
                r.next();
                wgmma_wait<1>();
                if (m > 0) {
                    if (lane0) mbar_arrive(sb + B_EMPTY + 8 * rel);
                    if (++rel == RING) rel = 0;
                }
                if (m == 4) { TS(25); epilogue(accA, 0); }
                if (m == 7) { TS(26); epilogue(accB, 1); }
                if (m == 11) { TS(27); epilogue(accA, 2); }
            }
            wgmma_wait<0>();
            if (lane0) { mbar_arrive(sb + B_EMPTY + 8 * rel); mbar_arrive(sb + B_HDEAD); }
            epilogue(accB, 3);
        }
        TS(6);
        {
            const float SC = 0.25f * 1.4426950408889634f;
            const int gb0 = 8 * ti - 16 + warp;
            int slotK = 0, slotV = 0;
            const uint32_t ostore = sb + OWN_OFF + (warp * 16 + ((lane >> 3) & 1) * 8 + (lane & 7)) * 128;
            uint32_t* odst = reinterpret_cast<uint32_t*>(g_o + (size_t)(ti * 128 + warp * 16 + g) * 512 + tj * 64 + ((lane & 1) ? 8 : 0) + (lane & 2) * 2);
#define NHEADS (dry ? 2 : 4)
#define ATT_KWAIT(kb) do { slotK = r.slot; CWAIT(); kb = sb + RING_OFF + slotK * SLOT + warp * 512 + lane * 16; r.next(); } while (0)
#define ATT_VWAIT(vb) do { slotV = r.slot; CWAIT(); vb = sb + RING_OFF + slotV * SLOT + warp * 512 + lane * 16; r.next(); TS(21 + hh); } while (0)
#define ATT_KREL() do { __syncwarp(); if (lane0) mbar_arrive(sb + B_EMPTY + 8 * slotK); } while (0)
#define ATT_VREL() do { __syncwarp(); if (lane0) mbar_arrive(sb + B_EMPTY + 8 * slotV); } while (0)
#define ATT_NEXTQ(h) do { \
                if ((h) == 1) { q0 = qf[1][0]; q1 = qf[1][1]; q2 = qf[1][2]; q3 = qf[1][3]; } \
                else if ((h) == 2) { q0 = qf[2][0]; q1 = qf[2][1]; q2 = qf[2][2]; q3 = qf[2][3]; } \
                else { q0 = qf[3][0]; q1 = qf[3][1]; q2 = qf[3][2]; q3 = qf[3][3]; } } while (0)
#define ATT_STORE(h, r0, r1, r2, r3) do { \
                if ((h) == 0 && !dry) mbar_wait(sb + B_SF, 1);        \
                stmatrix_x4(ostore + (((2 * (h) + (lane >> 4)) ^ (lane & 7)) << 4), r0, r1, r2, r3); \
                const bool odd = lane & 1; \
                const uint32_t sl = __shfl_xor_sync(0xffffffffu, odd ? (r0) : (r2), 1), sh = __shfl_xor_sync(0xffffffffu, odd ? (r1) : (r3), 1); \
                if (!dry) *reinterpret_cast<uint2*>(odst + 8 * (h)) = odd ? make_uint2(sl, r2) : make_uint2(r0, sl); \
                if (!dry) *reinterpret_cast<uint2*>(odst + 8 * (h) + 8 * 256) = odd ? make_uint2(sh, r3) : make_uint2(r1, sh); \
                } while (0)
            auto attention = [&](auto masked_tag) {
            constexpr bool MASKED = decltype(masked_tag)::value;
            const float NEG = -INFINITY;
            const uint32_t ONES = 0x3F803F80u;
            float sa[8][2][4];
            float o[2][4], ls[4];
            float m0, m1;
            uint32_t q0 = qf[0][0], q1 = qf[0][1], q2 = qf[0][2], q3 = qf[0][3];
            auto qk = [&](float (&s)[8][2][4], int ps, int t, uint32_t kbase, bool merged) {
                if (merged) {
                    const uint4 kd = lds128(kbase + 16 * 512);
                    const uint4 kf = lds128(kbase);
                    float f[2][4];
                    const float ci = (!MASKED || opaque(gb0) >= 0) ? 0.f : NEG;
                    mma16816_c(s[0][0], q0, q1, q2, q3, kd.x, kd.y, 0.f);
                    mma16816_c(s[0][1], q0, q1, q2, q3, kd.z, kd.w, 0.f);
                    mma16816_c(f[0], q0, q1, q2, q3, kf.x, kf.y, ci);
                    mma16816_c(f[1], q0, q1, q2, q3, kf.z, kf.w, ci);
#pragma unroll
                    for (int u = 0; u < 2; u++)
#pragma unroll
                        for (int e = 0; e < 4; e++) {
                            const int row = g + 8 * (e >> 1), col = 8 * u + 2 * c + (e & 1);
                            s[0][u][e] = (col > row) ? f[u][e] : s[0][u][e];
                        }
                } else {
                    const uint4 kf = lds128(kbase + (8 * ps + t) * 512);
                    const float ci = (!MASKED || opaque(gb0) + 8 * ps + t >= 0) ? 0.f : NEG;
                    mma16816_c(s[t][0], q0, q1, q2, q3, kf.x, kf.y, ci);
                    mma16816_c(s[t][1], q0, q1, q2, q3, kf.z, kf.w, ci);
                }
            };
            auto rowmax = [&](float (&s)[8][2][4], float b0, float b1, float& n0, float& n1) {
                int i0 = __float_as_int(b0), i1 = __float_as_int(b1);
#pragma unroll
                for (int t = 0; t < 8; t++)
#pragma unroll
                    for (int u = 0; u < 2; u++) {
                        i0 = __vimax3_s32(i0, __float_as_int(s[t][u][0]), __float_as_int(s[t][u][1]));
                        i1 = __vimax3_s32(i1, __float_as_int(s[t][u][2]), __float_as_int(s[t][u][3]));
                    }
                i0 = max(i0, __shfl_xor_sync(0xffffffffu, i0, 1)); i1 = max(i1, __shfl_xor_sync(0xffffffffu, i1, 1));
                i0 = max(i0, __shfl_xor_sync(0xffffffffu, i0, 2)); i1 = max(i1, __shfl_xor_sync(0xffffffffu, i1, 2));
                n0 = __int_as_float(i0); n1 = __int_as_float(i1);
                if (__any_sync(0xffffffffu, (i0 | i1) < 0)) {
                    asm volatile("" ::: "memory");
                    n0 = b0; n1 = b1;
#pragma unroll
                    for (int t = 0; t < 8; t++)
#pragma unroll
                        for (int u = 0; u < 2; u++) {
                            n0 = fmaxf(n0, fmaxf(s[t][u][0], s[t][u][1]));
                            n1 = fmaxf(n1, fmaxf(s[t][u][2], s[t][u][3]));
                        }
                    n0 = fmaxf(n0, __shfl_xor_sync(0xffffffffu, n0, 1)); n1 = fmaxf(n1, __shfl_xor_sync(0xffffffffu, n1, 1));
                    n0 = fmaxf(n0, __shfl_xor_sync(0xffffffffu, n0, 2)); n1 = fmaxf(n1, __shfl_xor_sync(0xffffffffu, n1, 2));
                }
            };
            auto pv = [&](const float (&p)[2][4], uint32_t vaddr) {
                const uint4 vf = lds128(vaddr);
                const uint32_t a0 = pack_bf16(p[0][0], p[0][1]), a1 = pack_bf16(p[0][2], p[0][3]);
                const uint32_t a2 = pack_bf16(p[1][0], p[1][1]), a3 = pack_bf16(p[1][2], p[1][3]);
                mma16816(o[0], a0, a1, a2, a3, vf.x, vf.y);
                mma16816(o[1], a0, a1, a2, a3, vf.z, vf.w);
                mma16816(ls, a0, a1, a2, a3, ONES, ONES);
            };
            auto expv = [&](float (&s)[8][2][4], int ps, int t, float mc0, float mc1, uint32_t vbase, bool merged) {
                float p[2][4];
#pragma unroll
                for (int u = 0; u < 2; u++) {
                    p[u][0] = ex2(fmaf(s[t][u][0], SC, -mc0)); p[u][1] = ex2(fmaf(s[t][u][1], SC, -mc0));
                    p[u][2] = ex2(fmaf(s[t][u][2], SC, -mc1)); p[u][3] = ex2(fmaf(s[t][u][3], SC, -mc1));
                }
                if (merged) {
                    float pd[2][4], pf[2][4];
#pragma unroll
                    for (int u = 0; u < 2; u++)
#pragma unroll
                        for (int e = 0; e < 4; e++) {
                            const int row = g + 8 * (e >> 1), col = 8 * u + 2 * c + (e & 1);
                            pf[u][e] = (col > row) ? p[u][e] : 0.f;
                            pd[u][e] = (col > row) ? 0.f : p[u][e];
                        }
                    pv(pd, vbase + 16 * 512);
                    pv(pf, vbase);
                } else {
                    pv(p, vbase + (8 * ps + t) * 512);
                }
            };
            uint32_t kbase = 0, vbase = 0;
#pragma unroll 1
            for (int hh = 0; hh < NHEADS; hh++) {
                ATT_KWAIT(kbase);
                if (hh > 0) ATT_NEXTQ(hh);
#pragma unroll
                for (int ps = 0; ps < 2; ps++) {
#pragma unroll
                    for (int t = 0; t < 8; t++) qk(sa, ps, t, kbase, ps == 0 && t == 0);
                    if (ps == 1) ATT_KREL();
                    float n0, n1;
                    rowmax(sa, ps ? m0 : NEG, ps ? m1 : NEG, n0, n1);
                    if (ps == 0) {
                        ATT_VWAIT(vbase);
#pragma unroll
                        for (int e = 0; e < 4; e++) { o[0][e] = 0.f; o[1][e] = 0.f; ls[e] = 0.f; }
                    } else {
                        const float a0 = ex2((m0 - n0) * SC), a1 = ex2((m1 - n1) * SC);
                        ls[0] *= a0; ls[2] *= a1;
                        o[0][0] *= a0; o[0][1] *= a0; o[1][0] *= a0; o[1][1] *= a0;
                        o[0][2] *= a1; o[0][3] *= a1; o[1][2] *= a1; o[1][3] *= a1;
                    }
                    m0 = n0; m1 = n1;
                    const float mc0 = n0 * SC, mc1 = n1 * SC;
#pragma unroll
                    for (int t = 0; t < 8; t++) expv(sa, ps, t, mc0, mc1, vbase, ps == 0 && t == 0);
                }
                ATT_VREL();
                const float f0 = __fdividef(g0, ls[0]), f1 = __fdividef(g1, ls[2]);
                ATT_STORE(hh, pack_bf16(o[0][0] * f0, o[0][1] * f0), pack_bf16(o[0][2] * f1, o[0][3] * f1),
                              pack_bf16(o[1][0] * f0, o[1][1] * f0), pack_bf16(o[1][2] * f1, o[1][3] * f1));
            }
            };
            if (ti >= 2) attention(BoolTag<false>{}); else attention(BoolTag<true>{});
            fence_async_smem();
            __syncwarp();
            if (lane0) mbar_arrive(sb + B_ODONE);
        }
        TS(7);
        {
            float acc[32];
            uint4 pv[4][4];
            if (!dry) mbar_wait(sb + B_PREADY, 0);
            {
                const uint4* p = g_part + (size_t)((ti * 8 + tj) * 8 + 4) * 1024 + warp * 128 + lane;
#pragma unroll
                for (int s = 0; s < 4; s++)
#pragma unroll
                    for (int n = 0; n < 4; n++) pv[n][s] = dry ? make_uint4(0u, 0u, 0u, 0u) : ldg_weak(p + s * 1024 + n * 32);
            }
            if (!dry) mbar_wait(sb + B_WOFULL, 0);
            if (!dry) mbar_wait(sb + B_ODONE, 0);
            TS(15);
            wgmma_fence();
#pragma unroll
            for (int k = 0; k < 4; k++) wgmma_ss_n64(acc, desc_a(sb + OWN_OFF + wg * 8192 + 32 * k), desc_b(sb + X_OFF + tj * 8192 + 2048 * k), k);
            wgmma_commit();
            TS(16);
#pragma unroll 1
            for (int m = 0; m < N_O; m++) {
                CWAIT();
                uint32_t js; asm volatile("ld.shared.u32 %0, [%1];" : "=r"(js) : "r"(sb + OSRC_OFF + 4 * m) : "memory");
                const uint32_t as = sb + RING_OFF + r.slot * SLOT + wg * 8192;
                const uint32_t bs = sb + X_OFF + (js & 7) * 8192;
                wgmma_fence();
#pragma unroll
                for (int k = 0; k < 4; k++) wgmma_ss_n64(acc, desc_a(as + 32 * k), desc_b(bs + 2048 * k), 1);
                wgmma_commit();
                if (m == 0) { wgmma_wait<0>(); if (lane0) mbar_arrive(sb + B_EMPTY + 8 * r.slot); }
                r.next();
            }
            float base[32];
            if (!dry) mbar_wait(sb + B_HSUM, 0);
#pragma unroll
            for (int n = 0; n < 4; n++) {
                const uint4 u0 = lds128(sb + HSUM_OFF + (warp * 8 + 2 * n) * 512 + lane * 16), u1 = lds128(sb + HSUM_OFF + (warp * 8 + 2 * n + 1) * 512 + lane * 16);
                float* a = &base[8 * n];
                a[0] = __uint_as_float(u0.x); a[1] = __uint_as_float(u0.y); a[2] = __uint_as_float(u0.z); a[3] = __uint_as_float(u0.w);
                a[4] = __uint_as_float(u1.x); a[5] = __uint_as_float(u1.y); a[6] = __uint_as_float(u1.z); a[7] = __uint_as_float(u1.w);
#pragma unroll
                for (int s = 0; s < 4; s++) {
                    a[0] += bf_lo(pv[n][s].x); a[1] += bf_hi(pv[n][s].x); a[2] += bf_lo(pv[n][s].y); a[3] += bf_hi(pv[n][s].y);
                    a[4] += bf_lo(pv[n][s].z); a[5] += bf_hi(pv[n][s].z); a[6] += bf_lo(pv[n][s].w); a[7] += bf_hi(pv[n][s].w);
                }
            }
            fence_acc(base);
            wgmma_wait<0>();
            fence_acc(acc);
            TS(17);
#pragma unroll
            for (int k = 0; k < 32; k++) acc[k] += base[k];
            __nv_bfloat16* o = out + (size_t)(ti * 128 + warp * 16 + g) * 512 + tj * 64 + ((lane & 1) ? 8 : 0) + (lane & 2) * 2;
            const bool odd = lane & 1;
#pragma unroll
            for (int t2 = 0; t2 < 4; t2++) {
                const uint32_t lo0 = pack_bf16(acc[8 * t2 + 0], acc[8 * t2 + 1]), hi0 = pack_bf16(acc[8 * t2 + 2], acc[8 * t2 + 3]);
                const uint32_t lo1 = pack_bf16(acc[8 * t2 + 4], acc[8 * t2 + 5]), hi1 = pack_bf16(acc[8 * t2 + 6], acc[8 * t2 + 7]);
                const uint32_t sl = __shfl_xor_sync(0xffffffffu, odd ? lo0 : lo1, 1), sh = __shfl_xor_sync(0xffffffffu, odd ? hi0 : hi1, 1);
                if (!dry) *reinterpret_cast<uint2*>(o + 16 * t2) = odd ? make_uint2(sl, lo1) : make_uint2(lo0, sl);
                if (!dry) *reinterpret_cast<uint2*>(o + 16 * t2 + 8 * 512) = odd ? make_uint2(sh, hi1) : make_uint2(hi0, sh);
            }
            if (tid == 0 && !dry) TSG(30);
        }
        TS(8);
    }
}

typedef CUresult (*PFN_encodeTiled)(CUtensorMap*, CUtensorMapDataType, cuuint32_t, void*, const cuuint64_t*, const cuuint64_t*,
                                    const cuuint32_t*, const cuuint32_t*, CUtensorMapInterleave, CUtensorMapSwizzle,
                                    CUtensorMapL2promotion, CUtensorMapFloatOOBfill);

void make_map(PFN_encodeTiled enc, CUtensorMap* m, const void* base, int rank, const cuuint64_t* dims, const cuuint64_t* strides, const cuuint32_t* box) {
    cuuint32_t es[5] = {1, 1, 1, 1, 1};
    enc(m, CU_TENSOR_MAP_DATA_TYPE_BFLOAT16, (cuuint32_t)rank, const_cast<void*>(base), dims, strides, box, es,
        CU_TENSOR_MAP_INTERLEAVE_NONE, CU_TENSOR_MAP_SWIZZLE_128B, CU_TENSOR_MAP_L2_PROMOTION_L2_256B, CU_TENSOR_MAP_FLOAT_OOB_FILL_NONE);
}

}

extern "C" void kernel_launch(void* const* d_in, const int* in_sizes, int n_in, void* d_out, int out_size) {
    (void)in_sizes; (void)n_in; (void)out_size;
    const void* x = d_in[0]; const void* wqkv = d_in[1]; const void* wo = d_in[2];
    const void* w1 = d_in[4]; const void* w2 = d_in[5]; const void* gate_w = d_in[6];
    static PFN_encodeTiled enc = nullptr;
    if (!enc) {
        void* fn = nullptr; cudaDriverEntryPointQueryResult st;
        cudaGetDriverEntryPoint("cuTensorMapEncodeTiled", &fn, cudaEnableDefault, &st);
        enc = (PFN_encodeTiled)fn;
        cudaFuncSetAttribute(fused_kernel, cudaFuncAttributeMaxDynamicSharedMemorySize, SMEM_BYTES);
    }
    CUtensorMap mx, mqkv, mw1, mw2, mwo, mw1a, mo;
    void* optr = nullptr;
    cudaGetSymbolAddress(&optr, g_o);
    { cuuint64_t d[2] = {512, 2048}, s[1] = {1024}; cuuint32_t b[2] = {64, 128}; make_map(enc, &mo, optr, 2, d, s, b); }
    { cuuint64_t d[4] = {64, 512, 3, 8}, s[3] = {3584, 128, 448}; cuuint32_t b[4] = {64, 32, 3, 1}; make_map(enc, &mw1a, w1, 4, d, s, b); }
    { cuuint64_t d[2] = {512, 2048}, s[1] = {1024}; cuuint32_t b[2] = {64, 128}; make_map(enc, &mx, x, 2, d, s, b); }
    { cuuint64_t d[4] = {64, 512, 8, 3}, s[3] = {3072, 128, 1024}; cuuint32_t b[4] = {64, 32, 1, 3}; make_map(enc, &mqkv, wqkv, 4, d, s, b); }
    { cuuint64_t d[2] = {1792, 512}, s[1] = {3584}; cuuint32_t b[2] = {64, 32}; make_map(enc, &mw1, w1, 2, d, s, b); }
    { cuuint64_t d[3] = {64, 1792, 8}, s[2] = {1024, 128}; cuuint32_t b[3] = {64, 32, 2}; make_map(enc, &mw2, w2, 3, d, s, b); }
    { cuuint64_t d[2] = {512, 512}, s[1] = {1024}; cuuint32_t b[2] = {64, 256}; make_map(enc, &mwo, wo, 2, d, s, b); }
    fused_kernel<<<NCTA, 384, SMEM_BYTES, cudaStreamPerThread>>>(mx, mqkv, mw1, mw2, mwo, mw1a, mo, (const __nv_bfloat16*)gate_w, (__nv_bfloat16*)d_out,
                                           (const uint8_t*)w1, (const uint8_t*)w2, (const uint8_t*)wo);
}
```

```cpp
#include <cuda_runtime.h>
#include <cuda_bf16.h>
#include <cuda.h>
#include <stdint.h>

namespace {

#define PF1_AT 1
#define PF2_AT 5
#define LEAD1 1
constexpr int RING = 6;
constexpr int SLOT = 16384;
constexpr uint32_t X_OFF = 0;
constexpr uint32_t STG_OFF = X_OFF + 4 * 16384;
constexpr uint32_t RING_OFF = 131072;
constexpr uint32_t BAR_OFF = RING_OFF + RING * SLOT;
constexpr uint32_t B_FULL = BAR_OFF, B_EMPTY = BAR_OFF + 64, B_XFULL = BAR_OFF + 128, B_HDEAD = BAR_OFF + 192,
                   B_EREADY = BAR_OFF + 200, B_KVDONE = BAR_OFF + 208, B_ODONE = BAR_OFF + 224,
                   B_KVREADY = BAR_OFF + 232, B_WOFULL = BAR_OFF + 240, B_HSUM = BAR_OFF + 248, B_PREADY = BAR_OFF + 264,
                   B_SQ = BAR_OFF + 272, B_SF = BAR_OFF + 304, B_XDEAD = BAR_OFF + 320;
constexpr uint32_t EPOCH_OFF = BAR_OFF + 256, ITEM_OFF = BAR_OFF + 260, OSRC_OFF = BAR_OFF + 384;
constexpr uint32_t OWN_OFF = X_OFF + 4 * 16384;
constexpr uint32_t HSUM_OFF = X_OFF + 6 * 16384;
constexpr uint32_t SMEM_BYTES = BAR_OFF + 1024;

constexpr int N_QKV = 16, N_FFN1 = 16, N_FFN2 = 14, N_KV = 8, N_O = 7;

__device__ uint4 g_kf[32 * 128 * 32];
__device__ uint4 g_vf[32 * 128 * 32];
__device__ uint4 g_part[16 * 8 * 8 * 8 * 4 * 32];
__device__ __nv_bfloat16 g_o[2048 * 512];
__device__ unsigned g_ticket;
__device__ unsigned g_kvcnt[128 * 32];
__device__ unsigned g_pcnt[128 * 32];
__device__ unsigned g_ocnt[128 * 32];
#define TS(k) do {} while (0)
#define TS2(k) do {} while (0)
#define TS2X(k) do {} while (0)
#define TSX(k) do {} while (0)
#define TSG(k) do {} while (0)

__device__ __forceinline__ uint32_t smem_u32(const void* p) { return (uint32_t)__cvta_generic_to_shared(p); }
__device__ __forceinline__ void mbar_init(uint32_t bar, uint32_t cnt) { asm volatile("mbarrier.init.shared::cta.b64 [%0], %1;" :: "r"(bar), "r"(cnt) : "memory"); }
__device__ __forceinline__ void mbar_expect_tx(uint32_t bar, uint32_t bytes) { asm volatile("mbarrier.arrive.expect_tx.shared::cta.b64 _, [%0], %1;" :: "r"(bar), "r"(bytes) : "memory"); }
__device__ __forceinline__ void mbar_expect_only(uint32_t bar, uint32_t bytes) { asm volatile("mbarrier.expect_tx.relaxed.cta.shared::cta.b64 [%0], %1;" :: "r"(bar), "r"(bytes) : "memory"); }
__device__ __forceinline__ void mbar_arrive(uint32_t bar) { asm volatile("mbarrier.arrive.shared::cta.b64 _, [%0];" :: "r"(bar) : "memory"); }
__device__ __forceinline__ void mbar_wait(uint32_t bar, uint32_t parity) {
    asm volatile("{\n.reg .pred P1, P2;\n.reg .u32 n;\nmov.u32 n, 0;\n"
                 "WAIT_LOOP:\n"
                 "mbarrier.try_wait.parity.shared::cta.b64 P1, [%0], %1;\n"
                 "@P1 bra WAIT_DONE;\n"
                 "add.u32 n, n, 1;\n"
                 "setp.lt.u32 P2, n, 0x400000;\n"
                 "@P2 bra WAIT_LOOP;\n"
                 "WAIT_DONE:\n}" :: "r"(bar), "r"(parity) : "memory");
}
__device__ __forceinline__ void tma_2d(uint32_t dst, const void* map, uint32_t bar, int c0, int c1) {
    asm volatile("cp.async.bulk.tensor.2d.shared::cluster.global.mbarrier::complete_tx::bytes [%0], [%1, {%3, %4}], [%2];"
        :: "r"(dst), "l"(map), "r"(bar), "r"(c0), "r"(c1) : "memory");
}
__device__ __forceinline__ void tma_3d(uint32_t dst, const void* map, uint32_t bar, int c0, int c1, int c2) {
    asm volatile("cp.async.bulk.tensor.3d.shared::cluster.global.mbarrier::complete_tx::bytes [%0], [%1, {%3, %4, %5}], [%2];"
        :: "r"(dst), "l"(map), "r"(bar), "r"(c0), "r"(c1), "r"(c2) : "memory");
}
__device__ __forceinline__ void tma_4d(uint32_t dst, const void* map, uint32_t bar, int c0, int c1, int c2, int c3) {
    asm volatile("cp.async.bulk.tensor.4d.shared::cluster.global.mbarrier::complete_tx::bytes [%0], [%1, {%3, %4, %5, %6}], [%2];"
        :: "r"(dst), "l"(map), "r"(bar), "r"(c0), "r"(c1), "r"(c2), "r"(c3) : "memory");
}
__device__ __forceinline__ void bulk_g2s(uint32_t dst, const void* src, uint32_t bytes, uint32_t bar) {
    asm volatile("cp.async.bulk.shared::cluster.global.mbarrier::complete_tx::bytes [%0], [%1], %2, [%3];"
        :: "r"(dst), "l"(src), "r"(bytes), "r"(bar) : "memory");
}
__device__ __forceinline__ void prefetch_l2(const void* src, uint32_t bytes) {
    asm volatile("cp.async.bulk.prefetch.L2.global [%0], %1;" :: "l"(src), "r"(bytes) : "memory");
}
__device__ __forceinline__ bool elect_one() {
    uint32_t p;
    asm volatile("{\n.reg .pred P;\nelect.sync _|P, 0xffffffff;\nselp.u32 %0, 1, 0, P;\n}" : "=r"(p));
    return p != 0;
}
__device__ __forceinline__ void wgmma_fence() { asm volatile("wgmma.fence.sync.aligned;" ::: "memory"); }
__device__ __forceinline__ void wgmma_commit() { asm volatile("wgmma.commit_group.sync.aligned;" ::: "memory"); }
template <int N> __device__ __forceinline__ void wgmma_wait() { asm volatile("wgmma.wait_group.sync.aligned %0;" :: "n"(N) : "memory"); }
__device__ __forceinline__ void fence_async_smem() { asm volatile("fence.proxy.async.shared::cta;" ::: "memory"); }
__device__ __forceinline__ uint64_t desc_a(uint32_t addr) {
    return (uint64_t)((addr & 0x3FFFF) >> 4) | ((uint64_t)1 << 16) | ((uint64_t)(1024 >> 4) << 32) | ((uint64_t)1 << 62);
}
__device__ __forceinline__ uint64_t desc_b(uint32_t addr) {
    return (uint64_t)((addr & 0x3FFFF) >> 4) | ((uint64_t)(4096 >> 4) << 16) | ((uint64_t)(1024 >> 4) << 32) | ((uint64_t)1 << 62);
}
__device__ __forceinline__ uint32_t pack_bf16(float lo, float hi) {
    uint32_t r; asm("cvt.rn.bf16x2.f32 %0, %1, %2;" : "=r"(r) : "f"(hi), "f"(lo)); return r;
}
__device__ __forceinline__ uint32_t pack_bf16_relu(float lo, float hi) {
    uint32_t r; asm("cvt.rn.relu.bf16x2.f32 %0, %1, %2;" : "=r"(r) : "f"(hi), "f"(lo)); return r;
}
__device__ __forceinline__ uint32_t movmatrix(uint32_t a) {
    uint32_t d; asm volatile("movmatrix.sync.aligned.m8n8.trans.b16 %0, %1;" : "=r"(d) : "r"(a)); return d;
}
__device__ __forceinline__ void stmatrix_x4(uint32_t addr, uint32_t r0, uint32_t r1, uint32_t r2, uint32_t r3) {
    asm volatile("stmatrix.sync.aligned.m8n8.x4.shared.b16 [%0], {%1, %2, %3, %4};" :: "r"(addr), "r"(r0), "r"(r1), "r"(r2), "r"(r3) : "memory");
}
__device__ __forceinline__ uint4 lds128(uint32_t addr) {
    uint4 v; asm volatile("ld.shared.v4.b32 {%0, %1, %2, %3}, [%4];" : "=r"(v.x), "=r"(v.y), "=r"(v.z), "=r"(v.w) : "r"(addr) : "memory"); return v;
}
__device__ __forceinline__ void mma16816(float (&c)[4], uint32_t a0, uint32_t a1, uint32_t a2, uint32_t a3, uint32_t b0, uint32_t b1) {
    asm volatile("mma.sync.aligned.m16n8k16.row.col.f32.bf16.bf16.f32 {%0,%1,%2,%3}, {%4,%5,%6,%7}, {%8,%9}, {%0,%1,%2,%3};"
        : "+f"(c[0]), "+f"(c[1]), "+f"(c[2]), "+f"(c[3]) : "r"(a0), "r"(a1), "r"(a2), "r"(a3), "r"(b0), "r"(b1));
}
__device__ __forceinline__ void mma16816_c(float (&c)[4], uint32_t a0, uint32_t a1, uint32_t a2, uint32_t a3, uint32_t b0, uint32_t b1, float ci) {
    asm volatile("mma.sync.aligned.m16n8k16.row.col.f32.bf16.bf16.f32 {%0,%1,%2,%3}, {%4,%5,%6,%7}, {%8,%9}, {%10,%10,%10,%10};"
        : "=f"(c[0]), "=f"(c[1]), "=f"(c[2]), "=f"(c[3]) : "r"(a0), "r"(a1), "r"(a2), "r"(a3), "r"(b0), "r"(b1), "f"(ci));
}
__device__ __forceinline__ int opaque(int v) { asm volatile("" : "+r"(v)); return v; }
__device__ __forceinline__ float ex2(float x) { float y; asm("ex2.approx.ftz.f32 %0, %1;" : "=f"(y) : "f"(x)); return y; }
__device__ __forceinline__ unsigned ld_acquire(const unsigned* p) {
    unsigned v; asm volatile("ld.acquire.gpu.global.u32 %0, [%1];" : "=r"(v) : "l"(p) : "memory"); return v;
}
__device__ __forceinline__ void red_release(unsigned* p, unsigned v) {
    asm volatile("red.release.gpu.global.add.u32 [%0], %1;" :: "l"(p), "r"(v) : "memory");
}
__device__ __forceinline__ void wait_counter(const unsigned* p, unsigned target) {
    uint32_t n = 0;
    while ((int)(ld_acquire(p) - target) < 0) { if (++n > (1u << 20)) break; }
}
__device__ __forceinline__ uint4 ldg_weak(const uint4* p) {
    uint4 v; asm volatile("ld.global.L1::no_allocate.v4.b32 {%0, %1, %2, %3}, [%4];" : "=r"(v.x), "=r"(v.y), "=r"(v.z), "=r"(v.w) : "l"(p) : "memory"); return v;
}
__device__ __forceinline__ float bf_lo(uint32_t v) { return __uint_as_float(v << 16); }
__device__ __forceinline__ float bf_hi(uint32_t v) { return __uint_as_float(v & 0xFFFF0000u); }

__device__ __forceinline__ void wgmma_ss_n64(float (&d)[32], uint64_t da, uint64_t db, int scale_d) {
    asm volatile("{\n.reg .pred p;\nsetp.ne.b32 p, %34, 0;\n"
        "wgmma.mma_async.sync.aligned.m64n64k16.f32.bf16.bf16 {%0, %1, %2, %3, %4, %5, %6, %7, %8, %9, %10, %11, %12, %13, %14, %15, %16, %17, %18, %19, %20, %21, %22, %23, %24, %25, %26, %27, %28, %29, %30, %31}, %32, %33, p, 1, 1, 0, 1;\n}\n"
        : "+f"(d[0]), "+f"(d[1]), "+f"(d[2]), "+f"(d[3]), "+f"(d[4]), "+f"(d[5]), "+f"(d[6]), "+f"(d[7]), "+f"(d[8]), "+f"(d[9]), "+f"(d[10]), "+f"(d[11]), "+f"(d[12]), "+f"(d[13]), "+f"(d[14]), "+f"(d[15]), "+f"(d[16]), "+f"(d[17]), "+f"(d[18]), "+f"(d[19]), "+f"(d[20]), "+f"(d[21]), "+f"(d[22]), "+f"(d[23]), "+f"(d[24]), "+f"(d[25]), "+f"(d[26]), "+f"(d[27]), "+f"(d[28]), "+f"(d[29]), "+f"(d[30]), "+f"(d[31])
        : "l"(da), "l"(db), "r"(scale_d));
}
__device__ __forceinline__ void wgmma_ss_n128(float (&d)[64], uint64_t da, uint64_t db, int scale_d) {
    asm volatile("{\n.reg .pred p;\nsetp.ne.b32 p, %66, 0;\n"
        "wgmma.mma_async.sync.aligned.m64n128k16.f32.bf16.bf16 {%0, %1, %2, %3, %4, %5, %6, %7, %8, %9, %10, %11, %12, %13, %14, %15, %16, %17, %18, %19, %20, %21, %22, %23, %24, %25, %26, %27, %28, %29, %30, %31, %32, %33, %34, %35, %36, %37, %38, %39, %40, %41, %42, %43, %44, %45, %46, %47, %48, %49, %50, %51, %52, %53, %54, %55, %56, %57, %58, %59, %60, %61, %62, %63}, %64, %65, p, 1, 1, 0, 1;\n}\n"
        : "+f"(d[0]), "+f"(d[1]), "+f"(d[2]), "+f"(d[3]), "+f"(d[4]), "+f"(d[5]), "+f"(d[6]), "+f"(d[7]), "+f"(d[8]), "+f"(d[9]), "+f"(d[10]), "+f"(d[11]), "+f"(d[12]), "+f"(d[13]), "+f"(d[14]), "+f"(d[15]), "+f"(d[16]), "+f"(d[17]), "+f"(d[18]), "+f"(d[19]), "+f"(d[20]), "+f"(d[21]), "+f"(d[22]), "+f"(d[23]), "+f"(d[24]), "+f"(d[25]), "+f"(d[26]), "+f"(d[27]), "+f"(d[28]), "+f"(d[29]), "+f"(d[30]), "+f"(d[31]), "+f"(d[32]), "+f"(d[33]), "+f"(d[34]), "+f"(d[35]), "+f"(d[36]), "+f"(d[37]), "+f"(d[38]), "+f"(d[39]), "+f"(d[40]), "+f"(d[41]), "+f"(d[42]), "+f"(d[43]), "+f"(d[44]), "+f"(d[45]), "+f"(d[46]), "+f"(d[47]), "+f"(d[48]), "+f"(d[49]), "+f"(d[50]), "+f"(d[51]), "+f"(d[52]), "+f"(d[53]), "+f"(d[54]), "+f"(d[55]), "+f"(d[56]), "+f"(d[57]), "+f"(d[58]), "+f"(d[59]), "+f"(d[60]), "+f"(d[61]), "+f"(d[62]), "+f"(d[63])
        : "l"(da), "l"(db), "r"(scale_d));
}
__device__ __forceinline__ void wgmma_ss_n200(float (&d)[100], uint64_t da, uint64_t db, int scale_d) {
    asm volatile("{\n.reg .pred p;\nsetp.ne.b32 p, %102, 0;\n"
        "wgmma.mma_async.sync.aligned.m64n200k16.f32.bf16.bf16 {%0, %1, %2, %3, %4, %5, %6, %7, %8, %9, %10, %11, %12, %13, %14, %15, %16, %17, %18, %19, %20, %21, %22, %23, %24, %25, %26, %27, %28, %29, %30, %31, %32, %33, %34, %35, %36, %37, %38, %39, %40, %41, %42, %43, %44, %45, %46, %47, %48, %49, %50, %51, %52, %53, %54, %55, %56, %57, %58, %59, %60, %61, %62, %63, %64, %65, %66, %67, %68, %69, %70, %71, %72, %73, %74, %75, %76, %77, %78, %79, %80, %81, %82, %83, %84, %85, %86, %87, %88, %89, %90, %91, %92, %93, %94, %95, %96, %97, %98, %99}, %100, %101, p, 1, 1, 0, 1;\n}\n"
        : "+f"(d[0]), "+f"(d[1]), "+f"(d[2]), "+f"(d[3]), "+f"(d[4]), "+f"(d[5]), "+f"(d[6]), "+f"(d[7]), "+f"(d[8]), "+f"(d[9]), "+f"(d[10]), "+f"(d[11]), "+f"(d[12]), "+f"(d[13]), "+f"(d[14]), "+f"(d[15]), "+f"(d[16]), "+f"(d[17]), "+f"(d[18]), "+f"(d[19]), "+f"(d[20]), "+f"(d[21]), "+f"(d[22]), "+f"(d[23]), "+f"(d[24]), "+f"(d[25]), "+f"(d[26]), "+f"(d[27]), "+f"(d[28]), "+f"(d[29]), "+f"(d[30]), "+f"(d[31]), "+f"(d[32]), "+f"(d[33]), "+f"(d[34]), "+f"(d[35]), "+f"(d[36]), "+f"(d[37]), "+f"(d[38]), "+f"(d[39]), "+f"(d[40]), "+f"(d[41]), "+f"(d[42]), "+f"(d[43]), "+f"(d[44]), "+f"(d[45]), "+f"(d[46]), "+f"(d[47]), "+f"(d[48]), "+f"(d[49]), "+f"(d[50]), "+f"(d[51]), "+f"(d[52]), "+f"(d[53]), "+f"(d[54]), "+f"(d[55]), "+f"(d[56]), "+f"(d[57]), "+f"(d[58]), "+f"(d[59]), "+f"(d[60]), "+f"(d[61]), "+f"(d[62]), "+f"(d[63]), "+f"(d[64]), "+f"(d[65]), "+f"(d[66]), "+f"(d[67]), "+f"(d[68]), "+f"(d[69]), "+f"(d[70]), "+f"(d[71]), "+f"(d[72]), "+f"(d[73]), "+f"(d[74]), "+f"(d[75]), "+f"(d[76]), "+f"(d[77]), "+f"(d[78]), "+f"(d[79]), "+f"(d[80]), "+f"(d[81]), "+f"(d[82]), "+f"(d[83]), "+f"(d[84]), "+f"(d[85]), "+f"(d[86]), "+f"(d[87]), "+f"(d[88]), "+f"(d[89]), "+f"(d[90]), "+f"(d[91]), "+f"(d[92]), "+f"(d[93]), "+f"(d[94]), "+f"(d[95]), "+f"(d[96]), "+f"(d[97]), "+f"(d[98]), "+f"(d[99])
        : "l"(da), "l"(db), "r"(scale_d));
}
__device__ __forceinline__ void wgmma_ss_n224(float (&d)[112], uint64_t da, uint64_t db, int scale_d) {
    asm volatile("{\n.reg .pred p;\nsetp.ne.b32 p, %114, 0;\n"
        "wgmma.mma_async.sync.aligned.m64n224k16.f32.bf16.bf16 {%0, %1, %2, %3, %4, %5, %6, %7, %8, %9, %10, %11, %12, %13, %14, %15, %16, %17, %18, %19, %20, %21, %22, %23, %24, %25, %26, %27, %28, %29, %30, %31, %32, %33, %34, %35, %36, %37, %38, %39, %40, %41, %42, %43, %44, %45, %46, %47, %48, %49, %50, %51, %52, %53, %54, %55, %56, %57, %58, %59, %60, %61, %62, %63, %64, %65, %66, %67, %68, %69, %70, %71, %72, %73, %74, %75, %76, %77, %78, %79, %80, %81, %82, %83, %84, %85, %86, %87, %88, %89, %90, %91, %92, %93, %94, %95, %96, %97, %98, %99, %100, %101, %102, %103, %104, %105, %106, %107, %108, %109, %110, %111}, %112, %113, p, 1, 1, 0, 1;\n}\n"
        : "+f"(d[0]), "+f"(d[1]), "+f"(d[2]), "+f"(d[3]), "+f"(d[4]), "+f"(d[5]), "+f"(d[6]), "+f"(d[7]), "+f"(d[8]), "+f"(d[9]), "+f"(d[10]), "+f"(d[11]), "+f"(d[12]), "+f"(d[13]), "+f"(d[14]), "+f"(d[15]), "+f"(d[16]), "+f"(d[17]), "+f"(d[18]), "+f"(d[19]), "+f"(d[20]), "+f"(d[21]), "+f"(d[22]), "+f"(d[23]), "+f"(d[24]), "+f"(d[25]), "+f"(d[26]), "+f"(d[27]), "+f"(d[28]), "+f"(d[29]), "+f"(d[30]), "+f"(d[31]), "+f"(d[32]), "+f"(d[33]), "+f"(d[34]), "+f"(d[35]), "+f"(d[36]), "+f"(d[37]), "+f"(d[38]), "+f"(d[39]), "+f"(d[40]), "+f"(d[41]), "+f"(d[42]), "+f"(d[43]), "+f"(d[44]), "+f"(d[45]), "+f"(d[46]), "+f"(d[47]), "+f"(d[48]), "+f"(d[49]), "+f"(d[50]), "+f"(d[51]), "+f"(d[52]), "+f"(d[53]), "+f"(d[54]), "+f"(d[55]), "+f"(d[56]), "+f"(d[57]), "+f"(d[58]), "+f"(d[59]), "+f"(d[60]), "+f"(d[61]), "+f"(d[62]), "+f"(d[63]), "+f"(d[64]), "+f"(d[65]), "+f"(d[66]), "+f"(d[67]), "+f"(d[68]), "+f"(d[69]), "+f"(d[70]), "+f"(d[71]), "+f"(d[72]), "+f"(d[73]), "+f"(d[74]), "+f"(d[75]), "+f"(d[76]), "+f"(d[77]), "+f"(d[78]), "+f"(d[79]), "+f"(d[80]), "+f"(d[81]), "+f"(d[82]), "+f"(d[83]), "+f"(d[84]), "+f"(d[85]), "+f"(d[86]), "+f"(d[87]), "+f"(d[88]), "+f"(d[89]), "+f"(d[90]), "+f"(d[91]), "+f"(d[92]), "+f"(d[93]), "+f"(d[94]), "+f"(d[95]), "+f"(d[96]), "+f"(d[97]), "+f"(d[98]), "+f"(d[99]), "+f"(d[100]), "+f"(d[101]), "+f"(d[102]), "+f"(d[103]), "+f"(d[104]), "+f"(d[105]), "+f"(d[106]), "+f"(d[107]), "+f"(d[108]), "+f"(d[109]), "+f"(d[110]), "+f"(d[111])
        : "l"(da), "l"(db), "r"(scale_d));
}
template <int N> __device__ __forceinline__ void fence_acc(float (&d)[N]) {
#pragma unroll
    for (int i = 0; i < N; i++) asm volatile("" : "+f"(d[i]) :: "memory");
}

__device__ __forceinline__ void bulk_s2g(void* dst, uint32_t src, uint32_t bytes) {
    asm volatile("cp.async.bulk.global.shared::cta.bulk_group [%0], [%1], %2;" :: "l"(dst), "r"(src), "r"(bytes) : "memory");
}
__device__ __forceinline__ void sts128(uint32_t addr, uint4 v) {
    asm volatile("st.shared.v4.b32 [%0], {%1, %2, %3, %4};" :: "r"(addr), "r"(v.x), "r"(v.y), "r"(v.z), "r"(v.w) : "memory");
}
__device__ __forceinline__ void sum_partials(uint32_t sb, int ti, int tj, int lane) {
    for (;;) {
        uint32_t item = 0;
        if (lane == 0) asm volatile("atom.shared.add.u32 %0, [%1], 1;" : "=r"(item) : "r"(sb + ITEM_OFF) : "memory");
        item = __shfl_sync(0xffffffffu, item, 0);
        if (item >= 8) break;
        const uint4* p = g_part + (size_t)((ti * 8 + tj) * 8) * 1024 + item * 128 + lane;
        uint4 v[4][4];
#pragma unroll
        for (int s = 0; s < 4; s++)
#pragma unroll
            for (int n = 0; n < 4; n++) v[n][s] = ldg_weak(p + s * 1024 + n * 32);
#pragma unroll
        for (int n = 0; n < 4; n++) {
            float a[8];
#pragma unroll
            for (int e = 0; e < 8; e++) a[e] = 0.f;
#pragma unroll
            for (int s = 0; s < 4; s++) {
                a[0] += bf_lo(v[n][s].x); a[1] += bf_hi(v[n][s].x); a[2] += bf_lo(v[n][s].y); a[3] += bf_hi(v[n][s].y);
                a[4] += bf_lo(v[n][s].z); a[5] += bf_hi(v[n][s].z); a[6] += bf_lo(v[n][s].w); a[7] += bf_hi(v[n][s].w);
            }
            const uint32_t d = sb + HSUM_OFF + (item * 8 + n * 2) * 512 + lane * 16;
            sts128(d, make_uint4(__float_as_uint(a[0]), __float_as_uint(a[1]), __float_as_uint(a[2]), __float_as_uint(a[3])));
            sts128(d + 512, make_uint4(__float_as_uint(a[4]), __float_as_uint(a[5]), __float_as_uint(a[6]), __float_as_uint(a[7])));
        }
    }
    __syncwarp();
    if (lane == 0) mbar_arrive(sb + B_HSUM);
}

#define PWAIT() mbar_wait(sb + B_EMPTY + 8 * r.slot, r.phase)
#define CWAIT() do { if (!dry) mbar_wait(sb + B_FULL + 8 * r.slot, r.phase); } while (0)
template <bool B> struct BoolTag { static constexpr bool value = B; };
struct Ring {
    int slot; uint32_t phase;
    __device__ __forceinline__ void next() { if (++slot == RING) { slot = 0; phase ^= 1; } }
};

__global__ void __launch_bounds__(384, 1)
fused_kernel(const __grid_constant__ CUtensorMap map_x, const __grid_constant__ CUtensorMap map_qkv,
             const __grid_constant__ CUtensorMap map_w1, const __grid_constant__ CUtensorMap map_w2,
             const __grid_constant__ CUtensorMap map_wo, const __grid_constant__ CUtensorMap map_w1a,
             const __grid_constant__ CUtensorMap map_o,
             const __nv_bfloat16* __restrict__ gate_w, __nv_bfloat16* __restrict__ out,
             const uint8_t* __restrict__ w1p, const uint8_t* __restrict__ w2p, const uint8_t* __restrict__ wop)
{
    extern __shared__ __align__(1024) uint8_t smem_raw[];
    const uint32_t sb = smem_u32(smem_raw);
    const int tid = threadIdx.x, warp = tid >> 5, lane = tid & 31;
    const bool dry = blockIdx.x >= 128;
    const int ti = dry ? (int)(blockIdx.x & 1) * 2 : blockIdx.x >> 3, tj = blockIdx.x & 7;
    if (dry && warp >= 8) {
        asm volatile("setmaxnreg.dec.sync.aligned.u32 88;");
        return;
    }

    if (tid == 0 && !dry) { TSG(31); TSX(0); }
    if (tid == 320) {
        asm volatile("prefetch.tensormap [%0];" :: "l"(&map_x) : "memory");
        asm volatile("prefetch.tensormap [%0];" :: "l"(&map_qkv) : "memory");
        asm volatile("prefetch.tensormap [%0];" :: "l"(&map_w1) : "memory");
        asm volatile("prefetch.tensormap [%0];" :: "l"(&map_w1a) : "memory");
        asm volatile("prefetch.tensormap [%0];" :: "l"(&map_w2) : "memory");
        asm volatile("prefetch.tensormap [%0];" :: "l"(&map_wo) : "memory");
        asm volatile("prefetch.tensormap [%0];" :: "l"(&map_o) : "memory");
    }
    if (tid == 256) {
        mbar_init(sb + B_FULL, 1); mbar_init(sb + B_XFULL, 1);
        fence_async_smem();
        mbar_expect_tx(sb + B_XFULL, 16384);
        tma_2d(sb + X_OFF, &map_x, sb + B_XFULL, 0, ti * 128);
        mbar_expect_only(sb + B_FULL, 12288);
        tma_4d(sb + RING_OFF, &map_qkv, sb + B_FULL, 0, 0, tj, 0);
    }
    uint32_t gwv[N_QKV / 2];
    if (warp == 8) {
        const unsigned short* gws = reinterpret_cast<const unsigned short*>(gate_w);
#pragma unroll
        for (int n = 0; n < N_QKV / 2; n++) gwv[n] = (uint32_t)__ldg(gws + 64 * n + lane) | ((uint32_t)__ldg(gws + 64 * n + 32 + lane) << 16);
    }
    if (tid == 288) {
        for (int s = 1; s < RING; s++) mbar_init(sb + B_FULL + 8 * s, 1);
        for (int s = 0; s < RING; s++) mbar_init(sb + B_EMPTY + 8 * s, 8);
        for (int s = 1; s < 8; s++) mbar_init(sb + B_XFULL + 8 * s, 1);
        fence_async_smem();
    }
    if (tid == 352) {
        mbar_init(sb + B_HDEAD, 8); mbar_init(sb + B_EREADY, 1); mbar_init(sb + B_KVDONE, 8); mbar_init(sb + B_KVREADY, 1);
        mbar_init(sb + B_ODONE, 8); mbar_init(sb + B_WOFULL, 1); mbar_init(sb + B_HSUM, 3);
        mbar_init(sb + B_XDEAD, 8); mbar_init(sb + B_PREADY, 1); mbar_init(sb + B_SF, 1); mbar_init(sb + B_SF + 8, 1);
        for (int s = 0; s < 4; s++) mbar_init(sb + B_SQ + 8 * s, 8);
        asm volatile("st.shared.u32 [%0], %1;" :: "r"(sb + ITEM_OFF), "r"(0) : "memory");
        fence_async_smem();
    }
    if (!dry) __syncthreads();

    if (warp >= 8) {
        asm volatile("setmaxnreg.dec.sync.aligned.u32 88;");
        if (warp == 8) {
            Ring r{0, 1};
            const bool leader = elect_one();
#pragma unroll
            for (int n = 0; n < N_QKV; n++) {
                const uint32_t full = sb + B_FULL + 8 * r.slot, dst = sb + RING_OFF + r.slot * SLOT;
                if (n > 0) {
                    if (!(n & 1) && leader) {
                        mbar_expect_tx(sb + B_XFULL + 8 * (n >> 1), 16384);
                        tma_2d(sb + X_OFF + (n >> 1) * 16384, &map_x, sb + B_XFULL + 8 * (n >> 1), (n >> 1) * 64, ti * 128);
                    }
                    if (n >= RING) PWAIT();
                    if (leader) {
                        mbar_expect_only(full, 12288);
                        tma_4d(dst, &map_qkv, full, 0, 32 * n, tj, 0);
                    }
                }
                const uint32_t gv = (n & 1) ? (gwv[n >> 1] >> 16) : (gwv[n >> 1] & 0xFFFFu);
                asm volatile("st.shared.v4.b32 [%0], {%1, %2, %2, %2};" :: "r"(dst + 12288 + lane * 128 + ((lane & 7) << 4)), "r"(gv), "r"(0) : "memory");
                fence_async_smem();
                __syncwarp();
                if (leader) mbar_arrive(full);
                r.next();
            }
#pragma unroll 1
            for (int n = 0; n < N_FFN1; n++) {
                const uint32_t full = sb + B_FULL + 8 * r.slot, dst = sb + RING_OFF + r.slot * SLOT;
                PWAIT();
                if (leader) {
                    mbar_expect_tx(full, 16384);
                    tma_4d(dst, &map_w1a, full, 0, 32 * n, 0, tj);
                    tma_2d(dst + 3 * 4096, &map_w1, full, 224 * tj + 192, 32 * n);
                }
                r.next();
            }
            {
                int q = 0, rr = 0;
#pragma unroll 1
                for (int n = 0; n < N_FFN2; n++) {
                    const uint32_t full = sb + B_FULL + 8 * r.slot, dst = sb + RING_OFF + r.slot * SLOT;
                    PWAIT();
                    if (leader) mbar_expect_tx(full, 16384);
#pragma unroll
                    for (int h = 0; h < 2; h++) {
                        if (leader) tma_3d(dst + h * 8192, &map_w2, full, 0, 224 * tj + 32 * rr, 2 * q);
                        if (++rr == 7) { rr = 0; q++; }
                    }
                    r.next();
                }
            }
            mbar_wait(sb + B_KVREADY, 0);
            asm volatile("fence.proxy.async.global;" ::: "memory");
            {
                const int bbase = 8 * ti - 16, b0 = bbase < 0 ? 0 : bbase;
                const uint32_t bytes = (uint32_t)(8 * ti + 8 - b0) * 512;
#pragma unroll 1
                for (int m = 0; m < N_KV; m++) {
                    const uint32_t full = sb + B_FULL + 8 * r.slot, dst = sb + RING_OFF + r.slot * SLOT;
                    if (m == RING) {
                        mbar_wait(sb + B_HDEAD, 0);
                        if (leader) {
                            mbar_expect_tx(sb + B_WOFULL, 65536);
#pragma unroll
                            for (int e = 0; e < 2; e++) tma_2d(sb + X_OFF + e * 32768, &map_wo, sb + B_WOFULL, 64 * tj, 256 * e);
                        }
                    }
                    PWAIT();
                    if (leader) {
                        const uint4* src = ((m & 1) ? g_vf : g_kf) + ((tj * 4 + (m >> 1)) * 128 + b0) * 32;
                        mbar_expect_tx(full, bytes);
                        bulk_g2s(dst + (b0 - bbase) * 512, src, bytes, full);
                    }
                    r.next();
                }
            }
            {
                mbar_wait(sb + B_EREADY, 0);
                unsigned epoch; asm volatile("ld.shared.u32 %0, [%1];" : "=r"(epoch) : "r"(sb + EPOCH_OFF) : "memory");
                uint32_t pending = 0xFFu & ~(1u << tj), ready = 0;
                mbar_wait(sb + B_HSUM, 0);
#pragma unroll 1
                for (int m = 0; m < N_O; m++) {
                    const uint32_t full = sb + B_FULL + 8 * r.slot, dst = sb + RING_OFF + r.slot * SLOT;
                    PWAIT();
                    for (int it = 0; it < (1 << 20) && !ready; it++) {
                        bool ok = false;
                        if (lane < 8 && ((pending >> lane) & 1)) ok = (int)(ld_acquire(&g_ocnt[(ti * 8 + lane) * 32]) - (epoch + 1)) >= 0;
                        ready = __ballot_sync(0xffffffffu, ok);
                        if (!ready) __nanosleep(100);
                    }
                    const int js = ready ? __ffs(ready) - 1 : __ffs(pending) - 1;
                    pending &= ~(1u << js); ready &= ~(1u << js);
                    asm volatile("fence.proxy.async.global;" ::: "memory");
                    if (leader) {
                        asm volatile("st.shared.u32 [%0], %1;" :: "r"(sb + OSRC_OFF + 4 * m), "r"(js) : "memory");
                        mbar_expect_tx(full, 16384);
                        tma_2d(dst, &map_o, full, 64 * js, ti * 128);
                    }
                    r.next();
                }
            }
        } else if (warp == 9) {
            unsigned epoch = 0;
            if (lane == 0) {
                epoch = atomicAdd(&g_ticket, 1u) >> 7;
                asm volatile("st.shared.u32 [%0], %1;" :: "r"(sb + EPOCH_OFF), "r"(epoch) : "memory");
                mbar_arrive(sb + B_EREADY);
                mbar_wait(sb + B_XFULL + 8 * PF1_AT, 0);
                prefetch_l2(w1p + (size_t)blockIdx.x * 14336, 14336);
                mbar_wait(sb + B_XFULL + 8 * PF2_AT, 0);
                prefetch_l2(w2p + (size_t)blockIdx.x * 14336, 14336);
                prefetch_l2(wop + (size_t)blockIdx.x * 4096, 4096);
                mbar_wait(sb + B_KVDONE, 0);
                red_release(&g_kvcnt[blockIdx.x * 32], 1u);
            }
            epoch = __shfl_sync(0xffffffffu, epoch, 0);
            if (lane < 3 && ti - lane >= 0) wait_counter(&g_kvcnt[((ti - lane) * 8 + tj) * 32], epoch + 1);
            __syncwarp();
            if (lane == 0) mbar_arrive(sb + B_KVREADY);
            mbar_wait(sb + B_SQ + 24, 0);
            if (lane < 8) wait_counter(&g_pcnt[(ti * 8 + lane) * 32], epoch + 1);
            __syncwarp();
            if (lane == 0) { mbar_arrive(sb + B_PREADY); TSX(13); }
            sum_partials(sb, ti, tj, lane);
            if (lane == 0) TSX(14);
        } else {
            if (warp == 10) {
#pragma unroll 1
                for (int q = 0; q < 4; q++) {
                    mbar_wait(sb + B_SQ + 8 * q, 0);
                    if (lane < 16) {
                        uint4* d = g_part + (size_t)(((ti * 8 + 2 * q + (lane & 1)) * 8 + tj) * 8 + (lane >> 1)) * 128;
                        bulk_s2g(d, sb + STG_OFF + (q & 1) * 32768 + lane * 2048, 2048);
                        asm volatile("cp.async.bulk.commit_group;" ::: "memory");
                        asm volatile("cp.async.bulk.wait_group.read 0;" ::: "memory");
                    }
                    __syncwarp();
                    if (lane == 0) mbar_arrive(sb + B_SF + 8 * (q & 1));
                }
                asm volatile("cp.async.bulk.wait_group 0;" ::: "memory");
                asm volatile("fence.proxy.async.global;" ::: "memory");
                __syncwarp();
                if (lane == 0) { red_release(&g_pcnt[blockIdx.x * 32], 1u); TSX(12); }
            }
            mbar_wait(sb + B_PREADY, 0);
            sum_partials(sb, ti, tj, lane);
            if (warp == 11 && lane == 0) {
                mbar_wait(sb + B_ODONE, 0);
                red_release(&g_ocnt[blockIdx.x * 32], 1u);
            }
        }
    } else {
        asm volatile("setmaxnreg.inc.sync.aligned.u32 208;");
        const int wg = warp >> 2, g = lane >> 2, c = lane & 3;
        const uint32_t xa = sb + X_OFF + wg * 8192;
        Ring r{0, 0};
        const bool lane0 = lane == 0 && !dry;
        uint32_t qf[4][4];
        float g0, g1;
        TS(9);
        {
            float acc[100];
            int prev = 0;
            if (wg == 1) asm volatile("bar.sync 3, 256;" ::: "memory");
            for (int s = 0; s < (dry ? 4 : N_QKV); s++) {
                if (!(s & 1) && !dry) mbar_wait(sb + B_XFULL + 8 * (s >> 1), 0);
                CWAIT();
                if (s == 0) TS(1);
                if (s == 2) TS(28);
                if (s == 6) TS(29);
                if (s == 10) TS(20);
                const uint32_t bs = sb + RING_OFF + r.slot * SLOT, as = xa + (s >> 1) * 16384 + (s & 1) * 64;
                wgmma_fence();
                wgmma_ss_n200(acc, desc_a(as), desc_b(bs), s);
                wgmma_ss_n200(acc, desc_a(as + 32), desc_b(bs + 2048), 1);
                wgmma_commit();
                if (wg == 0 && s == LEAD1) asm volatile("bar.arrive 3, 256;" ::: "memory");
                if (s > 0) { wgmma_wait<1>(); if (lane0) mbar_arrive(sb + B_EMPTY + 8 * prev); }
                prev = r.slot; r.next();
            }
            wgmma_wait<0>();
            fence_acc(acc);
            if (lane0) mbar_arrive(sb + B_EMPTY + 8 * prev);
            TS(2);
            const int blk = ti * 8 + warp;
#pragma unroll
            for (int hh = 0; hh < 4; hh++) {
                const float* t0 = &acc[8 * hh]; const float* t1 = &acc[8 * hh + 4];
                qf[hh][0] = pack_bf16(t0[0], t0[1]); qf[hh][1] = pack_bf16(t0[2], t0[3]);
                qf[hh][2] = pack_bf16(t1[0], t1[1]); qf[hh][3] = pack_bf16(t1[2], t1[3]);
                const float* k0 = &acc[32 + 8 * hh]; const float* k1 = &acc[32 + 8 * hh + 4];
                uint4 kv;
                kv.x = pack_bf16(k0[0], k0[1]); kv.y = pack_bf16(k1[0], k1[1]);
                kv.z = pack_bf16(k0[2], k0[3]); kv.w = pack_bf16(k1[2], k1[3]);
                if (!dry) g_kf[((tj * 4 + hh) * 128 + blk) * 32 + lane] = kv;
                const float* v0 = &acc[64 + 8 * hh]; const float* v1 = &acc[64 + 8 * hh + 4];
                uint4 vv;
                vv.x = movmatrix(pack_bf16(v0[0], v0[1])); vv.y = movmatrix(pack_bf16(v0[2], v0[3]));
                vv.z = movmatrix(pack_bf16(v1[0], v1[1])); vv.w = movmatrix(pack_bf16(v1[2], v1[3]));
                if (!dry) g_vf[((tj * 4 + hh) * 128 + blk) * 32 + lane] = vv;
            }
            __syncwarp();
            if (lane0) mbar_arrive(sb + B_KVDONE);
            const float z0 = __shfl_sync(0xffffffffu, acc[96], lane & ~3), z1 = __shfl_sync(0xffffffffu, acc[98], lane & ~3);
            g0 = 1.f / (1.f + __expf(-z0)); g1 = 1.f / (1.f + __expf(-z1));
        }
        TS(3);
        const int wrow = (warp & 3) * 16;
        {
            float acc[112];
            int prev = 0;
            for (int s = 0; s < (dry ? 4 : N_FFN1); s++) {
                CWAIT();
                const uint32_t bs = sb + RING_OFF + r.slot * SLOT, as = xa + (s >> 1) * 16384 + (s & 1) * 64;
                wgmma_fence();
                wgmma_ss_n224(acc, desc_a(as), desc_b(bs), s);
                wgmma_ss_n224(acc, desc_a(as + 32), desc_b(bs + 2048), 1);
                wgmma_commit();
                if (s > 0) { wgmma_wait<1>(); if (lane0) mbar_arrive(sb + B_EMPTY + 8 * prev); }
                prev = r.slot; r.next();
            }
            wgmma_wait<0>();
            fence_acc(acc);
            if (lane0) { mbar_arrive(sb + B_EMPTY + 8 * prev); mbar_arrive(sb + B_XDEAD); }
            TS(4);
            const float s0 = 1.f - g0, s1 = 1.f - g1;
            asm volatile("bar.sync %0, 128;" :: "r"(1 + wg) : "memory");
            const uint32_t strow = xa + (wrow + ((lane >> 3) & 1) * 8 + (lane & 7)) * 128;
#pragma unroll
            for (int p = 0; p < 14; p++) {
                const int nt = 2 * p + (lane >> 4);
                const float* a = &acc[8 * p];
                stmatrix_x4(strow + (p >> 2) * 16384 + (((nt & 7) ^ (lane & 7)) << 4),
                            pack_bf16_relu(a[0] * s0, a[1] * s0), pack_bf16_relu(a[2] * s1, a[3] * s1),
                            pack_bf16_relu(a[4] * s0, a[5] * s0), pack_bf16_relu(a[6] * s1, a[7] * s1));
            }
        }
        TS(5);
        {
            fence_async_smem();
            asm volatile("bar.sync %0, 128;" :: "r"(1 + wg) : "memory");
            float accA[64], accB[64];
            auto epilogue = [&](float (&acc)[64], int q) {
                fence_acc(acc);
                const uint32_t st = sb + STG_OFF + (q & 1) * 32768 + warp * 4096;
                if (q == 0 && !dry) mbar_wait(sb + B_XDEAD, 0);
                if (q >= 2 && !dry) mbar_wait(sb + B_SF + 8 * (q & 1), 0);
#pragma unroll
                for (int t2 = 0; t2 < 8; t2++) {
                    uint4 v;
                    v.x = pack_bf16(acc[8 * t2 + 0], acc[8 * t2 + 1]); v.y = pack_bf16(acc[8 * t2 + 2], acc[8 * t2 + 3]);
                    v.z = pack_bf16(acc[8 * t2 + 4], acc[8 * t2 + 5]); v.w = pack_bf16(acc[8 * t2 + 6], acc[8 * t2 + 7]);
                    sts128(st + t2 * 512 + lane * 16, v);
                }
                fence_async_smem();
                __syncwarp();
                if (lane0) mbar_arrive(sb + B_SQ + 8 * q);
            };
            int rel = r.slot;
#pragma unroll
            for (int m = 0; m < N_FFN2; m++) {
                CWAIT();
                wgmma_fence();
#pragma unroll
                for (int h = 0; h < 2; h++) {
                    const int u = 2 * m + h, q = u / 7, rr = u % 7;
                    const uint32_t bs = sb + RING_OFF + r.slot * SLOT + h * 8192;
                    const uint32_t as = xa + (rr >> 1) * 16384 + (rr & 1) * 64;
                    if (!(q & 1)) {
                        wgmma_ss_n128(accA, desc_a(as), desc_b(bs), rr);
                        wgmma_ss_n128(accA, desc_a(as + 32), desc_b(bs + 2048), 1);
                    } else {
                        wgmma_ss_n128(accB, desc_a(as), desc_b(bs), rr);
                        wgmma_ss_n128(accB, desc_a(as + 32), desc_b(bs + 2048), 1);
                    }
                }
                wgmma_commit();
                r.next();
                wgmma_wait<1>();
                if (m > 0) {
                    if (lane0) mbar_arrive(sb + B_EMPTY + 8 * rel);
                    if (++rel == RING) rel = 0;
                }
                if (m == 4) { TS(25); epilogue(accA, 0); }
                if (m == 7) { TS(26); epilogue(accB, 1); }
                if (m == 11) { TS(27); epilogue(accA, 2); }
            }
            wgmma_wait<0>();
            if (lane0) { mbar_arrive(sb + B_EMPTY + 8 * rel); mbar_arrive(sb + B_HDEAD); }
            epilogue(accB, 3);
        }
        TS(6);
        {
            const float SC = 0.25f * 1.4426950408889634f;
            const int gb0 = 8 * ti - 16 + warp;
            int slotK = 0, slotV = 0;
            const uint32_t ostore = sb + OWN_OFF + (warp * 16 + ((lane >> 3) & 1) * 8 + (lane & 7)) * 128;
            uint32_t* odst = reinterpret_cast<uint32_t*>(g_o + (size_t)(ti * 128 + warp * 16 + g) * 512 + tj * 64 + ((lane & 1) ? 8 : 0) + (lane & 2) * 2);
#define NHEADS (dry ? 2 : 4)
#define ATT_KWAIT(kb) do { slotK = r.slot; CWAIT(); kb = sb + RING_OFF + slotK * SLOT + warp * 512 + lane * 16; r.next(); } while (0)
#define ATT_VWAIT(vb) do { slotV = r.slot; CWAIT(); vb = sb + RING_OFF + slotV * SLOT + warp * 512 + lane * 16; r.next(); TS(21 + hh); } while (0)
#define ATT_KREL() do { __syncwarp(); if (lane0) mbar_arrive(sb + B_EMPTY + 8 * slotK); } while (0)
#define ATT_VREL() do { __syncwarp(); if (lane0) mbar_arrive(sb + B_EMPTY + 8 * slotV); } while (0)
#define ATT_NEXTQ(h) do { \
                if ((h) == 1) { q0 = qf[1][0]; q1 = qf[1][1]; q2 = qf[1][2]; q3 = qf[1][3]; } \
                else if ((h) == 2) { q0 = qf[2][0]; q1 = qf[2][1]; q2 = qf[2][2]; q3 = qf[2][3]; } \
                else { q0 = qf[3][0]; q1 = qf[3][1]; q2 = qf[3][2]; q3 = qf[3][3]; } } while (0)
#define ATT_STORE(h, r0, r1, r2, r3) do { \
                if ((h) == 0 && !dry) mbar_wait(sb + B_SF, 1);        \
                stmatrix_x4(ostore + (((2 * (h) + (lane >> 4)) ^ (lane & 7)) << 4), r0, r1, r2, r3); \
                const bool odd = lane & 1; \
                const uint32_t sl = __shfl_xor_sync(0xffffffffu, odd ? (r0) : (r2), 1), sh = __shfl_xor_sync(0xffffffffu, odd ? (r1) : (r3), 1); \
                if (!dry) *reinterpret_cast<uint2*>(odst + 8 * (h)) = odd ? make_uint2(sl, r2) : make_uint2(r0, sl); \
                if (!dry) *reinterpret_cast<uint2*>(odst + 8 * (h) + 8 * 256) = odd ? make_uint2(sh, r3) : make_uint2(r1, sh); \
                } while (0)
            auto attention = [&](auto masked_tag) {
            constexpr bool MASKED = decltype(masked_tag)::value;
            const float NEG = -INFINITY;
            const uint32_t ONES = 0x3F803F80u;
            float sa[8][2][4];
            float o[2][4], ls[4];
            float m0, m1;
            uint32_t q0 = qf[0][0], q1 = qf[0][1], q2 = qf[0][2], q3 = qf[0][3];
            auto qk = [&](float (&s)[8][2][4], int ps, int t, uint32_t kbase, bool merged) {
                if (merged) {
                    const uint4 kd = lds128(kbase + 16 * 512);
                    const uint4 kf = lds128(kbase);
                    float f[2][4];
                    const float ci = (!MASKED || opaque(gb0) >= 0) ? 0.f : NEG;
                    mma16816_c(s[0][0], q0, q1, q2, q3, kd.x, kd.y, 0.f);
                    mma16816_c(s[0][1], q0, q1, q2, q3, kd.z, kd.w, 0.f);
                    mma16816_c(f[0], q0, q1, q2, q3, kf.x, kf.y, ci);
                    mma16816_c(f[1], q0, q1, q2, q3, kf.z, kf.w, ci);
#pragma unroll
                    for (int u = 0; u < 2; u++)
#pragma unroll
                        for (int e = 0; e < 4; e++) {
                            const int row = g + 8 * (e >> 1), col = 8 * u + 2 * c + (e & 1);
                            s[0][u][e] = (col > row) ? f[u][e] : s[0][u][e];
                        }
                } else {
                    const uint4 kf = lds128(kbase + (8 * ps + t) * 512);
                    const float ci = (!MASKED || opaque(gb0) + 8 * ps + t >= 0) ? 0.f : NEG;
                    mma16816_c(s[t][0], q0, q1, q2, q3, kf.x, kf.y, ci);
                    mma16816_c(s[t][1], q0, q1, q2, q3, kf.z, kf.w, ci);
                }
            };
            auto rowmax = [&](float (&s)[8][2][4], float b0, float b1, float& n0, float& n1) {
                int i0 = __float_as_int(b0), i1 = __float_as_int(b1);
#pragma unroll
                for (int t = 0; t < 8; t++)
#pragma unroll
                    for (int u = 0; u < 2; u++) {
                        i0 = __vimax3_s32(i0, __float_as_int(s[t][u][0]), __float_as_int(s[t][u][1]));
                        i1 = __vimax3_s32(i1, __float_as_int(s[t][u][2]), __float_as_int(s[t][u][3]));
                    }
                i0 = max(i0, __shfl_xor_sync(0xffffffffu, i0, 1)); i1 = max(i1, __shfl_xor_sync(0xffffffffu, i1, 1));
                i0 = max(i0, __shfl_xor_sync(0xffffffffu, i0, 2)); i1 = max(i1, __shfl_xor_sync(0xffffffffu, i1, 2));
                n0 = __int_as_float(i0); n1 = __int_as_float(i1);
                if (__any_sync(0xffffffffu, (i0 | i1) < 0)) {
                    asm volatile("" ::: "memory");
                    n0 = b0; n1 = b1;
#pragma unroll
                    for (int t = 0; t < 8; t++)
#pragma unroll
                        for (int u = 0; u < 2; u++) {
                            n0 = fmaxf(n0, fmaxf(s[t][u][0], s[t][u][1]));
                            n1 = fmaxf(n1, fmaxf(s[t][u][2], s[t][u][3]));
                        }
                    n0 = fmaxf(n0, __shfl_xor_sync(0xffffffffu, n0, 1)); n1 = fmaxf(n1, __shfl_xor_sync(0xffffffffu, n1, 1));
                    n0 = fmaxf(n0, __shfl_xor_sync(0xffffffffu, n0, 2)); n1 = fmaxf(n1, __shfl_xor_sync(0xffffffffu, n1, 2));
                }
            };
            auto pv = [&](const float (&p)[2][4], uint32_t vaddr) {
                const uint4 vf = lds128(vaddr);
                const uint32_t a0 = pack_bf16(p[0][0], p[0][1]), a1 = pack_bf16(p[0][2], p[0][3]);
                const uint32_t a2 = pack_bf16(p[1][0], p[1][1]), a3 = pack_bf16(p[1][2], p[1][3]);
                mma16816(o[0], a0, a1, a2, a3, vf.x, vf.y);
                mma16816(o[1], a0, a1, a2, a3, vf.z, vf.w);
                mma16816(ls, a0, a1, a2, a3, ONES, ONES);
            };
            auto expv = [&](float (&s)[8][2][4], int ps, int t, float mc0, float mc1, uint32_t vbase, bool merged) {
                float p[2][4];
#pragma unroll
                for (int u = 0; u < 2; u++) {
                    p[u][0] = ex2(fmaf(s[t][u][0], SC, -mc0)); p[u][1] = ex2(fmaf(s[t][u][1], SC, -mc0));
                    p[u][2] = ex2(fmaf(s[t][u][2], SC, -mc1)); p[u][3] = ex2(fmaf(s[t][u][3], SC, -mc1));
                }
                if (merged) {
                    float pd[2][4], pf[2][4];
#pragma unroll
                    for (int u = 0; u < 2; u++)
#pragma unroll
                        for (int e = 0; e < 4; e++) {
                            const int row = g + 8 * (e >> 1), col = 8 * u + 2 * c + (e & 1);
                            pf[u][e] = (col > row) ? p[u][e] : 0.f;
                            pd[u][e] = (col > row) ? 0.f : p[u][e];
                        }
                    pv(pd, vbase + 16 * 512);
                    pv(pf, vbase);
                } else {
                    pv(p, vbase + (8 * ps + t) * 512);
                }
            };
            uint32_t kbase = 0, vbase = 0;
#pragma unroll 1
            for (int hh = 0; hh < NHEADS; hh++) {
                ATT_KWAIT(kbase);
                if (hh > 0) ATT_NEXTQ(hh);
#pragma unroll
                for (int ps = 0; ps < 2; ps++) {
#pragma unroll
                    for (int t = 0; t < 8; t++) qk(sa, ps, t, kbase, ps == 0 && t == 0);
                    if (ps == 1) ATT_KREL();
                    float n0, n1;
                    rowmax(sa, ps ? m0 : NEG, ps ? m1 : NEG, n0, n1);
                    if (ps == 0) {
                        ATT_VWAIT(vbase);
#pragma unroll
                        for (int e = 0; e < 4; e++) { o[0][e] = 0.f; o[1][e] = 0.f; ls[e] = 0.f; }
                    } else {
                        const float a0 = ex2((m0 - n0) * SC), a1 = ex2((m1 - n1) * SC);
                        ls[0] *= a0; ls[2] *= a1;
                        o[0][0] *= a0; o[0][1] *= a0; o[1][0] *= a0; o[1][1] *= a0;
                        o[0][2] *= a1; o[0][3] *= a1; o[1][2] *= a1; o[1][3] *= a1;
                    }
                    m0 = n0; m1 = n1;
                    const float mc0 = n0 * SC, mc1 = n1 * SC;
#pragma unroll
                    for (int t = 0; t < 8; t++) expv(sa, ps, t, mc0, mc1, vbase, ps == 0 && t == 0);
                }
                ATT_VREL();
                const float f0 = __fdividef(g0, ls[0]), f1 = __fdividef(g1, ls[2]);
                ATT_STORE(hh, pack_bf16(o[0][0] * f0, o[0][1] * f0), pack_bf16(o[0][2] * f1, o[0][3] * f1),
                              pack_bf16(o[1][0] * f0, o[1][1] * f0), pack_bf16(o[1][2] * f1, o[1][3] * f1));
            }
            };
            if (ti >= 2) attention(BoolTag<false>{}); else attention(BoolTag<true>{});
            fence_async_smem();
            __syncwarp();
            if (lane0) mbar_arrive(sb + B_ODONE);
        }
        TS(7);
        {
            float acc[32];
            uint4 pv[4][4];
            if (!dry) mbar_wait(sb + B_PREADY, 0);
            {
                const uint4* p = g_part + (size_t)((ti * 8 + tj) * 8 + 4) * 1024 + warp * 128 + lane;
#pragma unroll
                for (int s = 0; s < 4; s++)
#pragma unroll
                    for (int n = 0; n < 4; n++) pv[n][s] = dry ? make_uint4(0u, 0u, 0u, 0u) : ldg_weak(p + s * 1024 + n * 32);
            }
            if (!dry) mbar_wait(sb + B_WOFULL, 0);
            if (!dry) mbar_wait(sb + B_ODONE, 0);
            TS(15);
            wgmma_fence();
#pragma unroll
            for (int k = 0; k < 4; k++) wgmma_ss_n64(acc, desc_a(sb + OWN_OFF + wg * 8192 + 32 * k), desc_b(sb + X_OFF + tj * 8192 + 2048 * k), k);
            wgmma_commit();
            TS(16);
#pragma unroll 1
            for (int m = 0; m < N_O; m++) {
                CWAIT();
                uint32_t js; asm volatile("ld.shared.u32 %0, [%1];" : "=r"(js) : "r"(sb + OSRC_OFF + 4 * m) : "memory");
                const uint32_t as = sb + RING_OFF + r.slot * SLOT + wg * 8192;
                const uint32_t bs = sb + X_OFF + (js & 7) * 8192;
                wgmma_fence();
#pragma unroll
                for (int k = 0; k < 4; k++) wgmma_ss_n64(acc, desc_a(as + 32 * k), desc_b(bs + 2048 * k), 1);
                wgmma_commit();
                if (m == 0) { wgmma_wait<0>(); if (lane0) mbar_arrive(sb + B_EMPTY + 8 * r.slot); }
                r.next();
            }
            float base[32];
            if (!dry) mbar_wait(sb + B_HSUM, 0);
#pragma unroll
            for (int n = 0; n < 4; n++) {
                const uint4 u0 = lds128(sb + HSUM_OFF + (warp * 8 + 2 * n) * 512 + lane * 16), u1 = lds128(sb + HSUM_OFF + (warp * 8 + 2 * n + 1) * 512 + lane * 16);
                float* a = &base[8 * n];
                a[0] = __uint_as_float(u0.x); a[1] = __uint_as_float(u0.y); a[2] = __uint_as_float(u0.z); a[3] = __uint_as_float(u0.w);
                a[4] = __uint_as_float(u1.x); a[5] = __uint_as_float(u1.y); a[6] = __uint_as_float(u1.z); a[7] = __uint_as_float(u1.w);
#pragma unroll
                for (int s = 0; s < 4; s++) {
                    a[0] += bf_lo(pv[n][s].x); a[1] += bf_hi(pv[n][s].x); a[2] += bf_lo(pv[n][s].y); a[3] += bf_hi(pv[n][s].y);
                    a[4] += bf_lo(pv[n][s].z); a[5] += bf_hi(pv[n][s].z); a[6] += bf_lo(pv[n][s].w); a[7] += bf_hi(pv[n][s].w);
                }
            }
            fence_acc(base);
            wgmma_wait<0>();
            fence_acc(acc);
            TS(17);
#pragma unroll
            for (int k = 0; k < 32; k++) acc[k] += base[k];
            __nv_bfloat16* o = out + (size_t)(ti * 128 + warp * 16 + g) * 512 + tj * 64 + ((lane & 1) ? 8 : 0) + (lane & 2) * 2;
            const bool odd = lane & 1;
#pragma unroll
            for (int t2 = 0; t2 < 4; t2++) {
                const uint32_t lo0 = pack_bf16(acc[8 * t2 + 0], acc[8 * t2 + 1]), hi0 = pack_bf16(acc[8 * t2 + 2], acc[8 * t2 + 3]);
                const uint32_t lo1 = pack_bf16(acc[8 * t2 + 4], acc[8 * t2 + 5]), hi1 = pack_bf16(acc[8 * t2 + 6], acc[8 * t2 + 7]);
                const uint32_t sl = __shfl_xor_sync(0xffffffffu, odd ? lo0 : lo1, 1), sh = __shfl_xor_sync(0xffffffffu, odd ? hi0 : hi1, 1);
                if (!dry) *reinterpret_cast<uint2*>(o + 16 * t2) = odd ? make_uint2(sl, lo1) : make_uint2(lo0, sl);
                if (!dry) *reinterpret_cast<uint2*>(o + 16 * t2 + 8 * 512) = odd ? make_uint2(sh, hi1) : make_uint2(hi0, sh);
            }
            if (tid == 0 && !dry) TSG(30);
        }
        TS(8);
    }
}

typedef CUresult (*PFN_encodeTiled)(CUtensorMap*, CUtensorMapDataType, cuuint32_t, void*, const cuuint64_t*, const cuuint64_t*,
                                    const cuuint32_t*, const cuuint32_t*, CUtensorMapInterleave, CUtensorMapSwizzle,
                                    CUtensorMapL2promotion, CUtensorMapFloatOOBfill);

void make_map(PFN_encodeTiled enc, CUtensorMap* m, const void* base, int rank, const cuuint64_t* dims, const cuuint64_t* strides, const cuuint32_t* box) {
    cuuint32_t es[5] = {1, 1, 1, 1, 1};
    enc(m, CU_TENSOR_MAP_DATA_TYPE_BFLOAT16, (cuuint32_t)rank, const_cast<void*>(base), dims, strides, box, es,
        CU_TENSOR_MAP_INTERLEAVE_NONE, CU_TENSOR_MAP_SWIZZLE_128B, CU_TENSOR_MAP_L2_PROMOTION_L2_256B, CU_TENSOR_MAP_FLOAT_OOB_FILL_NONE);
}

}

extern "C" void kernel_launch(void* const* d_in, const int* in_sizes, int n_in, void* d_out, int out_size) {
    (void)in_sizes; (void)n_in; (void)out_size;
    const void* x = d_in[0]; const void* wqkv = d_in[1]; const void* wo = d_in[2];
    const void* w1 = d_in[4]; const void* w2 = d_in[5]; const void* gate_w = d_in[6];
    static PFN_encodeTiled enc = nullptr;
    static int ncta = 128;
    if (!enc) {
        int dev = 0, sms = 0;
        cudaGetDevice(&dev);
        cudaDeviceGetAttribute(&sms, cudaDevAttrMultiProcessorCount, dev);
        ncta = sms > 132 ? 132 : (sms > 128 ? sms : 128);
        void* fn = nullptr; cudaDriverEntryPointQueryResult st;
        cudaGetDriverEntryPoint("cuTensorMapEncodeTiled", &fn, cudaEnableDefault, &st);
        enc = (PFN_encodeTiled)fn;
        cudaFuncSetAttribute(fused_kernel, cudaFuncAttributeMaxDynamicSharedMemorySize, SMEM_BYTES);
    }
    CUtensorMap mx, mqkv, mw1, mw2, mwo, mw1a, mo;
    void* optr = nullptr;
    cudaGetSymbolAddress(&optr, g_o);
    { cuuint64_t d[2] = {512, 2048}, s[1] = {1024}; cuuint32_t b[2] = {64, 128}; make_map(enc, &mo, optr, 2, d, s, b); }
    { cuuint64_t d[4] = {64, 512, 3, 8}, s[3] = {3584, 128, 448}; cuuint32_t b[4] = {64, 32, 3, 1}; make_map(enc, &mw1a, w1, 4, d, s, b); }
    { cuuint64_t d[2] = {512, 2048}, s[1] = {1024}; cuuint32_t b[2] = {64, 128}; make_map(enc, &mx, x, 2, d, s, b); }
    { cuuint64_t d[4] = {64, 512, 8, 3}, s[3] = {3072, 128, 1024}; cuuint32_t b[4] = {64, 32, 1, 3}; make_map(enc, &mqkv, wqkv, 4, d, s, b); }
    { cuuint64_t d[2] = {1792, 512}, s[1] = {3584}; cuuint32_t b[2] = {64, 32}; make_map(enc, &mw1, w1, 2, d, s, b); }
    { cuuint64_t d[3] = {64, 1792, 8}, s[2] = {1024, 128}; cuuint32_t b[3] = {64, 32, 2}; make_map(enc, &mw2, w2, 3, d, s, b); }
    { cuuint64_t d[2] = {512, 512}, s[1] = {1024}; cuuint32_t b[2] = {64, 256}; make_map(enc, &mwo, wo, 2, d, s, b); }
    fused_kernel<<<ncta, 384, SMEM_BYTES, cudaStreamPerThread>>>(mx, mqkv, mw1, mw2, mwo, mw1a, mo, (const __nv_bfloat16*)gate_w, (__nv_bfloat16*)d_out,
                                           (const uint8_t*)w1, (const uint8_t*)w2, (const uint8_t*)wo);
}
```

```cpp
#include <cuda_runtime.h>
#include <cuda_bf16.h>
#include <cuda.h>
#include <stdint.h>

namespace {

#define PF1_AT 1
#define PF2_AT 5
#define LEAD1 1
constexpr int RING = 6;
constexpr int SLOT = 16384;
constexpr uint32_t X_OFF = 0;
constexpr uint32_t STG_OFF = X_OFF + 4 * 16384;
constexpr uint32_t RING_OFF = 131072;
constexpr uint32_t BAR_OFF = RING_OFF + RING * SLOT;
constexpr uint32_t B_FULL = BAR_OFF, B_EMPTY = BAR_OFF + 64, B_XFULL = BAR_OFF + 128, B_HDEAD = BAR_OFF + 192,
                   B_EREADY = BAR_OFF + 200, B_KVDONE = BAR_OFF + 208, B_ODONE = BAR_OFF + 224,
                   B_KVREADY = BAR_OFF + 232, B_WOFULL = BAR_OFF + 240, B_HSUM = BAR_OFF + 248, B_PREADY = BAR_OFF + 264,
                   B_SQ = BAR_OFF + 272, B_SF = BAR_OFF + 304, B_XDEAD = BAR_OFF + 320;
constexpr uint32_t EPOCH_OFF = BAR_OFF + 256, ITEM_OFF = BAR_OFF + 260, OSRC_OFF = BAR_OFF + 384;
constexpr uint32_t OWN_OFF = X_OFF + 4 * 16384;
constexpr uint32_t HSUM_OFF = X_OFF + 6 * 16384;
constexpr uint32_t SMEM_BYTES = BAR_OFF + 1024;

constexpr int N_QKV = 16, N_FFN1 = 16, N_FFN2 = 14, N_KV = 8, N_O = 7;

__device__ uint4 g_kf[32 * 128 * 32];
__device__ uint4 g_vf[32 * 128 * 32];
__device__ uint4 g_part[16 * 8 * 8 * 8 * 4 * 32];
__device__ __nv_bfloat16 g_o[2048 * 512];
__device__ unsigned g_ticket;
__device__ unsigned g_kvcnt[128 * 32];
__device__ unsigned g_pcnt[128 * 32];
__device__ unsigned g_ocnt[128 * 32];
#define TS(k) do {} while (0)
#define TS2(k) do {} while (0)
#define TS2X(k) do {} while (0)
#define TSX(k) do {} while (0)
#define TSG(k) do {} while (0)

__device__ __forceinline__ uint32_t smem_u32(const void* p) { return (uint32_t)__cvta_generic_to_shared(p); }
__device__ __forceinline__ void mbar_init(uint32_t bar, uint32_t cnt) { asm volatile("mbarrier.init.shared::cta.b64 [%0], %1;" :: "r"(bar), "r"(cnt) : "memory"); }
__device__ __forceinline__ void mbar_expect_tx(uint32_t bar, uint32_t bytes) { asm volatile("mbarrier.arrive.expect_tx.shared::cta.b64 _, [%0], %1;" :: "r"(bar), "r"(bytes) : "memory"); }
__device__ __forceinline__ void mbar_expect_only(uint32_t bar, uint32_t bytes) { asm volatile("mbarrier.expect_tx.relaxed.cta.shared::cta.b64 [%0], %1;" :: "r"(bar), "r"(bytes) : "memory"); }
__device__ __forceinline__ void mbar_arrive(uint32_t bar) { asm volatile("mbarrier.arrive.shared::cta.b64 _, [%0];" :: "r"(bar) : "memory"); }
__device__ __forceinline__ void mbar_wait(uint32_t bar, uint32_t parity) {
    asm volatile("{\n.reg .pred P1, P2;\n.reg .u32 n;\nmov.u32 n, 0;\n"
                 "WAIT_LOOP:\n"
                 "mbarrier.try_wait.parity.shared::cta.b64 P1, [%0], %1;\n"
                 "@P1 bra WAIT_DONE;\n"
                 "add.u32 n, n, 1;\n"
                 "setp.lt.u32 P2, n, 0x400000;\n"
                 "@P2 bra WAIT_LOOP;\n"
                 "WAIT_DONE:\n}" :: "r"(bar), "r"(parity) : "memory");
}
__device__ __forceinline__ void tma_2d(uint32_t dst, const void* map, uint32_t bar, int c0, int c1) {
    asm volatile("cp.async.bulk.tensor.2d.shared::cluster.global.mbarrier::complete_tx::bytes [%0], [%1, {%3, %4}], [%2];"
        :: "r"(dst), "l"(map), "r"(bar), "r"(c0), "r"(c1) : "memory");
}
__device__ __forceinline__ void tma_3d(uint32_t dst, const void* map, uint32_t bar, int c0, int c1, int c2) {
    asm volatile("cp.async.bulk.tensor.3d.shared::cluster.global.mbarrier::complete_tx::bytes [%0], [%1, {%3, %4, %5}], [%2];"
        :: "r"(dst), "l"(map), "r"(bar), "r"(c0), "r"(c1), "r"(c2) : "memory");
}
__device__ __forceinline__ void tma_4d(uint32_t dst, const void* map, uint32_t bar, int c0, int c1, int c2, int c3) {
    asm volatile("cp.async.bulk.tensor.4d.shared::cluster.global.mbarrier::complete_tx::bytes [%0], [%1, {%3, %4, %5, %6}], [%2];"
        :: "r"(dst), "l"(map), "r"(bar), "r"(c0), "r"(c1), "r"(c2), "r"(c3) : "memory");
}
__device__ __forceinline__ void bulk_g2s(uint32_t dst, const void* src, uint32_t bytes, uint32_t bar) {
    asm volatile("cp.async.bulk.shared::cluster.global.mbarrier::complete_tx::bytes [%0], [%1], %2, [%3];"
        :: "r"(dst), "l"(src), "r"(bytes), "r"(bar) : "memory");
}
__device__ __forceinline__ void prefetch_l2(const void* src, uint32_t bytes) {
    asm volatile("cp.async.bulk.prefetch.L2.global [%0], %1;" :: "l"(src), "r"(bytes) : "memory");
}
__device__ __forceinline__ bool elect_one() {
    uint32_t p;
    asm volatile("{\n.reg .pred P;\nelect.sync _|P, 0xffffffff;\nselp.u32 %0, 1, 0, P;\n}" : "=r"(p));
    return p != 0;
}
__device__ __forceinline__ void wgmma_fence() { asm volatile("wgmma.fence.sync.aligned;" ::: "memory"); }
__device__ __forceinline__ void wgmma_commit() { asm volatile("wgmma.commit_group.sync.aligned;" ::: "memory"); }
template <int N> __device__ __forceinline__ void wgmma_wait() { asm volatile("wgmma.wait_group.sync.aligned %0;" :: "n"(N) : "memory"); }
__device__ __forceinline__ void fence_async_smem() { asm volatile("fence.proxy.async.shared::cta;" ::: "memory"); }
__device__ __forceinline__ uint64_t desc_a(uint32_t addr) {
    return (uint64_t)((addr & 0x3FFFF) >> 4) | ((uint64_t)1 << 16) | ((uint64_t)(1024 >> 4) << 32) | ((uint64_t)1 << 62);
}
__device__ __forceinline__ uint64_t desc_b(uint32_t addr) {
    return (uint64_t)((addr & 0x3FFFF) >> 4) | ((uint64_t)(4096 >> 4) << 16) | ((uint64_t)(1024 >> 4) << 32) | ((uint64_t)1 << 62);
}
__device__ __forceinline__ uint32_t pack_bf16(float lo, float hi) {
    uint32_t r; asm("cvt.rn.bf16x2.f32 %0, %1, %2;" : "=r"(r) : "f"(hi), "f"(lo)); return r;
}
__device__ __forceinline__ uint32_t pack_bf16_relu(float lo, float hi) {
    uint32_t r; asm("cvt.rn.relu.bf16x2.f32 %0, %1, %2;" : "=r"(r) : "f"(hi), "f"(lo)); return r;
}
__device__ __forceinline__ uint32_t movmatrix(uint32_t a) {
    uint32_t d; asm volatile("movmatrix.sync.aligned.m8n8.trans.b16 %0, %1;" : "=r"(d) : "r"(a)); return d;
}
__device__ __forceinline__ void stmatrix_x4(uint32_t addr, uint32_t r0, uint32_t r1, uint32_t r2, uint32_t r3) {
    asm volatile("stmatrix.sync.aligned.m8n8.x4.shared.b16 [%0], {%1, %2, %3, %4};" :: "r"(addr), "r"(r0), "r"(r1), "r"(r2), "r"(r3) : "memory");
}
__device__ __forceinline__ uint4 lds128(uint32_t addr) {
    uint4 v; asm volatile("ld.shared.v4.b32 {%0, %1, %2, %3}, [%4];" : "=r"(v.x), "=r"(v.y), "=r"(v.z), "=r"(v.w) : "r"(addr) : "memory"); return v;
}
__device__ __forceinline__ uint4 lds128_free(uint32_t addr) {
    uint4 v; asm("ld.shared.v4.b32 {%0, %1, %2, %3}, [%4];" : "=r"(v.x), "=r"(v.y), "=r"(v.z), "=r"(v.w) : "r"(addr)); return v;
}
__device__ __forceinline__ void mma16816(float (&c)[4], uint32_t a0, uint32_t a1, uint32_t a2, uint32_t a3, uint32_t b0, uint32_t b1) {
    asm("mma.sync.aligned.m16n8k16.row.col.f32.bf16.bf16.f32 {%0,%1,%2,%3}, {%4,%5,%6,%7}, {%8,%9}, {%0,%1,%2,%3};"
        : "+f"(c[0]), "+f"(c[1]), "+f"(c[2]), "+f"(c[3]) : "r"(a0), "r"(a1), "r"(a2), "r"(a3), "r"(b0), "r"(b1));
}
__device__ __forceinline__ void mma16816_c(float (&c)[4], uint32_t a0, uint32_t a1, uint32_t a2, uint32_t a3, uint32_t b0, uint32_t b1, float ci) {
    asm("mma.sync.aligned.m16n8k16.row.col.f32.bf16.bf16.f32 {%0,%1,%2,%3}, {%4,%5,%6,%7}, {%8,%9}, {%10,%10,%10,%10};"
        : "=f"(c[0]), "=f"(c[1]), "=f"(c[2]), "=f"(c[3]) : "r"(a0), "r"(a1), "r"(a2), "r"(a3), "r"(b0), "r"(b1), "f"(ci));
}
__device__ __forceinline__ int opaque(int v) { asm volatile("" : "+r"(v)); return v; }
__device__ __forceinline__ float ex2(float x) { float y; asm("ex2.approx.ftz.f32 %0, %1;" : "=f"(y) : "f"(x)); return y; }
__device__ __forceinline__ unsigned ld_acquire(const unsigned* p) {
    unsigned v; asm volatile("ld.acquire.gpu.global.u32 %0, [%1];" : "=r"(v) : "l"(p) : "memory"); return v;
}
__device__ __forceinline__ void red_release(unsigned* p, unsigned v) {
    asm volatile("red.release.gpu.global.add.u32 [%0], %1;" :: "l"(p), "r"(v) : "memory");
}
__device__ __forceinline__ void wait_counter(const unsigned* p, unsigned target) {
    uint32_t n = 0;
    while ((int)(ld_acquire(p) - target) < 0) { if (++n > (1u << 20)) break; }
}
__device__ __forceinline__ uint4 ldg_weak(const uint4* p) {
    uint4 v; asm volatile("ld.global.L1::no_allocate.v4.b32 {%0, %1, %2, %3}, [%4];" : "=r"(v.x), "=r"(v.y), "=r"(v.z), "=r"(v.w) : "l"(p) : "memory"); return v;
}
__device__ __forceinline__ float bf_lo(uint32_t v) { return __uint_as_float(v << 16); }
__device__ __forceinline__ float bf_hi(uint32_t v) { return __uint_as_float(v & 0xFFFF0000u); }

__device__ __forceinline__ void wgmma_ss_n64(float (&d)[32], uint64_t da, uint64_t db, int scale_d) {
    asm volatile("{\n.reg .pred p;\nsetp.ne.b32 p, %34, 0;\n"
        "wgmma.mma_async.sync.aligned.m64n64k16.f32.bf16.bf16 {%0, %1, %2, %3, %4, %5, %6, %7, %8, %9, %10, %11, %12, %13, %14, %15, %16, %17, %18, %19, %20, %21, %22, %23, %24, %25, %26, %27, %28, %29, %30, %31}, %32, %33, p, 1, 1, 0, 1;\n}\n"
        : "+f"(d[0]), "+f"(d[1]), "+f"(d[2]), "+f"(d[3]), "+f"(d[4]), "+f"(d[5]), "+f"(d[6]), "+f"(d[7]), "+f"(d[8]), "+f"(d[9]), "+f"(d[10]), "+f"(d[11]), "+f"(d[12]), "+f"(d[13]), "+f"(d[14]), "+f"(d[15]), "+f"(d[16]), "+f"(d[17]), "+f"(d[18]), "+f"(d[19]), "+f"(d[20]), "+f"(d[21]), "+f"(d[22]), "+f"(d[23]), "+f"(d[24]), "+f"(d[25]), "+f"(d[26]), "+f"(d[27]), "+f"(d[28]), "+f"(d[29]), "+f"(d[30]), "+f"(d[31])
        : "l"(da), "l"(db), "r"(scale_d));
}
__device__ __forceinline__ void wgmma_ss_n128(float (&d)[64], uint64_t da, uint64_t db, int scale_d) {
    asm volatile("{\n.reg .pred p;\nsetp.ne.b32 p, %66, 0;\n"
        "wgmma.mma_async.sync.aligned.m64n128k16.f32.bf16.bf16 {%0, %1, %2, %3, %4, %5, %6, %7, %8, %9, %10, %11, %12, %13, %14, %15, %16, %17, %18, %19, %20, %21, %22, %23, %24, %25, %26, %27, %28, %29, %30, %31, %32, %33, %34, %35, %36, %37, %38, %39, %40, %41, %42, %43, %44, %45, %46, %47, %48, %49, %50, %51, %52, %53, %54, %55, %56, %57, %58, %59, %60, %61, %62, %63}, %64, %65, p, 1, 1, 0, 1;\n}\n"
        : "+f"(d[0]), "+f"(d[1]), "+f"(d[2]), "+f"(d[3]), "+f"(d[4]), "+f"(d[5]), "+f"(d[6]), "+f"(d[7]), "+f"(d[8]), "+f"(d[9]), "+f"(d[10]), "+f"(d[11]), "+f"(d[12]), "+f"(d[13]), "+f"(d[14]), "+f"(d[15]), "+f"(d[16]), "+f"(d[17]), "+f"(d[18]), "+f"(d[19]), "+f"(d[20]), "+f"(d[21]), "+f"(d[22]), "+f"(d[23]), "+f"(d[24]), "+f"(d[25]), "+f"(d[26]), "+f"(d[27]), "+f"(d[28]), "+f"(d[29]), "+f"(d[30]), "+f"(d[31]), "+f"(d[32]), "+f"(d[33]), "+f"(d[34]), "+f"(d[35]), "+f"(d[36]), "+f"(d[37]), "+f"(d[38]), "+f"(d[39]), "+f"(d[40]), "+f"(d[41]), "+f"(d[42]), "+f"(d[43]), "+f"(d[44]), "+f"(d[45]), "+f"(d[46]), "+f"(d[47]), "+f"(d[48]), "+f"(d[49]), "+f"(d[50]), "+f"(d[51]), "+f"(d[52]), "+f"(d[53]), "+f"(d[54]), "+f"(d[55]), "+f"(d[56]), "+f"(d[57]), "+f"(d[58]), "+f"(d[59]), "+f"(d[60]), "+f"(d[61]), "+f"(d[62]), "+f"(d[63])
        : "l"(da), "l"(db), "r"(scale_d));
}
__device__ __forceinline__ void wgmma_ss_n200(float (&d)[100], uint64_t da, uint64_t db, int scale_d) {
    asm volatile("{\n.reg .pred p;\nsetp.ne.b32 p, %102, 0;\n"
        "wgmma.mma_async.sync.aligned.m64n200k16.f32.bf16.bf16 {%0, %1, %2, %3, %4, %5, %6, %7, %8, %9, %10, %11, %12, %13, %14, %15, %16, %17, %18, %19, %20, %21, %22, %23, %24, %25, %26, %27, %28, %29, %30, %31, %32, %33, %34, %35, %36, %37, %38, %39, %40, %41, %42, %43, %44, %45, %46, %47, %48, %49, %50, %51, %52, %53, %54, %55, %56, %57, %58, %59, %60, %61, %62, %63, %64, %65, %66, %67, %68, %69, %70, %71, %72, %73, %74, %75, %76, %77, %78, %79, %80, %81, %82, %83, %84, %85, %86, %87, %88, %89, %90, %91, %92, %93, %94, %95, %96, %97, %98, %99}, %100, %101, p, 1, 1, 0, 1;\n}\n"
        : "+f"(d[0]), "+f"(d[1]), "+f"(d[2]), "+f"(d[3]), "+f"(d[4]), "+f"(d[5]), "+f"(d[6]), "+f"(d[7]), "+f"(d[8]), "+f"(d[9]), "+f"(d[10]), "+f"(d[11]), "+f"(d[12]), "+f"(d[13]), "+f"(d[14]), "+f"(d[15]), "+f"(d[16]), "+f"(d[17]), "+f"(d[18]), "+f"(d[19]), "+f"(d[20]), "+f"(d[21]), "+f"(d[22]), "+f"(d[23]), "+f"(d[24]), "+f"(d[25]), "+f"(d[26]), "+f"(d[27]), "+f"(d[28]), "+f"(d[29]), "+f"(d[30]), "+f"(d[31]), "+f"(d[32]), "+f"(d[33]), "+f"(d[34]), "+f"(d[35]), "+f"(d[36]), "+f"(d[37]), "+f"(d[38]), "+f"(d[39]), "+f"(d[40]), "+f"(d[41]), "+f"(d[42]), "+f"(d[43]), "+f"(d[44]), "+f"(d[45]), "+f"(d[46]), "+f"(d[47]), "+f"(d[48]), "+f"(d[49]), "+f"(d[50]), "+f"(d[51]), "+f"(d[52]), "+f"(d[53]), "+f"(d[54]), "+f"(d[55]), "+f"(d[56]), "+f"(d[57]), "+f"(d[58]), "+f"(d[59]), "+f"(d[60]), "+f"(d[61]), "+f"(d[62]), "+f"(d[63]), "+f"(d[64]), "+f"(d[65]), "+f"(d[66]), "+f"(d[67]), "+f"(d[68]), "+f"(d[69]), "+f"(d[70]), "+f"(d[71]), "+f"(d[72]), "+f"(d[73]), "+f"(d[74]), "+f"(d[75]), "+f"(d[76]), "+f"(d[77]), "+f"(d[78]), "+f"(d[79]), "+f"(d[80]), "+f"(d[81]), "+f"(d[82]), "+f"(d[83]), "+f"(d[84]), "+f"(d[85]), "+f"(d[86]), "+f"(d[87]), "+f"(d[88]), "+f"(d[89]), "+f"(d[90]), "+f"(d[91]), "+f"(d[92]), "+f"(d[93]), "+f"(d[94]), "+f"(d[95]), "+f"(d[96]), "+f"(d[97]), "+f"(d[98]), "+f"(d[99])
        : "l"(da), "l"(db), "r"(scale_d));
}
__device__ __forceinline__ void wgmma_ss_n224(float (&d)[112], uint64_t da, uint64_t db, int scale_d) {
    asm volatile("{\n.reg .pred p;\nsetp.ne.b32 p, %114, 0;\n"
        "wgmma.mma_async.sync.aligned.m64n224k16.f32.bf16.bf16 {%0, %1, %2, %3, %4, %5, %6, %7, %8, %9, %10, %11, %12, %13, %14, %15, %16, %17, %18, %19, %20, %21, %22, %23, %24, %25, %26, %27, %28, %29, %30, %31, %32, %33, %34, %35, %36, %37, %38, %39, %40, %41, %42, %43, %44, %45, %46, %47, %48, %49, %50, %51, %52, %53, %54, %55, %56, %57, %58, %59, %60, %61, %62, %63, %64, %65, %66, %67, %68, %69, %70, %71, %72, %73, %74, %75, %76, %77, %78, %79, %80, %81, %82, %83, %84, %85, %86, %87, %88, %89, %90, %91, %92, %93, %94, %95, %96, %97, %98, %99, %100, %101, %102, %103, %104, %105, %106, %107, %108, %109, %110, %111}, %112, %113, p, 1, 1, 0, 1;\n}\n"
        : "+f"(d[0]), "+f"(d[1]), "+f"(d[2]), "+f"(d[3]), "+f"(d[4]), "+f"(d[5]), "+f"(d[6]), "+f"(d[7]), "+f"(d[8]), "+f"(d[9]), "+f"(d[10]), "+f"(d[11]), "+f"(d[12]), "+f"(d[13]), "+f"(d[14]), "+f"(d[15]), "+f"(d[16]), "+f"(d[17]), "+f"(d[18]), "+f"(d[19]), "+f"(d[20]), "+f"(d[21]), "+f"(d[22]), "+f"(d[23]), "+f"(d[24]), "+f"(d[25]), "+f"(d[26]), "+f"(d[27]), "+f"(d[28]), "+f"(d[29]), "+f"(d[30]), "+f"(d[31]), "+f"(d[32]), "+f"(d[33]), "+f"(d[34]), "+f"(d[35]), "+f"(d[36]), "+f"(d[37]), "+f"(d[38]), "+f"(d[39]), "+f"(d[40]), "+f"(d[41]), "+f"(d[42]), "+f"(d[43]), "+f"(d[44]), "+f"(d[45]), "+f"(d[46]), "+f"(d[47]), "+f"(d[48]), "+f"(d[49]), "+f"(d[50]), "+f"(d[51]), "+f"(d[52]), "+f"(d[53]), "+f"(d[54]), "+f"(d[55]), "+f"(d[56]), "+f"(d[57]), "+f"(d[58]), "+f"(d[59]), "+f"(d[60]), "+f"(d[61]), "+f"(d[62]), "+f"(d[63]), "+f"(d[64]), "+f"(d[65]), "+f"(d[66]), "+f"(d[67]), "+f"(d[68]), "+f"(d[69]), "+f"(d[70]), "+f"(d[71]), "+f"(d[72]), "+f"(d[73]), "+f"(d[74]), "+f"(d[75]), "+f"(d[76]), "+f"(d[77]), "+f"(d[78]), "+f"(d[79]), "+f"(d[80]), "+f"(d[81]), "+f"(d[82]), "+f"(d[83]), "+f"(d[84]), "+f"(d[85]), "+f"(d[86]), "+f"(d[87]), "+f"(d[88]), "+f"(d[89]), "+f"(d[90]), "+f"(d[91]), "+f"(d[92]), "+f"(d[93]), "+f"(d[94]), "+f"(d[95]), "+f"(d[96]), "+f"(d[97]), "+f"(d[98]), "+f"(d[99]), "+f"(d[100]), "+f"(d[101]), "+f"(d[102]), "+f"(d[103]), "+f"(d[104]), "+f"(d[105]), "+f"(d[106]), "+f"(d[107]), "+f"(d[108]), "+f"(d[109]), "+f"(d[110]), "+f"(d[111])
        : "l"(da), "l"(db), "r"(scale_d));
}
template <int N> __device__ __forceinline__ void fence_acc(float (&d)[N]) {
#pragma unroll
    for (int i = 0; i < N; i++) asm volatile("" : "+f"(d[i]) :: "memory");
}

__device__ __forceinline__ void bulk_s2g(void* dst, uint32_t src, uint32_t bytes) {
    asm volatile("cp.async.bulk.global.shared::cta.bulk_group [%0], [%1], %2;" :: "l"(dst), "r"(src), "r"(bytes) : "memory");
}
__device__ __forceinline__ void sts128(uint32_t addr, uint4 v) {
    asm volatile("st.shared.v4.b32 [%0], {%1, %2, %3, %4};" :: "r"(addr), "r"(v.x), "r"(v.y), "r"(v.z), "r"(v.w) : "memory");
}
__device__ __forceinline__ void sum_partials(uint32_t sb, int ti, int tj, int lane) {
    for (;;) {
        uint32_t item = 0;
        if (lane == 0) asm volatile("atom.shared.add.u32 %0, [%1], 1;" : "=r"(item) : "r"(sb + ITEM_OFF) : "memory");
        item = __shfl_sync(0xffffffffu, item, 0);
        if (item >= 8) break;
        const uint4* p = g_part + (size_t)((ti * 8 + tj) * 8) * 1024 + item * 128 + lane;
        uint4 v[4][4];
#pragma unroll
        for (int s = 0; s < 4; s++)
#pragma unroll
            for (int n = 0; n < 4; n++) v[n][s] = ldg_weak(p + s * 1024 + n * 32);
#pragma unroll
        for (int n = 0; n < 4; n++) {
            float a[8];
#pragma unroll
            for (int e = 0; e < 8; e++) a[e] = 0.f;
#pragma unroll
            for (int s = 0; s < 4; s++) {
                a[0] += bf_lo(v[n][s].x); a[1] += bf_hi(v[n][s].x); a[2] += bf_lo(v[n][s].y); a[3] += bf_hi(v[n][s].y);
                a[4] += bf_lo(v[n][s].z); a[5] += bf_hi(v[n][s].z); a[6] += bf_lo(v[n][s].w); a[7] += bf_hi(v[n][s].w);
            }
            const uint32_t d = sb + HSUM_OFF + (item * 8 + n * 2) * 512 + lane * 16;
            sts128(d, make_uint4(__float_as_uint(a[0]), __float_as_uint(a[1]), __float_as_uint(a[2]), __float_as_uint(a[3])));
            sts128(d + 512, make_uint4(__float_as_uint(a[4]), __float_as_uint(a[5]), __float_as_uint(a[6]), __float_as_uint(a[7])));
        }
    }
    __syncwarp();
    if (lane == 0) mbar_arrive(sb + B_HSUM);
}

#define PWAIT() mbar_wait(sb + B_EMPTY + 8 * r.slot, r.phase)
#define CWAIT() do { if (!dry) mbar_wait(sb + B_FULL + 8 * r.slot, r.phase); } while (0)
template <bool B> struct BoolTag { static constexpr bool value = B; };
struct Ring {
    int slot; uint32_t phase;
    __device__ __forceinline__ void next() { if (++slot == RING) { slot = 0; phase ^= 1; } }
};

__global__ void __launch_bounds__(384, 1)
fused_kernel(const __grid_constant__ CUtensorMap map_x, const __grid_constant__ CUtensorMap map_qkv,
             const __grid_constant__ CUtensorMap map_w1, const __grid_constant__ CUtensorMap map_w2,
             const __grid_constant__ CUtensorMap map_wo, const __grid_constant__ CUtensorMap map_w1a,
             const __grid_constant__ CUtensorMap map_o,
             const __nv_bfloat16* __restrict__ gate_w, __nv_bfloat16* __restrict__ out,
             const uint8_t* __restrict__ w1p, const uint8_t* __restrict__ w2p, const uint8_t* __restrict__ wop)
{
    extern __shared__ __align__(1024) uint8_t smem_raw[];
    const uint32_t sb = smem_u32(smem_raw);
    const int tid = threadIdx.x, warp = tid >> 5, lane = tid & 31;
    const bool dry = blockIdx.x >= 128;
    const int ti = dry ? (int)(blockIdx.x & 1) * 2 : blockIdx.x >> 3, tj = blockIdx.x & 7;
    if (dry && warp >= 8) {
        asm volatile("setmaxnreg.dec.sync.aligned.u32 88;");
        return;
    }

    if (tid == 0 && !dry) { TSG(31); TSX(0); }
    if (tid == 320) {
        asm volatile("prefetch.tensormap [%0];" :: "l"(&map_x) : "memory");
        asm volatile("prefetch.tensormap [%0];" :: "l"(&map_qkv) : "memory");
        asm volatile("prefetch.tensormap [%0];" :: "l"(&map_w1) : "memory");
        asm volatile("prefetch.tensormap [%0];" :: "l"(&map_w1a) : "memory");
        asm volatile("prefetch.tensormap [%0];" :: "l"(&map_w2) : "memory");
        asm volatile("prefetch.tensormap [%0];" :: "l"(&map_wo) : "memory");
        asm volatile("prefetch.tensormap [%0];" :: "l"(&map_o) : "memory");
    }
    if (tid == 256) {
        mbar_init(sb + B_FULL, 1); mbar_init(sb + B_XFULL, 1);
        fence_async_smem();
        mbar_expect_tx(sb + B_XFULL, 16384);
        tma_2d(sb + X_OFF, &map_x, sb + B_XFULL, 0, ti * 128);
        mbar_expect_only(sb + B_FULL, 12288);
        tma_4d(sb + RING_OFF, &map_qkv, sb + B_FULL, 0, 0, tj, 0);
    }
    uint32_t gwv[N_QKV / 2];
    if (warp == 8) {
        const unsigned short* gws = reinterpret_cast<const unsigned short*>(gate_w);
#pragma unroll
        for (int n = 0; n < N_QKV / 2; n++) gwv[n] = (uint32_t)__ldg(gws + 64 * n + lane) | ((uint32_t)__ldg(gws + 64 * n + 32 + lane) << 16);
    }
    if (tid == 288) {
        for (int s = 1; s < RING; s++) mbar_init(sb + B_FULL + 8 * s, 1);
        for (int s = 0; s < RING; s++) mbar_init(sb + B_EMPTY + 8 * s, 8);
        for (int s = 1; s < 8; s++) mbar_init(sb + B_XFULL + 8 * s, 1);
        fence_async_smem();
    }
    if (tid == 352) {
        mbar_init(sb + B_HDEAD, 8); mbar_init(sb + B_EREADY, 1); mbar_init(sb + B_KVDONE, 8); mbar_init(sb + B_KVREADY, 1);
        mbar_init(sb + B_ODONE, 8); mbar_init(sb + B_WOFULL, 1); mbar_init(sb + B_HSUM, 3);
        mbar_init(sb + B_XDEAD, 8); mbar_init(sb + B_PREADY, 1); mbar_init(sb + B_SF, 1); mbar_init(sb + B_SF + 8, 1);
        for (int s = 0; s < 4; s++) mbar_init(sb + B_SQ + 8 * s, 8);
        asm volatile("st.shared.u32 [%0], %1;" :: "r"(sb + ITEM_OFF), "r"(0) : "memory");
        fence_async_smem();
    }
    if (!dry) __syncthreads();

    if (warp >= 8) {
        asm volatile("setmaxnreg.dec.sync.aligned.u32 88;");
        if (warp == 8) {
            Ring r{0, 1};
            const bool leader = elect_one();
#pragma unroll
            for (int n = 0; n < N_QKV; n++) {
                const uint32_t full = sb + B_FULL + 8 * r.slot, dst = sb + RING_OFF + r.slot * SLOT;
                if (n > 0) {
                    if (!(n & 1) && leader) {
                        mbar_expect_tx(sb + B_XFULL + 8 * (n >> 1), 16384);
                        tma_2d(sb + X_OFF + (n >> 1) * 16384, &map_x, sb + B_XFULL + 8 * (n >> 1), (n >> 1) * 64, ti * 128);
                    }
                    if (n >= RING) PWAIT();
                    if (leader) {
                        mbar_expect_only(full, 12288);
                        tma_4d(dst, &map_qkv, full, 0, 32 * n, tj, 0);
                    }
                }
                const uint32_t gv = (n & 1) ? (gwv[n >> 1] >> 16) : (gwv[n >> 1] & 0xFFFFu);
                asm volatile("st.shared.v4.b32 [%0], {%1, %2, %2, %2};" :: "r"(dst + 12288 + lane * 128 + ((lane & 7) << 4)), "r"(gv), "r"(0) : "memory");
                fence_async_smem();
                __syncwarp();
                if (leader) mbar_arrive(full);
                r.next();
            }
#pragma unroll 1
            for (int n = 0; n < N_FFN1; n++) {
                const uint32_t full = sb + B_FULL + 8 * r.slot, dst = sb + RING_OFF + r.slot * SLOT;
                PWAIT();
                if (leader) {
                    mbar_expect_tx(full, 16384);
                    tma_4d(dst, &map_w1a, full, 0, 32 * n, 0, tj);
                    tma_2d(dst + 3 * 4096, &map_w1, full, 224 * tj + 192, 32 * n);
                }
                r.next();
            }
            {
                int q = 0, rr = 0;
#pragma unroll 1
                for (int n = 0; n < N_FFN2; n++) {
                    const uint32_t full = sb + B_FULL + 8 * r.slot, dst = sb + RING_OFF + r.slot * SLOT;
                    PWAIT();
                    if (leader) mbar_expect_tx(full, 16384);
#pragma unroll
                    for (int h = 0; h < 2; h++) {
                        if (leader) tma_3d(dst + h * 8192, &map_w2, full, 0, 224 * tj + 32 * rr, 2 * q);
                        if (++rr == 7) { rr = 0; q++; }
                    }
                    r.next();
                }
            }
            mbar_wait(sb + B_KVREADY, 0);
            asm volatile("fence.proxy.async.global;" ::: "memory");
            {
                const int bbase = 8 * ti - 16, b0 = bbase < 0 ? 0 : bbase;
                const uint32_t bytes = (uint32_t)(8 * ti + 8 - b0) * 512;
#pragma unroll 1
                for (int m = 0; m < N_KV; m++) {
                    const uint32_t full = sb + B_FULL + 8 * r.slot, dst = sb + RING_OFF + r.slot * SLOT;
                    if (m == RING) {
                        mbar_wait(sb + B_HDEAD, 0);
                        if (leader) {
                            mbar_expect_tx(sb + B_WOFULL, 65536);
#pragma unroll
                            for (int e = 0; e < 2; e++) tma_2d(sb + X_OFF + e * 32768, &map_wo, sb + B_WOFULL, 64 * tj, 256 * e);
                        }
                    }
                    PWAIT();
                    if (leader) {
                        const uint4* src = ((m & 1) ? g_vf : g_kf) + ((tj * 4 + (m >> 1)) * 128 + b0) * 32;
                        mbar_expect_tx(full, bytes);
                        bulk_g2s(dst + (b0 - bbase) * 512, src, bytes, full);
                    }
                    r.next();
                }
            }
            {
                mbar_wait(sb + B_EREADY, 0);
                unsigned epoch; asm volatile("ld.shared.u32 %0, [%1];" : "=r"(epoch) : "r"(sb + EPOCH_OFF) : "memory");
                uint32_t pending = 0xFFu & ~(1u << tj), ready = 0;
                mbar_wait(sb + B_HSUM, 0);
#pragma unroll 1
                for (int m = 0; m < N_O; m++) {
                    const uint32_t full = sb + B_FULL + 8 * r.slot, dst = sb + RING_OFF + r.slot * SLOT;
                    PWAIT();
                    for (int it = 0; it < (1 << 20) && !ready; it++) {
                        bool ok = false;
                        if (lane < 8 && ((pending >> lane) & 1)) ok = (int)(ld_acquire(&g_ocnt[(ti * 8 + lane) * 32]) - (epoch + 1)) >= 0;
                        ready = __ballot_sync(0xffffffffu, ok);
                        if (!ready) __nanosleep(100);
                    }
                    const int js = ready ? __ffs(ready) - 1 : __ffs(pending) - 1;
                    pending &= ~(1u << js); ready &= ~(1u << js);
                    asm volatile("fence.proxy.async.global;" ::: "memory");
                    if (leader) {
                        asm volatile("st.shared.u32 [%0], %1;" :: "r"(sb + OSRC_OFF + 4 * m), "r"(js) : "memory");
                        mbar_expect_tx(full, 16384);
                        tma_2d(dst, &map_o, full, 64 * js, ti * 128);
                    }
                    r.next();
                }
            }
        } else if (warp == 9) {
            unsigned epoch = 0;
            if (lane == 0) {
                epoch = atomicAdd(&g_ticket, 1u) >> 7;
                asm volatile("st.shared.u32 [%0], %1;" :: "r"(sb + EPOCH_OFF), "r"(epoch) : "memory");
                mbar_arrive(sb + B_EREADY);
                mbar_wait(sb + B_XFULL + 8 * PF1_AT, 0);
                prefetch_l2(w1p + (size_t)blockIdx.x * 14336, 14336);
                mbar_wait(sb + B_XFULL + 8 * PF2_AT, 0);
                prefetch_l2(w2p + (size_t)blockIdx.x * 14336, 14336);
                prefetch_l2(wop + (size_t)blockIdx.x * 4096, 4096);
                mbar_wait(sb + B_KVDONE, 0);
                red_release(&g_kvcnt[blockIdx.x * 32], 1u);
            }
            epoch = __shfl_sync(0xffffffffu, epoch, 0);
            if (lane < 3 && ti - lane >= 0) wait_counter(&g_kvcnt[((ti - lane) * 8 + tj) * 32], epoch + 1);
            __syncwarp();
            if (lane == 0) mbar_arrive(sb + B_KVREADY);
            mbar_wait(sb + B_SQ + 24, 0);
            if (lane < 8) wait_counter(&g_pcnt[(ti * 8 + lane) * 32], epoch + 1);
            __syncwarp();
            if (lane == 0) { mbar_arrive(sb + B_PREADY); TSX(13); }
            sum_partials(sb, ti, tj, lane);
            if (lane == 0) TSX(14);
        } else {
            if (warp == 10) {
#pragma unroll 1
                for (int q = 0; q < 4; q++) {
                    mbar_wait(sb + B_SQ + 8 * q, 0);
                    if (lane < 16) {
                        uint4* d = g_part + (size_t)(((ti * 8 + 2 * q + (lane & 1)) * 8 + tj) * 8 + (lane >> 1)) * 128;
                        bulk_s2g(d, sb + STG_OFF + (q & 1) * 32768 + lane * 2048, 2048);
                        asm volatile("cp.async.bulk.commit_group;" ::: "memory");
                        asm volatile("cp.async.bulk.wait_group.read 0;" ::: "memory");
                    }
                    __syncwarp();
                    if (lane == 0) mbar_arrive(sb + B_SF + 8 * (q & 1));
                }
                asm volatile("cp.async.bulk.wait_group 0;" ::: "memory");
                asm volatile("fence.proxy.async.global;" ::: "memory");
                __syncwarp();
                if (lane == 0) { red_release(&g_pcnt[blockIdx.x * 32], 1u); TSX(12); }
            }
            mbar_wait(sb + B_PREADY, 0);
            sum_partials(sb, ti, tj, lane);
            if (warp == 11 && lane == 0) {
                mbar_wait(sb + B_ODONE, 0);
                red_release(&g_ocnt[blockIdx.x * 32], 1u);
            }
        }
    } else {
        asm volatile("setmaxnreg.inc.sync.aligned.u32 208;");
        const int wg = warp >> 2, g = lane >> 2, c = lane & 3;
        const uint32_t xa = sb + X_OFF + wg * 8192;
        Ring r{0, 0};
        const bool lane0 = lane == 0 && !dry;
        uint32_t qf[4][4];
        float g0, g1;
        TS(9);
        {
            float acc[100];
            int prev = 0;
            if (wg == 1) asm volatile("bar.sync 3, 256;" ::: "memory");
            for (int s = 0; s < (dry ? 4 : N_QKV); s++) {
                if (!(s & 1) && !dry) mbar_wait(sb + B_XFULL + 8 * (s >> 1), 0);
                CWAIT();
                if (s == 0) TS(1);
                if (s == 2) TS(28);
                if (s == 6) TS(29);
                if (s == 10) TS(20);
                const uint32_t bs = sb + RING_OFF + r.slot * SLOT, as = xa + (s >> 1) * 16384 + (s & 1) * 64;
                wgmma_fence();
                wgmma_ss_n200(acc, desc_a(as), desc_b(bs), s);
                wgmma_ss_n200(acc, desc_a(as + 32), desc_b(bs + 2048), 1);
                wgmma_commit();
                if (wg == 0 && s == LEAD1) asm volatile("bar.arrive 3, 256;" ::: "memory");
                if (s > 0) { wgmma_wait<1>(); if (lane0) mbar_arrive(sb + B_EMPTY + 8 * prev); }
                prev = r.slot; r.next();
            }
            wgmma_wait<0>();
            fence_acc(acc);
            if (lane0) mbar_arrive(sb + B_EMPTY + 8 * prev);
            TS(2);
            const int blk = ti * 8 + warp;
#pragma unroll
            for (int hh = 0; hh < 4; hh++) {
                const float* t0 = &acc[8 * hh]; const float* t1 = &acc[8 * hh + 4];
                qf[hh][0] = pack_bf16(t0[0], t0[1]); qf[hh][1] = pack_bf16(t0[2], t0[3]);
                qf[hh][2] = pack_bf16(t1[0], t1[1]); qf[hh][3] = pack_bf16(t1[2], t1[3]);
                const float* k0 = &acc[32 + 8 * hh]; const float* k1 = &acc[32 + 8 * hh + 4];
                uint4 kv;
                kv.x = pack_bf16(k0[0], k0[1]); kv.y = pack_bf16(k1[0], k1[1]);
                kv.z = pack_bf16(k0[2], k0[3]); kv.w = pack_bf16(k1[2], k1[3]);
                if (!dry) g_kf[((tj * 4 + hh) * 128 + blk) * 32 + lane] = kv;
                const float* v0 = &acc[64 + 8 * hh]; const float* v1 = &acc[64 + 8 * hh + 4];
                uint4 vv;
                vv.x = movmatrix(pack_bf16(v0[0], v0[1])); vv.y = movmatrix(pack_bf16(v0[2], v0[3]));
                vv.z = movmatrix(pack_bf16(v1[0], v1[1])); vv.w = movmatrix(pack_bf16(v1[2], v1[3]));
                if (!dry) g_vf[((tj * 4 + hh) * 128 + blk) * 32 + lane] = vv;
            }
            __syncwarp();
            if (lane0) mbar_arrive(sb + B_KVDONE);
            const float z0 = __shfl_sync(0xffffffffu, acc[96], lane & ~3), z1 = __shfl_sync(0xffffffffu, acc[98], lane & ~3);
            g0 = 1.f / (1.f + __expf(-z0)); g1 = 1.f / (1.f + __expf(-z1));
        }
        TS(3);
        const int wrow = (warp & 3) * 16;
        {
            float acc[112];
            int prev = 0;
            for (int s = 0; s < (dry ? 4 : N_FFN1); s++) {
                CWAIT();
                const uint32_t bs = sb + RING_OFF + r.slot * SLOT, as = xa + (s >> 1) * 16384 + (s & 1) * 64;
                wgmma_fence();
                wgmma_ss_n224(acc, desc_a(as), desc_b(bs), s);
                wgmma_ss_n224(acc, desc_a(as + 32), desc_b(bs + 2048), 1);
                wgmma_commit();
                if (s > 0) { wgmma_wait<1>(); if (lane0) mbar_arrive(sb + B_EMPTY + 8 * prev); }
                prev = r.slot; r.next();
            }
            wgmma_wait<0>();
            fence_acc(acc);
            if (lane0) { mbar_arrive(sb + B_EMPTY + 8 * prev); mbar_arrive(sb + B_XDEAD); }
            TS(4);
            const float s0 = 1.f - g0, s1 = 1.f - g1;
            asm volatile("bar.sync %0, 128;" :: "r"(1 + wg) : "memory");
            const uint32_t strow = xa + (wrow + ((lane >> 3) & 1) * 8 + (lane & 7)) * 128;
#pragma unroll
            for (int p = 0; p < 14; p++) {
                const int nt = 2 * p + (lane >> 4);
                const float* a = &acc[8 * p];
                stmatrix_x4(strow + (p >> 2) * 16384 + (((nt & 7) ^ (lane & 7)) << 4),
                            pack_bf16_relu(a[0] * s0, a[1] * s0), pack_bf16_relu(a[2] * s1, a[3] * s1),
                            pack_bf16_relu(a[4] * s0, a[5] * s0), pack_bf16_relu(a[6] * s1, a[7] * s1));
            }
        }
        TS(5);
        {
            fence_async_smem();
            asm volatile("bar.sync %0, 128;" :: "r"(1 + wg) : "memory");
            float accA[64], accB[64];
            auto epilogue = [&](float (&acc)[64], int q) {
                fence_acc(acc);
                const uint32_t st = sb + STG_OFF + (q & 1) * 32768 + warp * 4096;
                if (q == 0 && !dry) mbar_wait(sb + B_XDEAD, 0);
                if (q >= 2 && !dry) mbar_wait(sb + B_SF + 8 * (q & 1), 0);
#pragma unroll
                for (int t2 = 0; t2 < 8; t2++) {
                    uint4 v;
                    v.x = pack_bf16(acc[8 * t2 + 0], acc[8 * t2 + 1]); v.y = pack_bf16(acc[8 * t2 + 2], acc[8 * t2 + 3]);
                    v.z = pack_bf16(acc[8 * t2 + 4], acc[8 * t2 + 5]); v.w = pack_bf16(acc[8 * t2 + 6], acc[8 * t2 + 7]);
                    sts128(st + t2 * 512 + lane * 16, v);
                }
                fence_async_smem();
                __syncwarp();
                if (lane0) mbar_arrive(sb + B_SQ + 8 * q);
            };
            int rel = r.slot;
#pragma unroll
            for (int m = 0; m < N_FFN2; m++) {
                CWAIT();
                wgmma_fence();
#pragma unroll
                for (int h = 0; h < 2; h++) {
                    const int u = 2 * m + h, q = u / 7, rr = u % 7;
                    const uint32_t bs = sb + RING_OFF + r.slot * SLOT + h * 8192;
                    const uint32_t as = xa + (rr >> 1) * 16384 + (rr & 1) * 64;
                    if (!(q & 1)) {
                        wgmma_ss_n128(accA, desc_a(as), desc_b(bs), rr);
                        wgmma_ss_n128(accA, desc_a(as + 32), desc_b(bs + 2048), 1);
                    } else {
                        wgmma_ss_n128(accB, desc_a(as), desc_b(bs), rr);
                        wgmma_ss_n128(accB, desc_a(as + 32), desc_b(bs + 2048), 1);
                    }
                }
                wgmma_commit();
                r.next();
                wgmma_wait<1>();
                if (m > 0) {
                    if (lane0) mbar_arrive(sb + B_EMPTY + 8 * rel);
                    if (++rel == RING) rel = 0;
                }
                if (m == 4) { TS(25); epilogue(accA, 0); }
                if (m == 7) { TS(26); epilogue(accB, 1); }
                if (m == 11) { TS(27); epilogue(accA, 2); }
            }
            wgmma_wait<0>();
            if (lane0) { mbar_arrive(sb + B_EMPTY + 8 * rel); mbar_arrive(sb + B_HDEAD); }
            epilogue(accB, 3);
        }
        TS(6);
        {
            const float SC = 0.25f * 1.4426950408889634f;
            const int gb0 = 8 * ti - 16 + warp;
            int slotK = 0, slotV = 0;
            const uint32_t ostore = sb + OWN_OFF + (warp * 16 + ((lane >> 3) & 1) * 8 + (lane & 7)) * 128;
            uint32_t* odst = reinterpret_cast<uint32_t*>(g_o + (size_t)(ti * 128 + warp * 16 + g) * 512 + tj * 64 + ((lane & 1) ? 8 : 0) + (lane & 2) * 2);
#define NHEADS (dry ? 2 : 4)
#define ATT_KWAIT(kb) do { slotK = r.slot; CWAIT(); kb = sb + RING_OFF + slotK * SLOT + warp * 512 + lane * 16; r.next(); } while (0)
#define ATT_VWAIT(vb) do { slotV = r.slot; CWAIT(); vb = sb + RING_OFF + slotV * SLOT + warp * 512 + lane * 16; r.next(); TS(21 + hh); } while (0)
#define ATT_KVREL() do { __syncwarp(); if (lane0) { mbar_arrive(sb + B_EMPTY + 8 * slotK); mbar_arrive(sb + B_EMPTY + 8 * slotV); } } while (0)
#define ATT_NEXTQ(h) do { \
                if ((h) == 1) { q0 = qf[1][0]; q1 = qf[1][1]; q2 = qf[1][2]; q3 = qf[1][3]; } \
                else if ((h) == 2) { q0 = qf[2][0]; q1 = qf[2][1]; q2 = qf[2][2]; q3 = qf[2][3]; } \
                else { q0 = qf[3][0]; q1 = qf[3][1]; q2 = qf[3][2]; q3 = qf[3][3]; } } while (0)
#define ATT_STORE(h, r0, r1, r2, r3) do { \
                if ((h) == 0 && !dry) mbar_wait(sb + B_SF, 1);        \
                stmatrix_x4(ostore + (((2 * (h) + (lane >> 4)) ^ (lane & 7)) << 4), r0, r1, r2, r3); \
                const bool odd = lane & 1; \
                const uint32_t sl = __shfl_xor_sync(0xffffffffu, odd ? (r0) : (r2), 1), sh = __shfl_xor_sync(0xffffffffu, odd ? (r1) : (r3), 1); \
                if (!dry) *reinterpret_cast<uint2*>(odst + 8 * (h)) = odd ? make_uint2(sl, r2) : make_uint2(r0, sl); \
                if (!dry) *reinterpret_cast<uint2*>(odst + 8 * (h) + 8 * 256) = odd ? make_uint2(sh, r3) : make_uint2(r1, sh); \
                } while (0)
            auto attention = [&](auto masked_tag) {
            constexpr bool MASKED = decltype(masked_tag)::value;
            const float NEG = -INFINITY;
            const uint32_t ONES = 0x3F803F80u;
            float sa[8][2][4];
            float o[2][4], ls[4];
            float m0, m1;
            uint32_t q0 = qf[0][0], q1 = qf[0][1], q2 = qf[0][2], q3 = qf[0][3];
            auto qk = [&](float (&s)[8][2][4], int ps, int t, uint32_t kbase, bool merged) {
                if (merged) {
                    const uint4 kd = lds128_free(kbase + 16 * 512);
                    const uint4 kf = lds128_free(kbase);
                    float f[2][4];
                    const float ci = (!MASKED || opaque(gb0) >= 0) ? 0.f : NEG;
                    mma16816_c(s[0][0], q0, q1, q2, q3, kd.x, kd.y, 0.f);
                    mma16816_c(s[0][1], q0, q1, q2, q3, kd.z, kd.w, 0.f);
                    mma16816_c(f[0], q0, q1, q2, q3, kf.x, kf.y, ci);
                    mma16816_c(f[1], q0, q1, q2, q3, kf.z, kf.w, ci);
#pragma unroll
                    for (int u = 0; u < 2; u++)
#pragma unroll
                        for (int e = 0; e < 4; e++) {
                            const int row = g + 8 * (e >> 1), col = 8 * u + 2 * c + (e & 1);
                            s[0][u][e] = (col > row) ? f[u][e] : s[0][u][e];
                        }
                } else {
                    const uint4 kf = lds128_free(kbase + (8 * ps + t) * 512);
                    const float ci = (!MASKED || opaque(gb0) + 8 * ps + t >= 0) ? 0.f : NEG;
                    mma16816_c(s[t][0], q0, q1, q2, q3, kf.x, kf.y, ci);
                    mma16816_c(s[t][1], q0, q1, q2, q3, kf.z, kf.w, ci);
                }
            };
            auto rowmax = [&](float (&s)[8][2][4], float b0, float b1, float& n0, float& n1) {
                int i0 = __float_as_int(b0), i1 = __float_as_int(b1);
#pragma unroll
                for (int t = 0; t < 8; t++)
#pragma unroll
                    for (int u = 0; u < 2; u++) {
                        i0 = __vimax3_s32(i0, __float_as_int(s[t][u][0]), __float_as_int(s[t][u][1]));
                        i1 = __vimax3_s32(i1, __float_as_int(s[t][u][2]), __float_as_int(s[t][u][3]));
                    }
                i0 = max(i0, __shfl_xor_sync(0xffffffffu, i0, 1)); i1 = max(i1, __shfl_xor_sync(0xffffffffu, i1, 1));
                i0 = max(i0, __shfl_xor_sync(0xffffffffu, i0, 2)); i1 = max(i1, __shfl_xor_sync(0xffffffffu, i1, 2));
                n0 = __int_as_float(i0); n1 = __int_as_float(i1);
                if (__any_sync(0xffffffffu, (i0 | i1) < 0)) {
                    asm volatile("" ::: "memory");
                    n0 = b0; n1 = b1;
#pragma unroll
                    for (int t = 0; t < 8; t++)
#pragma unroll
                        for (int u = 0; u < 2; u++) {
                            n0 = fmaxf(n0, fmaxf(s[t][u][0], s[t][u][1]));
                            n1 = fmaxf(n1, fmaxf(s[t][u][2], s[t][u][3]));
                        }
                    n0 = fmaxf(n0, __shfl_xor_sync(0xffffffffu, n0, 1)); n1 = fmaxf(n1, __shfl_xor_sync(0xffffffffu, n1, 1));
                    n0 = fmaxf(n0, __shfl_xor_sync(0xffffffffu, n0, 2)); n1 = fmaxf(n1, __shfl_xor_sync(0xffffffffu, n1, 2));
                }
            };
            auto pv = [&](const float (&p)[2][4], uint32_t vaddr) {
                const uint4 vf = lds128_free(vaddr);
                const uint32_t a0 = pack_bf16(p[0][0], p[0][1]), a1 = pack_bf16(p[0][2], p[0][3]);
                const uint32_t a2 = pack_bf16(p[1][0], p[1][1]), a3 = pack_bf16(p[1][2], p[1][3]);
                mma16816(o[0], a0, a1, a2, a3, vf.x, vf.y);
                mma16816(o[1], a0, a1, a2, a3, vf.z, vf.w);
                mma16816(ls, a0, a1, a2, a3, ONES, ONES);
            };
            auto expv = [&](float (&s)[8][2][4], int ps, int t, float mc0, float mc1, uint32_t vbase, bool merged) {
                float p[2][4];
#pragma unroll
                for (int u = 0; u < 2; u++) {
                    p[u][0] = ex2(fmaf(s[t][u][0], SC, -mc0)); p[u][1] = ex2(fmaf(s[t][u][1], SC, -mc0));
                    p[u][2] = ex2(fmaf(s[t][u][2], SC, -mc1)); p[u][3] = ex2(fmaf(s[t][u][3], SC, -mc1));
                }
                if (merged) {
                    float pd[2][4], pf[2][4];
#pragma unroll
                    for (int u = 0; u < 2; u++)
#pragma unroll
                        for (int e = 0; e < 4; e++) {
                            const int row = g + 8 * (e >> 1), col = 8 * u + 2 * c + (e & 1);
                            pf[u][e] = (col > row) ? p[u][e] : 0.f;
                            pd[u][e] = (col > row) ? 0.f : p[u][e];
                        }
                    pv(pd, vbase + 16 * 512);
                    pv(pf, vbase);
                } else {
                    pv(p, vbase + (8 * ps + t) * 512);
                }
            };
            uint32_t kbase = 0, vbase = 0;
#pragma unroll 1
            for (int hh = 0; hh < NHEADS; hh++) {
                ATT_KWAIT(kbase);
                ATT_VWAIT(vbase);
                asm volatile("" : "+r"(kbase), "+r"(vbase) :: "memory");
                if (hh > 0) ATT_NEXTQ(hh);
#pragma unroll
                for (int ps = 0; ps < 2; ps++) {
#pragma unroll
                    for (int t = 0; t < 8; t++) qk(sa, ps, t, kbase, ps == 0 && t == 0);
                    float n0, n1;
                    rowmax(sa, ps ? m0 : NEG, ps ? m1 : NEG, n0, n1);
                    if (ps == 0) {
#pragma unroll
                        for (int e = 0; e < 4; e++) { o[0][e] = 0.f; o[1][e] = 0.f; ls[e] = 0.f; }
                    } else {
                        const float a0 = ex2((m0 - n0) * SC), a1 = ex2((m1 - n1) * SC);
                        ls[0] *= a0; ls[2] *= a1;
                        o[0][0] *= a0; o[0][1] *= a0; o[1][0] *= a0; o[1][1] *= a0;
                        o[0][2] *= a1; o[0][3] *= a1; o[1][2] *= a1; o[1][3] *= a1;
                    }
                    m0 = n0; m1 = n1;
                    const float mc0 = n0 * SC, mc1 = n1 * SC;
#pragma unroll
                    for (int t = 0; t < 8; t++) expv(sa, ps, t, mc0, mc1, vbase, ps == 0 && t == 0);
                }
                const float f0 = __fdividef(g0, ls[0]), f1 = __fdividef(g1, ls[2]);
                ATT_STORE(hh, pack_bf16(o[0][0] * f0, o[0][1] * f0), pack_bf16(o[0][2] * f1, o[0][3] * f1),
                              pack_bf16(o[1][0] * f0, o[1][1] * f0), pack_bf16(o[1][2] * f1, o[1][3] * f1));
                ATT_KVREL();
            }
            };
            if (ti >= 2) attention(BoolTag<false>{}); else attention(BoolTag<true>{});
            fence_async_smem();
            __syncwarp();
            if (lane0) mbar_arrive(sb + B_ODONE);
        }
        TS(7);
        {
            float acc[32];
            uint4 pv[4][4];
            if (!dry) mbar_wait(sb + B_PREADY, 0);
            {
                const uint4* p = g_part + (size_t)((ti * 8 + tj) * 8 + 4) * 1024 + warp * 128 + lane;
#pragma unroll
                for (int s = 0; s < 4; s++)
#pragma unroll
                    for (int n = 0; n < 4; n++) pv[n][s] = dry ? make_uint4(0u, 0u, 0u, 0u) : ldg_weak(p + s * 1024 + n * 32);
            }
            if (!dry) mbar_wait(sb + B_WOFULL, 0);
            if (!dry) mbar_wait(sb + B_ODONE, 0);
            TS(15);
            wgmma_fence();
#pragma unroll
            for (int k = 0; k < 4; k++) wgmma_ss_n64(acc, desc_a(sb + OWN_OFF + wg * 8192 + 32 * k), desc_b(sb + X_OFF + tj * 8192 + 2048 * k), k);
            wgmma_commit();
            TS(16);
#pragma unroll 1
            for (int m = 0; m < N_O; m++) {
                CWAIT();
                uint32_t js; asm volatile("ld.shared.u32 %0, [%1];" : "=r"(js) : "r"(sb + OSRC_OFF + 4 * m) : "memory");
                const uint32_t as = sb + RING_OFF + r.slot * SLOT + wg * 8192;
                const uint32_t bs = sb + X_OFF + (js & 7) * 8192;
                wgmma_fence();
#pragma unroll
                for (int k = 0; k < 4; k++) wgmma_ss_n64(acc, desc_a(as + 32 * k), desc_b(bs + 2048 * k), 1);
                wgmma_commit();
                if (m == 0) { wgmma_wait<0>(); if (lane0) mbar_arrive(sb + B_EMPTY + 8 * r.slot); }
                r.next();
            }
            float base[32];
            if (!dry) mbar_wait(sb + B_HSUM, 0);
#pragma unroll
            for (int n = 0; n < 4; n++) {
                const uint4 u0 = lds128(sb + HSUM_OFF + (warp * 8 + 2 * n) * 512 + lane * 16), u1 = lds128(sb + HSUM_OFF + (warp * 8 + 2 * n + 1) * 512 + lane * 16);
                float* a = &base[8 * n];
                a[0] = __uint_as_float(u0.x); a[1] = __uint_as_float(u0.y); a[2] = __uint_as_float(u0.z); a[3] = __uint_as_float(u0.w);
                a[4] = __uint_as_float(u1.x); a[5] = __uint_as_float(u1.y); a[6] = __uint_as_float(u1.z); a[7] = __uint_as_float(u1.w);
#pragma unroll
                for (int s = 0; s < 4; s++) {
                    a[0] += bf_lo(pv[n][s].x); a[1] += bf_hi(pv[n][s].x); a[2] += bf_lo(pv[n][s].y); a[3] += bf_hi(pv[n][s].y);
                    a[4] += bf_lo(pv[n][s].z); a[5] += bf_hi(pv[n][s].z); a[6] += bf_lo(pv[n][s].w); a[7] += bf_hi(pv[n][s].w);
                }
            }
            fence_acc(base);
            wgmma_wait<0>();
            fence_acc(acc);
            TS(17);
#pragma unroll
            for (int k = 0; k < 32; k++) acc[k] += base[k];
            __nv_bfloat16* o = out + (size_t)(ti * 128 + warp * 16 + g) * 512 + tj * 64 + ((lane & 1) ? 8 : 0) + (lane & 2) * 2;
            const bool odd = lane & 1;
#pragma unroll
            for (int t2 = 0; t2 < 4; t2++) {
                const uint32_t lo0 = pack_bf16(acc[8 * t2 + 0], acc[8 * t2 + 1]), hi0 = pack_bf16(acc[8 * t2 + 2], acc[8 * t2 + 3]);
                const uint32_t lo1 = pack_bf16(acc[8 * t2 + 4], acc[8 * t2 + 5]), hi1 = pack_bf16(acc[8 * t2 + 6], acc[8 * t2 + 7]);
                const uint32_t sl = __shfl_xor_sync(0xffffffffu, odd ? lo0 : lo1, 1), sh = __shfl_xor_sync(0xffffffffu, odd ? hi0 : hi1, 1);
                if (!dry) *reinterpret_cast<uint2*>(o + 16 * t2) = odd ? make_uint2(sl, lo1) : make_uint2(lo0, sl);
                if (!dry) *reinterpret_cast<uint2*>(o + 16 * t2 + 8 * 512) = odd ? make_uint2(sh, hi1) : make_uint2(hi0, sh);
            }
            if (tid == 0 && !dry) TSG(30);
        }
        TS(8);
    }
}

typedef CUresult (*PFN_encodeTiled)(CUtensorMap*, CUtensorMapDataType, cuuint32_t, void*, const cuuint64_t*, const cuuint64_t*,
                                    const cuuint32_t*, const cuuint32_t*, CUtensorMapInterleave, CUtensorMapSwizzle,
                                    CUtensorMapL2promotion, CUtensorMapFloatOOBfill);

void make_map(PFN_encodeTiled enc, CUtensorMap* m, const void* base, int rank, const cuuint64_t* dims, const cuuint64_t* strides, const cuuint32_t* box) {
    cuuint32_t es[5] = {1, 1, 1, 1, 1};
    enc(m, CU_TENSOR_MAP_DATA_TYPE_BFLOAT16, (cuuint32_t)rank, const_cast<void*>(base), dims, strides, box, es,
        CU_TENSOR_MAP_INTERLEAVE_NONE, CU_TENSOR_MAP_SWIZZLE_128B, CU_TENSOR_MAP_L2_PROMOTION_L2_256B, CU_TENSOR_MAP_FLOAT_OOB_FILL_NONE);
}

}

extern "C" void kernel_launch(void* const* d_in, const int* in_sizes, int n_in, void* d_out, int out_size) {
    (void)in_sizes; (void)n_in; (void)out_size;
    const void* x = d_in[0]; const void* wqkv = d_in[1]; const void* wo = d_in[2];
    const void* w1 = d_in[4]; const void* w2 = d_in[5]; const void* gate_w = d_in[6];
    static PFN_encodeTiled enc = nullptr;
    static int ncta = 128;
    if (!enc) {
        int dev = 0, sms = 0;
        cudaGetDevice(&dev);
        cudaDeviceGetAttribute(&sms, cudaDevAttrMultiProcessorCount, dev);
        ncta = sms > 132 ? 132 : (sms > 128 ? sms : 128);
        void* fn = nullptr; cudaDriverEntryPointQueryResult st;
        cudaGetDriverEntryPoint("cuTensorMapEncodeTiled", &fn, cudaEnableDefault, &st);
        enc = (PFN_encodeTiled)fn;
        cudaFuncSetAttribute(fused_kernel, cudaFuncAttributeMaxDynamicSharedMemorySize, SMEM_BYTES);
    }
    CUtensorMap mx, mqkv, mw1, mw2, mwo, mw1a, mo;
    void* optr = nullptr;
    cudaGetSymbolAddress(&optr, g_o);
    { cuuint64_t d[2] = {512, 2048}, s[1] = {1024}; cuuint32_t b[2] = {64, 128}; make_map(enc, &mo, optr, 2, d, s, b); }
    { cuuint64_t d[4] = {64, 512, 3, 8}, s[3] = {3584, 128, 448}; cuuint32_t b[4] = {64, 32, 3, 1}; make_map(enc, &mw1a, w1, 4, d, s, b); }
    { cuuint64_t d[2] = {512, 2048}, s[1] = {1024}; cuuint32_t b[2] = {64, 128}; make_map(enc, &mx, x, 2, d, s, b); }
    { cuuint64_t d[4] = {64, 512, 8, 3}, s[3] = {3072, 128, 1024}; cuuint32_t b[4] = {64, 32, 1, 3}; make_map(enc, &mqkv, wqkv, 4, d, s, b); }
    { cuuint64_t d[2] = {1792, 512}, s[1] = {3584}; cuuint32_t b[2] = {64, 32}; make_map(enc, &mw1, w1, 2, d, s, b); }
    { cuuint64_t d[3] = {64, 1792, 8}, s[2] = {1024, 128}; cuuint32_t b[3] = {64, 32, 2}; make_map(enc, &mw2, w2, 3, d, s, b); }
    { cuuint64_t d[2] = {512, 512}, s[1] = {1024}; cuuint32_t b[2] = {64, 256}; make_map(enc, &mwo, wo, 2, d, s, b); }
    fused_kernel<<<ncta, 384, SMEM_BYTES, cudaStreamPerThread>>>(mx, mqkv, mw1, mw2, mwo, mw1a, mo, (const __nv_bfloat16*)gate_w, (__nv_bfloat16*)d_out,
                                           (const uint8_t*)w1, (const uint8_t*)w2, (const uint8_t*)wo);
}
```

```cpp
#include <cuda_runtime.h>
#include <cuda_bf16.h>
#include <cuda.h>
#include <stdint.h>

namespace {

#define PF1_AT 1
#define PF2_AT 5
#define LEAD1 1
constexpr int RING = 6;
constexpr int SLOT = 16384;
constexpr uint32_t X_OFF = 0;
constexpr uint32_t STG_OFF = X_OFF + 4 * 16384;
constexpr uint32_t RING_OFF = 131072;
constexpr uint32_t BAR_OFF = RING_OFF + RING * SLOT;
constexpr uint32_t B_FULL = BAR_OFF, B_EMPTY = BAR_OFF + 64, B_XFULL = BAR_OFF + 128, B_HDEAD = BAR_OFF + 192,
                   B_EREADY = BAR_OFF + 200, B_KVDONE = BAR_OFF + 208, B_ODONE = BAR_OFF + 224,
                   B_KVREADY = BAR_OFF + 232, B_WOFULL = BAR_OFF + 240, B_HSUM = BAR_OFF + 248, B_PREADY = BAR_OFF + 264,
                   B_SQ = BAR_OFF + 272, B_SF = BAR_OFF + 304, B_XDEAD = BAR_OFF + 320;
constexpr uint32_t EPOCH_OFF = BAR_OFF + 256, ITEM_OFF = BAR_OFF + 260, OSRC_OFF = BAR_OFF + 384;
constexpr uint32_t OWN_OFF = X_OFF + 4 * 16384;
constexpr uint32_t HSUM_OFF = X_OFF + 6 * 16384;
constexpr uint32_t SMEM_BYTES = BAR_OFF + 1024;

constexpr int N_QKV = 16, N_FFN1 = 16, N_FFN2 = 14, N_KV = 8, N_O = 7;

__device__ uint4 g_kf[32 * 128 * 32];
__device__ uint4 g_vf[32 * 128 * 32];
__device__ uint4 g_part[16 * 8 * 8 * 8 * 4 * 32];
__device__ __nv_bfloat16 g_o[2048 * 512];
__device__ unsigned g_ticket;
__device__ unsigned g_kvcnt[128 * 32];
__device__ unsigned g_pcnt[128 * 32];
__device__ unsigned g_ocnt[128 * 32];
#define TS(k) do {} while (0)
#define TS2(k) do {} while (0)
#define TS2X(k) do {} while (0)
#define TSX(k) do {} while (0)
#define TSG(k) do {} while (0)

__device__ __forceinline__ uint32_t smem_u32(const void* p) { return (uint32_t)__cvta_generic_to_shared(p); }
__device__ __forceinline__ void mbar_init(uint32_t bar, uint32_t cnt) { asm volatile("mbarrier.init.shared::cta.b64 [%0], %1;" :: "r"(bar), "r"(cnt) : "memory"); }
__device__ __forceinline__ void mbar_expect_tx(uint32_t bar, uint32_t bytes) { asm volatile("mbarrier.arrive.expect_tx.shared::cta.b64 _, [%0], %1;" :: "r"(bar), "r"(bytes) : "memory"); }
__device__ __forceinline__ void mbar_expect_only(uint32_t bar, uint32_t bytes) { asm volatile("mbarrier.expect_tx.relaxed.cta.shared::cta.b64 [%0], %1;" :: "r"(bar), "r"(bytes) : "memory"); }
__device__ __forceinline__ void mbar_arrive(uint32_t bar) { asm volatile("mbarrier.arrive.shared::cta.b64 _, [%0];" :: "r"(bar) : "memory"); }
__device__ __forceinline__ void mbar_wait(uint32_t bar, uint32_t parity) {
    asm volatile("{\n.reg .pred P1, P2;\n.reg .u32 n;\nmov.u32 n, 0;\n"
                 "WAIT_LOOP:\n"
                 "mbarrier.try_wait.parity.shared::cta.b64 P1, [%0], %1;\n"
                 "@P1 bra WAIT_DONE;\n"
                 "add.u32 n, n, 1;\n"
                 "setp.lt.u32 P2, n, 0x400000;\n"
                 "@P2 bra WAIT_LOOP;\n"
                 "WAIT_DONE:\n}" :: "r"(bar), "r"(parity) : "memory");
}
__device__ __forceinline__ void mbar_wait_idle(uint32_t bar, uint32_t parity) {
    asm volatile("{\n.reg .pred P1, P2;\n.reg .u32 n;\nmov.u32 n, 0;\n"
                 "WAIT_LOOP:\n"
                 "mbarrier.try_wait.parity.shared::cta.b64 P1, [%0], %1, 2000;\n"
                 "@P1 bra WAIT_DONE;\n"
                 "add.u32 n, n, 1;\n"
                 "setp.lt.u32 P2, n, 0x100000;\n"
                 "@P2 bra WAIT_LOOP;\n"
                 "WAIT_DONE:\n}" :: "r"(bar), "r"(parity) : "memory");
}
__device__ __forceinline__ void tma_2d(uint32_t dst, const void* map, uint32_t bar, int c0, int c1) {
    asm volatile("cp.async.bulk.tensor.2d.shared::cluster.global.mbarrier::complete_tx::bytes [%0], [%1, {%3, %4}], [%2];"
        :: "r"(dst), "l"(map), "r"(bar), "r"(c0), "r"(c1) : "memory");
}
__device__ __forceinline__ void tma_3d(uint32_t dst, const void* map, uint32_t bar, int c0, int c1, int c2) {
    asm volatile("cp.async.bulk.tensor.3d.shared::cluster.global.mbarrier::complete_tx::bytes [%0], [%1, {%3, %4, %5}], [%2];"
        :: "r"(dst), "l"(map), "r"(bar), "r"(c0), "r"(c1), "r"(c2) : "memory");
}
__device__ __forceinline__ void tma_4d(uint32_t dst, const void* map, uint32_t bar, int c0, int c1, int c2, int c3) {
    asm volatile("cp.async.bulk.tensor.4d.shared::cluster.global.mbarrier::complete_tx::bytes [%0], [%1, {%3, %4, %5, %6}], [%2];"
        :: "r"(dst), "l"(map), "r"(bar), "r"(c0), "r"(c1), "r"(c2), "r"(c3) : "memory");
}
__device__ __forceinline__ void bulk_g2s(uint32_t dst, const void* src, uint32_t bytes, uint32_t bar) {
    asm volatile("cp.async.bulk.shared::cluster.global.mbarrier::complete_tx::bytes [%0], [%1], %2, [%3];"
        :: "r"(dst), "l"(src), "r"(bytes), "r"(bar) : "memory");
}
__device__ __forceinline__ void prefetch_l2(const void* src, uint32_t bytes) {
    asm volatile("cp.async.bulk.prefetch.L2.global [%0], %1;" :: "l"(src), "r"(bytes) : "memory");
}
__device__ __forceinline__ bool elect_one() {
    uint32_t p;
    asm volatile("{\n.reg .pred P;\nelect.sync _|P, 0xffffffff;\nselp.u32 %0, 1, 0, P;\n}" : "=r"(p));
    return p != 0;
}
__device__ __forceinline__ void wgmma_fence() { asm volatile("wgmma.fence.sync.aligned;" ::: "memory"); }
__device__ __forceinline__ void wgmma_commit() { asm volatile("wgmma.commit_group.sync.aligned;" ::: "memory"); }
template <int N> __device__ __forceinline__ void wgmma_wait() { asm volatile("wgmma.wait_group.sync.aligned %0;" :: "n"(N) : "memory"); }
__device__ __forceinline__ void fence_async_smem() { asm volatile("fence.proxy.async.shared::cta;" ::: "memory"); }
__device__ __forceinline__ uint64_t desc_a(uint32_t addr) {
    return (uint64_t)((addr & 0x3FFFF) >> 4) | ((uint64_t)1 << 16) | ((uint64_t)(1024 >> 4) << 32) | ((uint64_t)1 << 62);
}
__device__ __forceinline__ uint64_t desc_b(uint32_t addr) {
    return (uint64_t)((addr & 0x3FFFF) >> 4) | ((uint64_t)(4096 >> 4) << 16) | ((uint64_t)(1024 >> 4) << 32) | ((uint64_t)1 << 62);
}
__device__ __forceinline__ uint32_t pack_bf16(float lo, float hi) {
    uint32_t r; asm("cvt.rn.bf16x2.f32 %0, %1, %2;" : "=r"(r) : "f"(hi), "f"(lo)); return r;
}
__device__ __forceinline__ uint32_t pack_bf16_relu(float lo, float hi) {
    uint32_t r; asm("cvt.rn.relu.bf16x2.f32 %0, %1, %2;" : "=r"(r) : "f"(hi), "f"(lo)); return r;
}
__device__ __forceinline__ uint32_t movmatrix(uint32_t a) {
    uint32_t d; asm volatile("movmatrix.sync.aligned.m8n8.trans.b16 %0, %1;" : "=r"(d) : "r"(a)); return d;
}
__device__ __forceinline__ void stmatrix_x4(uint32_t addr, uint32_t r0, uint32_t r1, uint32_t r2, uint32_t r3) {
    asm volatile("stmatrix.sync.aligned.m8n8.x4.shared.b16 [%0], {%1, %2, %3, %4};" :: "r"(addr), "r"(r0), "r"(r1), "r"(r2), "r"(r3) : "memory");
}
__device__ __forceinline__ uint4 lds128(uint32_t addr) {
    uint4 v; asm volatile("ld.shared.v4.b32 {%0, %1, %2, %3}, [%4];" : "=r"(v.x), "=r"(v.y), "=r"(v.z), "=r"(v.w) : "r"(addr) : "memory"); return v;
}
__device__ __forceinline__ uint4 lds128_free(uint32_t addr) {
    uint4 v; asm("ld.shared.v4.b32 {%0, %1, %2, %3}, [%4];" : "=r"(v.x), "=r"(v.y), "=r"(v.z), "=r"(v.w) : "r"(addr)); return v;
}
__device__ __forceinline__ void mma16816(float (&c)[4], uint32_t a0, uint32_t a1, uint32_t a2, uint32_t a3, uint32_t b0, uint32_t b1) {
    asm("mma.sync.aligned.m16n8k16.row.col.f32.bf16.bf16.f32 {%0,%1,%2,%3}, {%4,%5,%6,%7}, {%8,%9}, {%0,%1,%2,%3};"
        : "+f"(c[0]), "+f"(c[1]), "+f"(c[2]), "+f"(c[3]) : "r"(a0), "r"(a1), "r"(a2), "r"(a3), "r"(b0), "r"(b1));
}
__device__ __forceinline__ void mma16816_c(float (&c)[4], uint32_t a0, uint32_t a1, uint32_t a2, uint32_t a3, uint32_t b0, uint32_t b1, float ci) {
    asm("mma.sync.aligned.m16n8k16.row.col.f32.bf16.bf16.f32 {%0,%1,%2,%3}, {%4,%5,%6,%7}, {%8,%9}, {%10,%10,%10,%10};"
        : "=f"(c[0]), "=f"(c[1]), "=f"(c[2]), "=f"(c[3]) : "r"(a0), "r"(a1), "r"(a2), "r"(a3), "r"(b0), "r"(b1), "f"(ci));
}
__device__ __forceinline__ int opaque(int v) { asm volatile("" : "+r"(v)); return v; }
__device__ __forceinline__ float ex2(float x) { float y; asm("ex2.approx.ftz.f32 %0, %1;" : "=f"(y) : "f"(x)); return y; }
__device__ __forceinline__ unsigned ld_acquire(const unsigned* p) {
    unsigned v; asm volatile("ld.acquire.gpu.global.u32 %0, [%1];" : "=r"(v) : "l"(p) : "memory"); return v;
}
__device__ __forceinline__ void red_release(unsigned* p, unsigned v) {
    asm volatile("red.release.gpu.global.add.u32 [%0], %1;" :: "l"(p), "r"(v) : "memory");
}
__device__ __forceinline__ void wait_counter(const unsigned* p, unsigned target) {
    uint32_t n = 0;
    while ((int)(ld_acquire(p) - target) < 0) { if (++n > (1u << 20)) break; }
}
__device__ __forceinline__ uint4 ldg_weak(const uint4* p) {
    uint4 v; asm volatile("ld.global.L1::no_allocate.v4.b32 {%0, %1, %2, %3}, [%4];" : "=r"(v.x), "=r"(v.y), "=r"(v.z), "=r"(v.w) : "l"(p) : "memory"); return v;
}
__device__ __forceinline__ float bf_lo(uint32_t v) { return __uint_as_float(v << 16); }
__device__ __forceinline__ float bf_hi(uint32_t v) { return __uint_as_float(v & 0xFFFF0000u); }

__device__ __forceinline__ void wgmma_ss_n64(float (&d)[32], uint64_t da, uint64_t db, int scale_d) {
    asm volatile("{\n.reg .pred p;\nsetp.ne.b32 p, %34, 0;\n"
        "wgmma.mma_async.sync.aligned.m64n64k16.f32.bf16.bf16 {%0, %1, %2, %3, %4, %5, %6, %7, %8, %9, %10, %11, %12, %13, %14, %15, %16, %17, %18, %19, %20, %21, %22, %23, %24, %25, %26, %27, %28, %29, %30, %31}, %32, %33, p, 1, 1, 0, 1;\n}\n"
        : "+f"(d[0]), "+f"(d[1]), "+f"(d[2]), "+f"(d[3]), "+f"(d[4]), "+f"(d[5]), "+f"(d[6]), "+f"(d[7]), "+f"(d[8]), "+f"(d[9]), "+f"(d[10]), "+f"(d[11]), "+f"(d[12]), "+f"(d[13]), "+f"(d[14]), "+f"(d[15]), "+f"(d[16]), "+f"(d[17]), "+f"(d[18]), "+f"(d[19]), "+f"(d[20]), "+f"(d[21]), "+f"(d[22]), "+f"(d[23]), "+f"(d[24]), "+f"(d[25]), "+f"(d[26]), "+f"(d[27]), "+f"(d[28]), "+f"(d[29]), "+f"(d[30]), "+f"(d[31])
        : "l"(da), "l"(db), "r"(scale_d));
}
__device__ __forceinline__ void wgmma_ss_n128(float (&d)[64], uint64_t da, uint64_t db, int scale_d) {
    asm volatile("{\n.reg .pred p;\nsetp.ne.b32 p, %66, 0;\n"
        "wgmma.mma_async.sync.aligned.m64n128k16.f32.bf16.bf16 {%0, %1, %2, %3, %4, %5, %6, %7, %8, %9, %10, %11, %12, %13, %14, %15, %16, %17, %18, %19, %20, %21, %22, %23, %24, %25, %26, %27, %28, %29, %30, %31, %32, %33, %34, %35, %36, %37, %38, %39, %40, %41, %42, %43, %44, %45, %46, %47, %48, %49, %50, %51, %52, %53, %54, %55, %56, %57, %58, %59, %60, %61, %62, %63}, %64, %65, p, 1, 1, 0, 1;\n}\n"
        : "+f"(d[0]), "+f"(d[1]), "+f"(d[2]), "+f"(d[3]), "+f"(d[4]), "+f"(d[5]), "+f"(d[6]), "+f"(d[7]), "+f"(d[8]), "+f"(d[9]), "+f"(d[10]), "+f"(d[11]), "+f"(d[12]), "+f"(d[13]), "+f"(d[14]), "+f"(d[15]), "+f"(d[16]), "+f"(d[17]), "+f"(d[18]), "+f"(d[19]), "+f"(d[20]), "+f"(d[21]), "+f"(d[22]), "+f"(d[23]), "+f"(d[24]), "+f"(d[25]), "+f"(d[26]), "+f"(d[27]), "+f"(d[28]), "+f"(d[29]), "+f"(d[30]), "+f"(d[31]), "+f"(d[32]), "+f"(d[33]), "+f"(d[34]), "+f"(d[35]), "+f"(d[36]), "+f"(d[37]), "+f"(d[38]), "+f"(d[39]), "+f"(d[40]), "+f"(d[41]), "+f"(d[42]), "+f"(d[43]), "+f"(d[44]), "+f"(d[45]), "+f"(d[46]), "+f"(d[47]), "+f"(d[48]), "+f"(d[49]), "+f"(d[50]), "+f"(d[51]), "+f"(d[52]), "+f"(d[53]), "+f"(d[54]), "+f"(d[55]), "+f"(d[56]), "+f"(d[57]), "+f"(d[58]), "+f"(d[59]), "+f"(d[60]), "+f"(d[61]), "+f"(d[62]), "+f"(d[63])
        : "l"(da), "l"(db), "r"(scale_d));
}
__device__ __forceinline__ void wgmma_ss_n200(float (&d)[100], uint64_t da, uint64_t db, int scale_d) {
    asm volatile("{\n.reg .pred p;\nsetp.ne.b32 p, %102, 0;\n"
        "wgmma.mma_async.sync.aligned.m64n200k16.f32.bf16.bf16 {%0, %1, %2, %3, %4, %5, %6, %7, %8, %9, %10, %11, %12, %13, %14, %15, %16, %17, %18, %19, %20, %21, %22, %23, %24, %25, %26, %27, %28, %29, %30, %31, %32, %33, %34, %35, %36, %37, %38, %39, %40, %41, %42, %43, %44, %45, %46, %47, %48, %49, %50, %51, %52, %53, %54, %55, %56, %57, %58, %59, %60, %61, %62, %63, %64, %65, %66, %67, %68, %69, %70, %71, %72, %73, %74, %75, %76, %77, %78, %79, %80, %81, %82, %83, %84, %85, %86, %87, %88, %89, %90, %91, %92, %93, %94, %95, %96, %97, %98, %99}, %100, %101, p, 1, 1, 0, 1;\n}\n"
        : "+f"(d[0]), "+f"(d[1]), "+f"(d[2]), "+f"(d[3]), "+f"(d[4]), "+f"(d[5]), "+f"(d[6]), "+f"(d[7]), "+f"(d[8]), "+f"(d[9]), "+f"(d[10]), "+f"(d[11]), "+f"(d[12]), "+f"(d[13]), "+f"(d[14]), "+f"(d[15]), "+f"(d[16]), "+f"(d[17]), "+f"(d[18]), "+f"(d[19]), "+f"(d[20]), "+f"(d[21]), "+f"(d[22]), "+f"(d[23]), "+f"(d[24]), "+f"(d[25]), "+f"(d[26]), "+f"(d[27]), "+f"(d[28]), "+f"(d[29]), "+f"(d[30]), "+f"(d[31]), "+f"(d[32]), "+f"(d[33]), "+f"(d[34]), "+f"(d[35]), "+f"(d[36]), "+f"(d[37]), "+f"(d[38]), "+f"(d[39]), "+f"(d[40]), "+f"(d[41]), "+f"(d[42]), "+f"(d[43]), "+f"(d[44]), "+f"(d[45]), "+f"(d[46]), "+f"(d[47]), "+f"(d[48]), "+f"(d[49]), "+f"(d[50]), "+f"(d[51]), "+f"(d[52]), "+f"(d[53]), "+f"(d[54]), "+f"(d[55]), "+f"(d[56]), "+f"(d[57]), "+f"(d[58]), "+f"(d[59]), "+f"(d[60]), "+f"(d[61]), "+f"(d[62]), "+f"(d[63]), "+f"(d[64]), "+f"(d[65]), "+f"(d[66]), "+f"(d[67]), "+f"(d[68]), "+f"(d[69]), "+f"(d[70]), "+f"(d[71]), "+f"(d[72]), "+f"(d[73]), "+f"(d[74]), "+f"(d[75]), "+f"(d[76]), "+f"(d[77]), "+f"(d[78]), "+f"(d[79]), "+f"(d[80]), "+f"(d[81]), "+f"(d[82]), "+f"(d[83]), "+f"(d[84]), "+f"(d[85]), "+f"(d[86]), "+f"(d[87]), "+f"(d[88]), "+f"(d[89]), "+f"(d[90]), "+f"(d[91]), "+f"(d[92]), "+f"(d[93]), "+f"(d[94]), "+f"(d[95]), "+f"(d[96]), "+f"(d[97]), "+f"(d[98]), "+f"(d[99])
        : "l"(da), "l"(db), "r"(scale_d));
}
__device__ __forceinline__ void wgmma_ss_n224(float (&d)[112], uint64_t da, uint64_t db, int scale_d) {
    asm volatile("{\n.reg .pred p;\nsetp.ne.b32 p, %114, 0;\n"
        "wgmma.mma_async.sync.aligned.m64n224k16.f32.bf16.bf16 {%0, %1, %2, %3, %4, %5, %6, %7, %8, %9, %10, %11, %12, %13, %14, %15, %16, %17, %18, %19, %20, %21, %22, %23, %24, %25, %26, %27, %28, %29, %30, %31, %32, %33, %34, %35, %36, %37, %38, %39, %40, %41, %42, %43, %44, %45, %46, %47, %48, %49, %50, %51, %52, %53, %54, %55, %56, %57, %58, %59, %60, %61, %62, %63, %64, %65, %66, %67, %68, %69, %70, %71, %72, %73, %74, %75, %76, %77, %78, %79, %80, %81, %82, %83, %84, %85, %86, %87, %88, %89, %90, %91, %92, %93, %94, %95, %96, %97, %98, %99, %100, %101, %102, %103, %104, %105, %106, %107, %108, %109, %110, %111}, %112, %113, p, 1, 1, 0, 1;\n}\n"
        : "+f"(d[0]), "+f"(d[1]), "+f"(d[2]), "+f"(d[3]), "+f"(d[4]), "+f"(d[5]), "+f"(d[6]), "+f"(d[7]), "+f"(d[8]), "+f"(d[9]), "+f"(d[10]), "+f"(d[11]), "+f"(d[12]), "+f"(d[13]), "+f"(d[14]), "+f"(d[15]), "+f"(d[16]), "+f"(d[17]), "+f"(d[18]), "+f"(d[19]), "+f"(d[20]), "+f"(d[21]), "+f"(d[22]), "+f"(d[23]), "+f"(d[24]), "+f"(d[25]), "+f"(d[26]), "+f"(d[27]), "+f"(d[28]), "+f"(d[29]), "+f"(d[30]), "+f"(d[31]), "+f"(d[32]), "+f"(d[33]), "+f"(d[34]), "+f"(d[35]), "+f"(d[36]), "+f"(d[37]), "+f"(d[38]), "+f"(d[39]), "+f"(d[40]), "+f"(d[41]), "+f"(d[42]), "+f"(d[43]), "+f"(d[44]), "+f"(d[45]), "+f"(d[46]), "+f"(d[47]), "+f"(d[48]), "+f"(d[49]), "+f"(d[50]), "+f"(d[51]), "+f"(d[52]), "+f"(d[53]), "+f"(d[54]), "+f"(d[55]), "+f"(d[56]), "+f"(d[57]), "+f"(d[58]), "+f"(d[59]), "+f"(d[60]), "+f"(d[61]), "+f"(d[62]), "+f"(d[63]), "+f"(d[64]), "+f"(d[65]), "+f"(d[66]), "+f"(d[67]), "+f"(d[68]), "+f"(d[69]), "+f"(d[70]), "+f"(d[71]), "+f"(d[72]), "+f"(d[73]), "+f"(d[74]), "+f"(d[75]), "+f"(d[76]), "+f"(d[77]), "+f"(d[78]), "+f"(d[79]), "+f"(d[80]), "+f"(d[81]), "+f"(d[82]), "+f"(d[83]), "+f"(d[84]), "+f"(d[85]), "+f"(d[86]), "+f"(d[87]), "+f"(d[88]), "+f"(d[89]), "+f"(d[90]), "+f"(d[91]), "+f"(d[92]), "+f"(d[93]), "+f"(d[94]), "+f"(d[95]), "+f"(d[96]), "+f"(d[97]), "+f"(d[98]), "+f"(d[99]), "+f"(d[100]), "+f"(d[101]), "+f"(d[102]), "+f"(d[103]), "+f"(d[104]), "+f"(d[105]), "+f"(d[106]), "+f"(d[107]), "+f"(d[108]), "+f"(d[109]), "+f"(d[110]), "+f"(d[111])
        : "l"(da), "l"(db), "r"(scale_d));
}
template <int N> __device__ __forceinline__ void fence_acc(float (&d)[N]) {
#pragma unroll
    for (int i = 0; i < N; i++) asm volatile("" : "+f"(d[i]) :: "memory");
}

__device__ __forceinline__ void bulk_s2g(void* dst, uint32_t src, uint32_t bytes) {
    asm volatile("cp.async.bulk.global.shared::cta.bulk_group [%0], [%1], %2;" :: "l"(dst), "r"(src), "r"(bytes) : "memory");
}
__device__ __forceinline__ void sts128(uint32_t addr, uint4 v) {
    asm volatile("st.shared.v4.b32 [%0], {%1, %2, %3, %4};" :: "r"(addr), "r"(v.x), "r"(v.y), "r"(v.z), "r"(v.w) : "memory");
}
__device__ __forceinline__ void sum_partials(uint32_t sb, int ti, int tj, int lane) {
    for (;;) {
        uint32_t item = 0;
        if (lane == 0) asm volatile("atom.shared.add.u32 %0, [%1], 1;" : "=r"(item) : "r"(sb + ITEM_OFF) : "memory");
        item = __shfl_sync(0xffffffffu, item, 0);
        if (item >= 8) break;
        const uint4* p = g_part + (size_t)((ti * 8 + tj) * 8) * 1024 + item * 128 + lane;
        uint4 v[4][4];
#pragma unroll
        for (int s = 0; s < 4; s++)
#pragma unroll
            for (int n = 0; n < 4; n++) v[n][s] = ldg_weak(p + s * 1024 + n * 32);
#pragma unroll
        for (int n = 0; n < 4; n++) {
            float a[8];
#pragma unroll
            for (int e = 0; e < 8; e++) a[e] = 0.f;
#pragma unroll
            for (int s = 0; s < 4; s++) {
                a[0] += bf_lo(v[n][s].x); a[1] += bf_hi(v[n][s].x); a[2] += bf_lo(v[n][s].y); a[3] += bf_hi(v[n][s].y);
                a[4] += bf_lo(v[n][s].z); a[5] += bf_hi(v[n][s].z); a[6] += bf_lo(v[n][s].w); a[7] += bf_hi(v[n][s].w);
            }
            const uint32_t d = sb + HSUM_OFF + (item * 8 + n * 2) * 512 + lane * 16;
            sts128(d, make_uint4(__float_as_uint(a[0]), __float_as_uint(a[1]), __float_as_uint(a[2]), __float_as_uint(a[3])));
            sts128(d + 512, make_uint4(__float_as_uint(a[4]), __float_as_uint(a[5]), __float_as_uint(a[6]), __float_as_uint(a[7])));
        }
    }
    __syncwarp();
    if (lane == 0) mbar_arrive(sb + B_HSUM);
}

#define PWAIT() mbar_wait_idle(sb + B_EMPTY + 8 * r.slot, r.phase)
#define CWAIT() do { if (!dry) mbar_wait(sb + B_FULL + 8 * r.slot, r.phase); } while (0)
template <bool B> struct BoolTag { static constexpr bool value = B; };
struct Ring {
    int slot; uint32_t phase;
    __device__ __forceinline__ void next() { if (++slot == RING) { slot = 0; phase ^= 1; } }
};

__global__ void __launch_bounds__(384, 1)
fused_kernel(const __grid_constant__ CUtensorMap map_x, const __grid_constant__ CUtensorMap map_qkv,
             const __grid_constant__ CUtensorMap map_w1, const __grid_constant__ CUtensorMap map_w2,
             const __grid_constant__ CUtensorMap map_wo, const __grid_constant__ CUtensorMap map_w1a,
             const __grid_constant__ CUtensorMap map_o,
             const __nv_bfloat16* __restrict__ gate_w, __nv_bfloat16* __restrict__ out,
             const uint8_t* __restrict__ w1p, const uint8_t* __restrict__ w2p, const uint8_t* __restrict__ wop)
{
    extern __shared__ __align__(1024) uint8_t smem_raw[];
    const uint32_t sb = smem_u32(smem_raw);
    const int tid = threadIdx.x, warp = tid >> 5, lane = tid & 31;
    const bool dry = blockIdx.x >= 128;
    const int ti = dry ? (int)(blockIdx.x & 1) * 2 : blockIdx.x >> 3, tj = blockIdx.x & 7;
    if (dry && warp >= 8) {
        asm volatile("setmaxnreg.dec.sync.aligned.u32 88;");
        return;
    }

    if (tid == 0 && !dry) { TSG(31); TSX(0); }
    if (tid == 320) {
        asm volatile("prefetch.tensormap [%0];" :: "l"(&map_x) : "memory");
        asm volatile("prefetch.tensormap [%0];" :: "l"(&map_qkv) : "memory");
        asm volatile("prefetch.tensormap [%0];" :: "l"(&map_w1) : "memory");
        asm volatile("prefetch.tensormap [%0];" :: "l"(&map_w1a) : "memory");
        asm volatile("prefetch.tensormap [%0];" :: "l"(&map_w2) : "memory");
        asm volatile("prefetch.tensormap [%0];" :: "l"(&map_wo) : "memory");
        asm volatile("prefetch.tensormap [%0];" :: "l"(&map_o) : "memory");
    }
    if (tid == 256) {
        mbar_init(sb + B_FULL, 1); mbar_init(sb + B_XFULL, 1);
        fence_async_smem();
        mbar_expect_tx(sb + B_XFULL, 16384);
        tma_2d(sb + X_OFF, &map_x, sb + B_XFULL, 0, ti * 128);
        mbar_expect_only(sb + B_FULL, 12288);
        tma_4d(sb + RING_OFF, &map_qkv, sb + B_FULL, 0, 0, tj, 0);
    }
    uint32_t gwv[N_QKV / 2];
    if (warp == 8) {
        const unsigned short* gws = reinterpret_cast<const unsigned short*>(gate_w);
#pragma unroll
        for (int n = 0; n < N_QKV / 2; n++) gwv[n] = (uint32_t)__ldg(gws + 64 * n + lane) | ((uint32_t)__ldg(gws + 64 * n + 32 + lane) << 16);
    }
    if (tid == 288) {
        for (int s = 1; s < RING; s++) mbar_init(sb + B_FULL + 8 * s, 1);
        for (int s = 0; s < RING; s++) mbar_init(sb + B_EMPTY + 8 * s, 8);
        for (int s = 1; s < 8; s++) mbar_init(sb + B_XFULL + 8 * s, 1);
        fence_async_smem();
    }
    if (tid == 352) {
        mbar_init(sb + B_HDEAD, 8); mbar_init(sb + B_EREADY, 1); mbar_init(sb + B_KVDONE, 8); mbar_init(sb + B_KVREADY, 1);
        mbar_init(sb + B_ODONE, 8); mbar_init(sb + B_WOFULL, 1); mbar_init(sb + B_HSUM, 3);
        mbar_init(sb + B_XDEAD, 8); mbar_init(sb + B_PREADY, 1); mbar_init(sb + B_SF, 1); mbar_init(sb + B_SF + 8, 1);
        for (int s = 0; s < 4; s++) mbar_init(sb + B_SQ + 8 * s, 8);
        asm volatile("st.shared.u32 [%0], %1;" :: "r"(sb + ITEM_OFF), "r"(0) : "memory");
        fence_async_smem();
    }
    if (!dry) __syncthreads();

    if (warp >= 8) {
        asm volatile("setmaxnreg.dec.sync.aligned.u32 88;");
        if (warp == 8) {
            Ring r{0, 1};
            const bool leader = elect_one();
#pragma unroll
            for (int n = 0; n < N_QKV; n++) {
                const uint32_t full = sb + B_FULL + 8 * r.slot, dst = sb + RING_OFF + r.slot * SLOT;
                if (n > 0) {
                    if (!(n & 1) && leader) {
                        mbar_expect_tx(sb + B_XFULL + 8 * (n >> 1), 16384);
                        tma_2d(sb + X_OFF + (n >> 1) * 16384, &map_x, sb + B_XFULL + 8 * (n >> 1), (n >> 1) * 64, ti * 128);
                    }
                    if (n >= RING) PWAIT();
                    if (leader) {
                        mbar_expect_only(full, 12288);
                        tma_4d(dst, &map_qkv, full, 0, 32 * n, tj, 0);
                    }
                }
                const uint32_t gv = (n & 1) ? (gwv[n >> 1] >> 16) : (gwv[n >> 1] & 0xFFFFu);
                asm volatile("st.shared.v4.b32 [%0], {%1, %2, %2, %2};" :: "r"(dst + 12288 + lane * 128 + ((lane & 7) << 4)), "r"(gv), "r"(0) : "memory");
                fence_async_smem();
                __syncwarp();
                if (leader) mbar_arrive(full);
                r.next();
            }
#pragma unroll 1
            for (int n = 0; n < N_FFN1; n++) {
                const uint32_t full = sb + B_FULL + 8 * r.slot, dst = sb + RING_OFF + r.slot * SLOT;
                PWAIT();
                if (leader) {
                    mbar_expect_tx(full, 16384);
                    tma_4d(dst, &map_w1a, full, 0, 32 * n, 0, tj);
                    tma_2d(dst + 3 * 4096, &map_w1, full, 224 * tj + 192, 32 * n);
                }
                r.next();
            }
            {
                int q = 0, rr = 0;
#pragma unroll 1
                for (int n = 0; n < N_FFN2; n++) {
                    const uint32_t full = sb + B_FULL + 8 * r.slot, dst = sb + RING_OFF + r.slot * SLOT;
                    PWAIT();
                    if (leader) mbar_expect_tx(full, 16384);
#pragma unroll
                    for (int h = 0; h < 2; h++) {
                        if (leader) tma_3d(dst + h * 8192, &map_w2, full, 0, 224 * tj + 32 * rr, 2 * q);
                        if (++rr == 7) { rr = 0; q++; }
                    }
                    r.next();
                }
            }
            mbar_wait_idle(sb + B_KVREADY, 0);
            asm volatile("fence.proxy.async.global;" ::: "memory");
            {
                const int bbase = 8 * ti - 16, b0 = bbase < 0 ? 0 : bbase;
                const uint32_t bytes = (uint32_t)(8 * ti + 8 - b0) * 512;
#pragma unroll 1
                for (int m = 0; m < N_KV; m++) {
                    const uint32_t full = sb + B_FULL + 8 * r.slot, dst = sb + RING_OFF + r.slot * SLOT;
                    if (m == RING) {
                        mbar_wait_idle(sb + B_HDEAD, 0);
                        if (leader) {
                            mbar_expect_tx(sb + B_WOFULL, 65536);
#pragma unroll
                            for (int e = 0; e < 2; e++) tma_2d(sb + X_OFF + e * 32768, &map_wo, sb + B_WOFULL, 64 * tj, 256 * e);
                        }
                    }
                    PWAIT();
                    if (leader) {
                        const uint4* src = ((m & 1) ? g_vf : g_kf) + ((tj * 4 + (m >> 1)) * 128 + b0) * 32;
                        mbar_expect_tx(full, bytes);
                        bulk_g2s(dst + (b0 - bbase) * 512, src, bytes, full);
                    }
                    r.next();
                }
            }
            {
                mbar_wait_idle(sb + B_EREADY, 0);
                unsigned epoch; asm volatile("ld.shared.u32 %0, [%1];" : "=r"(epoch) : "r"(sb + EPOCH_OFF) : "memory");
                uint32_t pending = 0xFFu & ~(1u << tj), ready = 0;
                mbar_wait_idle(sb + B_HSUM, 0);
#pragma unroll 1
                for (int m = 0; m < N_O; m++) {
                    const uint32_t full = sb + B_FULL + 8 * r.slot, dst = sb + RING_OFF + r.slot * SLOT;
                    PWAIT();
                    for (int it = 0; it < (1 << 20) && !ready; it++) {
                        bool ok = false;
                        if (lane < 8 && ((pending >> lane) & 1)) ok = (int)(ld_acquire(&g_ocnt[(ti * 8 + lane) * 32]) - (epoch + 1)) >= 0;
                        ready = __ballot_sync(0xffffffffu, ok);
                        if (!ready) __nanosleep(100);
                    }
                    const int js = ready ? __ffs(ready) - 1 : __ffs(pending) - 1;
                    pending &= ~(1u << js); ready &= ~(1u << js);
                    asm volatile("fence.proxy.async.global;" ::: "memory");
                    if (leader) {
                        asm volatile("st.shared.u32 [%0], %1;" :: "r"(sb + OSRC_OFF + 4 * m), "r"(js) : "memory");
                        mbar_expect_tx(full, 16384);
                        tma_2d(dst, &map_o, full, 64 * js, ti * 128);
                    }
                    r.next();
                }
            }
        } else if (warp == 9) {
            unsigned epoch = 0;
            if (lane == 0) {
                epoch = atomicAdd(&g_ticket, 1u) >> 7;
                asm volatile("st.shared.u32 [%0], %1;" :: "r"(sb + EPOCH_OFF), "r"(epoch) : "memory");
                mbar_arrive(sb + B_EREADY);
                mbar_wait_idle(sb + B_XFULL + 8 * PF1_AT, 0);
                prefetch_l2(w1p + (size_t)blockIdx.x * 14336, 14336);
                mbar_wait_idle(sb + B_XFULL + 8 * PF2_AT, 0);
                prefetch_l2(w2p + (size_t)blockIdx.x * 14336, 14336);
                prefetch_l2(wop + (size_t)blockIdx.x * 4096, 4096);
                mbar_wait_idle(sb + B_KVDONE, 0);
                red_release(&g_kvcnt[blockIdx.x * 32], 1u);
            }
            epoch = __shfl_sync(0xffffffffu, epoch, 0);
            if (lane < 3 && ti - lane >= 0) wait_counter(&g_kvcnt[((ti - lane) * 8 + tj) * 32], epoch + 1);
            __syncwarp();
            if (lane == 0) mbar_arrive(sb + B_KVREADY);
            mbar_wait_idle(sb + B_SQ + 24, 0);
            if (lane < 8) wait_counter(&g_pcnt[(ti * 8 + lane) * 32], epoch + 1);
            __syncwarp();
            if (lane == 0) { mbar_arrive(sb + B_PREADY); TSX(13); }
            sum_partials(sb, ti, tj, lane);
            if (lane == 0) TSX(14);
        } else {
            if (warp == 10) {
#pragma unroll 1
                for (int q = 0; q < 4; q++) {
                    mbar_wait_idle(sb + B_SQ + 8 * q, 0);
                    if (lane < 16) {
                        uint4* d = g_part + (size_t)(((ti * 8 + 2 * q + (lane & 1)) * 8 + tj) * 8 + (lane >> 1)) * 128;
                        bulk_s2g(d, sb + STG_OFF + (q & 1) * 32768 + lane * 2048, 2048);
                        asm volatile("cp.async.bulk.commit_group;" ::: "memory");
                        asm volatile("cp.async.bulk.wait_group.read 0;" ::: "memory");
                    }
                    __syncwarp();
                    if (lane == 0) mbar_arrive(sb + B_SF + 8 * (q & 1));
                }
                asm volatile("cp.async.bulk.wait_group 0;" ::: "memory");
                asm volatile("fence.proxy.async.global;" ::: "memory");
                __syncwarp();
                if (lane == 0) { red_release(&g_pcnt[blockIdx.x * 32], 1u); TSX(12); }
            }
            mbar_wait_idle(sb + B_PREADY, 0);
            sum_partials(sb, ti, tj, lane);
            if (warp == 11 && lane == 0) {
                mbar_wait_idle(sb + B_ODONE, 0);
                red_release(&g_ocnt[blockIdx.x * 32], 1u);
            }
        }
    } else {
        asm volatile("setmaxnreg.inc.sync.aligned.u32 208;");
        const int wg = warp >> 2, g = lane >> 2, c = lane & 3;
        const uint32_t xa = sb + X_OFF + wg * 8192;
        Ring r{0, 0};
        const bool lane0 = lane == 0 && !dry;
        uint32_t qf[4][4];
        float g0, g1;
        TS(9);
        {
            float acc[100];
            int prev = 0;
            if (wg == 1) asm volatile("bar.sync 3, 256;" ::: "memory");
            for (int s = 0; s < (dry ? 4 : N_QKV); s++) {
                if (!(s & 1) && !dry) mbar_wait(sb + B_XFULL + 8 * (s >> 1), 0);
                CWAIT();
                if (s == 0) TS(1);
                if (s == 2) TS(28);
                if (s == 6) TS(29);
                if (s == 10) TS(20);
                const uint32_t bs = sb + RING_OFF + r.slot * SLOT, as = xa + (s >> 1) * 16384 + (s & 1) * 64;
                wgmma_fence();
                wgmma_ss_n200(acc, desc_a(as), desc_b(bs), s);
                wgmma_ss_n200(acc, desc_a(as + 32), desc_b(bs + 2048), 1);
                wgmma_commit();
                if (wg == 0 && s == LEAD1) asm volatile("bar.arrive 3, 256;" ::: "memory");
                if (s > 0) { wgmma_wait<1>(); if (lane0) mbar_arrive(sb + B_EMPTY + 8 * prev); }
                prev = r.slot; r.next();
            }
            wgmma_wait<0>();
            fence_acc(acc);
            if (lane0) mbar_arrive(sb + B_EMPTY + 8 * prev);
            TS(2);
            const int blk = ti * 8 + warp;
#pragma unroll
            for (int hh = 0; hh < 4; hh++) {
                const float* t0 = &acc[8 * hh]; const float* t1 = &acc[8 * hh + 4];
                qf[hh][0] = pack_bf16(t0[0], t0[1]); qf[hh][1] = pack_bf16(t0[2], t0[3]);
                qf[hh][2] = pack_bf16(t1[0], t1[1]); qf[hh][3] = pack_bf16(t1[2], t1[3]);
                const float* k0 = &acc[32 + 8 * hh]; const float* k1 = &acc[32 + 8 * hh + 4];
                uint4 kv;
                kv.x = pack_bf16(k0[0], k0[1]); kv.y = pack_bf16(k1[0], k1[1]);
                kv.z = pack_bf16(k0[2], k0[3]); kv.w = pack_bf16(k1[2], k1[3]);
                if (!dry) g_kf[((tj * 4 + hh) * 128 + blk) * 32 + lane] = kv;
                const float* v0 = &acc[64 + 8 * hh]; const float* v1 = &acc[64 + 8 * hh + 4];
                uint4 vv;
                vv.x = movmatrix(pack_bf16(v0[0], v0[1])); vv.y = movmatrix(pack_bf16(v0[2], v0[3]));
                vv.z = movmatrix(pack_bf16(v1[0], v1[1])); vv.w = movmatrix(pack_bf16(v1[2], v1[3]));
                if (!dry) g_vf[((tj * 4 + hh) * 128 + blk) * 32 + lane] = vv;
            }
            __syncwarp();
            if (lane0) mbar_arrive(sb + B_KVDONE);
            const float z0 = __shfl_sync(0xffffffffu, acc[96], lane & ~3), z1 = __shfl_sync(0xffffffffu, acc[98], lane & ~3);
            g0 = 1.f / (1.f + __expf(-z0)); g1 = 1.f / (1.f + __expf(-z1));
        }
        TS(3);
        const int wrow = (warp & 3) * 16;
        {
            float acc[112];
            int prev = 0;
            for (int s = 0; s < (dry ? 4 : N_FFN1); s++) {
                CWAIT();
                const uint32_t bs = sb + RING_OFF + r.slot * SLOT, as = xa + (s >> 1) * 16384 + (s & 1) * 64;
                wgmma_fence();
                wgmma_ss_n224(acc, desc_a(as), desc_b(bs), s);
                wgmma_ss_n224(acc, desc_a(as + 32), desc_b(bs + 2048), 1);
                wgmma_commit();
                if (s > 0) { wgmma_wait<1>(); if (lane0) mbar_arrive(sb + B_EMPTY + 8 * prev); }
                prev = r.slot; r.next();
            }
            wgmma_wait<0>();
            fence_acc(acc);
            if (lane0) { mbar_arrive(sb + B_EMPTY + 8 * prev); mbar_arrive(sb + B_XDEAD); }
            TS(4);
            const float s0 = 1.f - g0, s1 = 1.f - g1;
            asm volatile("bar.sync %0, 128;" :: "r"(1 + wg) : "memory");
            const uint32_t strow = xa + (wrow + ((lane >> 3) & 1) * 8 + (lane & 7)) * 128;
#pragma unroll
            for (int p = 0; p < 14; p++) {
                const int nt = 2 * p + (lane >> 4);
                const float* a = &acc[8 * p];
                stmatrix_x4(strow + (p >> 2) * 16384 + (((nt & 7) ^ (lane & 7)) << 4),
                            pack_bf16_relu(a[0] * s0, a[1] * s0), pack_bf16_relu(a[2] * s1, a[3] * s1),
                            pack_bf16_relu(a[4] * s0, a[5] * s0), pack_bf16_relu(a[6] * s1, a[7] * s1));
            }
        }
        TS(5);
        {
            fence_async_smem();
            asm volatile("bar.sync %0, 128;" :: "r"(1 + wg) : "memory");
            float accA[64], accB[64];
            auto epilogue = [&](float (&acc)[64], int q) {
                fence_acc(acc);
                const uint32_t st = sb + STG_OFF + (q & 1) * 32768 + warp * 4096;
                if (q == 0 && !dry) mbar_wait(sb + B_XDEAD, 0);
                if (q >= 2 && !dry) mbar_wait(sb + B_SF + 8 * (q & 1), 0);
#pragma unroll
                for (int t2 = 0; t2 < 8; t2++) {
                    uint4 v;
                    v.x = pack_bf16(acc[8 * t2 + 0], acc[8 * t2 + 1]); v.y = pack_bf16(acc[8 * t2 + 2], acc[8 * t2 + 3]);
                    v.z = pack_bf16(acc[8 * t2 + 4], acc[8 * t2 + 5]); v.w = pack_bf16(acc[8 * t2 + 6], acc[8 * t2 + 7]);
                    sts128(st + t2 * 512 + lane * 16, v);
                }
                fence_async_smem();
                __syncwarp();
                if (lane0) mbar_arrive(sb + B_SQ + 8 * q);
            };
            int rel = r.slot;
#pragma unroll
            for (int m = 0; m < N_FFN2; m++) {
                CWAIT();
                wgmma_fence();
#pragma unroll
                for (int h = 0; h < 2; h++) {
                    const int u = 2 * m + h, q = u / 7, rr = u % 7;
                    const uint32_t bs = sb + RING_OFF + r.slot * SLOT + h * 8192;
                    const uint32_t as = xa + (rr >> 1) * 16384 + (rr & 1) * 64;
                    if (!(q & 1)) {
                        wgmma_ss_n128(accA, desc_a(as), desc_b(bs), rr);
                        wgmma_ss_n128(accA, desc_a(as + 32), desc_b(bs + 2048), 1);
                    } else {
                        wgmma_ss_n128(accB, desc_a(as), desc_b(bs), rr);
                        wgmma_ss_n128(accB, desc_a(as + 32), desc_b(bs + 2048), 1);
                    }
                }
                wgmma_commit();
                r.next();
                wgmma_wait<1>();
                if (m > 0) {
                    if (lane0) mbar_arrive(sb + B_EMPTY + 8 * rel);
                    if (++rel == RING) rel = 0;
                }
                if (m == 4) { TS(25); epilogue(accA, 0); }
                if (m == 7) { TS(26); epilogue(accB, 1); }
                if (m == 11) { TS(27); epilogue(accA, 2); }
            }
            wgmma_wait<0>();
            if (lane0) { mbar_arrive(sb + B_EMPTY + 8 * rel); mbar_arrive(sb + B_HDEAD); }
            epilogue(accB, 3);
        }
        TS(6);
        {
            const float SC = 0.25f * 1.4426950408889634f;
            const int gb0 = 8 * ti - 16 + warp;
            int slotK = 0, slotV = 0;
            const uint32_t ostore = sb + OWN_OFF + (warp * 16 + ((lane >> 3) & 1) * 8 + (lane & 7)) * 128;
            uint32_t* odst = reinterpret_cast<uint32_t*>(g_o + (size_t)(ti * 128 + warp * 16 + g) * 512 + tj * 64 + ((lane & 1) ? 8 : 0) + (lane & 2) * 2);
#define NHEADS (dry ? 2 : 4)
#define ATT_KWAIT(kb) do { slotK = r.slot; CWAIT(); kb = sb + RING_OFF + slotK * SLOT + warp * 512 + lane * 16; r.next(); } while (0)
#define ATT_VWAIT(vb) do { slotV = r.slot; CWAIT(); vb = sb + RING_OFF + slotV * SLOT + warp * 512 + lane * 16; r.next(); TS(21 + hh); } while (0)
#define ATT_KVREL() do { __syncwarp(); if (lane0) { mbar_arrive(sb + B_EMPTY + 8 * slotK); mbar_arrive(sb + B_EMPTY + 8 * slotV); } } while (0)
#define ATT_NEXTQ(h) do { \
                if ((h) == 1) { q0 = qf[1][0]; q1 = qf[1][1]; q2 = qf[1][2]; q3 = qf[1][3]; } \
                else if ((h) == 2) { q0 = qf[2][0]; q1 = qf[2][1]; q2 = qf[2][2]; q3 = qf[2][3]; } \
                else { q0 = qf[3][0]; q1 = qf[3][1]; q2 = qf[3][2]; q3 = qf[3][3]; } } while (0)
#define ATT_STORE(h, r0, r1, r2, r3) do { \
                if ((h) == 0 && !dry) mbar_wait(sb + B_SF, 1);        \
                stmatrix_x4(ostore + (((2 * (h) + (lane >> 4)) ^ (lane & 7)) << 4), r0, r1, r2, r3); \
                const bool odd = lane & 1; \
                const uint32_t sl = __shfl_xor_sync(0xffffffffu, odd ? (r0) : (r2), 1), sh = __shfl_xor_sync(0xffffffffu, odd ? (r1) : (r3), 1); \
                if (!dry) *reinterpret_cast<uint2*>(odst + 8 * (h)) = odd ? make_uint2(sl, r2) : make_uint2(r0, sl); \
                if (!dry) *reinterpret_cast<uint2*>(odst + 8 * (h) + 8 * 256) = odd ? make_uint2(sh, r3) : make_uint2(r1, sh); \
                } while (0)
            auto attention = [&](auto masked_tag) {
            constexpr bool MASKED = decltype(masked_tag)::value;
            const float NEG = -INFINITY;
            const uint32_t ONES = 0x3F803F80u;
            float sa[8][2][4];
            float o[2][4], ls[4];
            float m0, m1;
            uint32_t q0 = qf[0][0], q1 = qf[0][1], q2 = qf[0][2], q3 = qf[0][3];
            auto qk = [&](float (&s)[8][2][4], int ps, int t, uint32_t kbase, bool merged) {
                if (merged) {
                    const uint4 kd = lds128_free(kbase + 16 * 512);
                    const uint4 kf = lds128_free(kbase);
                    float f[2][4];
                    const float ci = (!MASKED || opaque(gb0) >= 0) ? 0.f : NEG;
                    mma16816_c(s[0][0], q0, q1, q2, q3, kd.x, kd.y, 0.f);
                    mma16816_c(s[0][1], q0, q1, q2, q3, kd.z, kd.w, 0.f);
                    mma16816_c(f[0], q0, q1, q2, q3, kf.x, kf.y, ci);
                    mma16816_c(f[1], q0, q1, q2, q3, kf.z, kf.w, ci);
#pragma unroll
                    for (int u = 0; u < 2; u++)
#pragma unroll
                        for (int e = 0; e < 4; e++) {
                            const int row = g + 8 * (e >> 1), col = 8 * u + 2 * c + (e & 1);
                            s[0][u][e] = (col > row) ? f[u][e] : s[0][u][e];
                        }
                } else {
                    const uint4 kf = lds128_free(kbase + (8 * ps + t) * 512);
                    const float ci = (!MASKED || opaque(gb0) + 8 * ps + t >= 0) ? 0.f : NEG;
                    mma16816_c(s[t][0], q0, q1, q2, q3, kf.x, kf.y, ci);
                    mma16816_c(s[t][1], q0, q1, q2, q3, kf.z, kf.w, ci);
                }
            };
            auto rowmax = [&](float (&s)[8][2][4], float b0, float b1, float& n0, float& n1) {
                int i0 = __float_as_int(b0), i1 = __float_as_int(b1);
#pragma unroll
                for (int t = 0; t < 8; t++)
#pragma unroll
                    for (int u = 0; u < 2; u++) {
                        i0 = __vimax3_s32(i0, __float_as_int(s[t][u][0]), __float_as_int(s[t][u][1]));
                        i1 = __vimax3_s32(i1, __float_as_int(s[t][u][2]), __float_as_int(s[t][u][3]));
                    }
                i0 = max(i0, __shfl_xor_sync(0xffffffffu, i0, 1)); i1 = max(i1, __shfl_xor_sync(0xffffffffu, i1, 1));
                i0 = max(i0, __shfl_xor_sync(0xffffffffu, i0, 2)); i1 = max(i1, __shfl_xor_sync(0xffffffffu, i1, 2));
                n0 = __int_as_float(i0); n1 = __int_as_float(i1);
                if (__any_sync(0xffffffffu, (i0 | i1) < 0)) {
                    asm volatile("" ::: "memory");
                    n0 = b0; n1 = b1;
#pragma unroll
                    for (int t = 0; t < 8; t++)
#pragma unroll
                        for (int u = 0; u < 2; u++) {
                            n0 = fmaxf(n0, fmaxf(s[t][u][0], s[t][u][1]));
                            n1 = fmaxf(n1, fmaxf(s[t][u][2], s[t][u][3]));
                        }
                    n0 = fmaxf(n0, __shfl_xor_sync(0xffffffffu, n0, 1)); n1 = fmaxf(n1, __shfl_xor_sync(0xffffffffu, n1, 1));
                    n0 = fmaxf(n0, __shfl_xor_sync(0xffffffffu, n0, 2)); n1 = fmaxf(n1, __shfl_xor_sync(0xffffffffu, n1, 2));
                }
            };
            auto pv = [&](const float (&p)[2][4], uint32_t vaddr) {
                const uint4 vf = lds128_free(vaddr);
                const uint32_t a0 = pack_bf16(p[0][0], p[0][1]), a1 = pack_bf16(p[0][2], p[0][3]);
                const uint32_t a2 = pack_bf16(p[1][0], p[1][1]), a3 = pack_bf16(p[1][2], p[1][3]);
                mma16816(o[0], a0, a1, a2, a3, vf.x, vf.y);
                mma16816(o[1], a0, a1, a2, a3, vf.z, vf.w);
                mma16816(ls, a0, a1, a2, a3, ONES, ONES);
            };
            auto expv = [&](float (&s)[8][2][4], int ps, int t, float mc0, float mc1, uint32_t vbase, bool merged) {
                float p[2][4];
#pragma unroll
                for (int u = 0; u < 2; u++) {
                    p[u][0] = ex2(fmaf(s[t][u][0], SC, -mc0)); p[u][1] = ex2(fmaf(s[t][u][1], SC, -mc0));
                    p[u][2] = ex2(fmaf(s[t][u][2], SC, -mc1)); p[u][3] = ex2(fmaf(s[t][u][3], SC, -mc1));
                }
                if (merged) {
                    float pd[2][4], pf[2][4];
#pragma unroll
                    for (int u = 0; u < 2; u++)
#pragma unroll
                        for (int e = 0; e < 4; e++) {
                            const int row = g + 8 * (e >> 1), col = 8 * u + 2 * c + (e & 1);
                            pf[u][e] = (col > row) ? p[u][e] : 0.f;
                            pd[u][e] = (col > row) ? 0.f : p[u][e];
                        }
                    pv(pd, vbase + 16 * 512);
                    pv(pf, vbase);
                } else {
                    pv(p, vbase + (8 * ps + t) * 512);
                }
            };
            uint32_t kbase = 0, vbase = 0;
#pragma unroll 1
            for (int hh = 0; hh < NHEADS; hh++) {
                ATT_KWAIT(kbase);
                ATT_VWAIT(vbase);
                asm volatile("" : "+r"(kbase), "+r"(vbase) :: "memory");
                if (hh > 0) ATT_NEXTQ(hh);
#pragma unroll
                for (int ps = 0; ps < 2; ps++) {
#pragma unroll
                    for (int t = 0; t < 8; t++) qk(sa, ps, t, kbase, ps == 0 && t == 0);
                    float n0, n1;
                    rowmax(sa, ps ? m0 : NEG, ps ? m1 : NEG, n0, n1);
                    if (ps == 0) {
#pragma unroll
                        for (int e = 0; e < 4; e++) { o[0][e] = 0.f; o[1][e] = 0.f; ls[e] = 0.f; }
                    } else {
                        const float a0 = ex2((m0 - n0) * SC), a1 = ex2((m1 - n1) * SC);
                        ls[0] *= a0; ls[2] *= a1;
                        o[0][0] *= a0; o[0][1] *= a0; o[1][0] *= a0; o[1][1] *= a0;
                        o[0][2] *= a1; o[0][3] *= a1; o[1][2] *= a1; o[1][3] *= a1;
                    }
                    m0 = n0; m1 = n1;
                    const float mc0 = n0 * SC, mc1 = n1 * SC;
#pragma unroll
                    for (int t = 0; t < 8; t++) expv(sa, ps, t, mc0, mc1, vbase, ps == 0 && t == 0);
                }
                const float f0 = __fdividef(g0, ls[0]), f1 = __fdividef(g1, ls[2]);
                ATT_STORE(hh, pack_bf16(o[0][0] * f0, o[0][1] * f0), pack_bf16(o[0][2] * f1, o[0][3] * f1),
                              pack_bf16(o[1][0] * f0, o[1][1] * f0), pack_bf16(o[1][2] * f1, o[1][3] * f1));
                ATT_KVREL();
            }
            };
            if (ti >= 2) attention(BoolTag<false>{}); else attention(BoolTag<true>{});
            fence_async_smem();
            __syncwarp();
            if (lane0) mbar_arrive(sb + B_ODONE);
        }
        TS(7);
        {
            float acc[32];
            uint4 pv[4][4];
            if (!dry) mbar_wait(sb + B_PREADY, 0);
            {
                const uint4* p = g_part + (size_t)((ti * 8 + tj) * 8 + 4) * 1024 + warp * 128 + lane;
#pragma unroll
                for (int s = 0; s < 4; s++)
#pragma unroll
                    for (int n = 0; n < 4; n++) pv[n][s] = dry ? make_uint4(0u, 0u, 0u, 0u) : ldg_weak(p + s * 1024 + n * 32);
            }
            if (!dry) mbar_wait(sb + B_WOFULL, 0);
            if (!dry) mbar_wait(sb + B_ODONE, 0);
            TS(15);
            wgmma_fence();
#pragma unroll
            for (int k = 0; k < 4; k++) wgmma_ss_n64(acc, desc_a(sb + OWN_OFF + wg * 8192 + 32 * k), desc_b(sb + X_OFF + tj * 8192 + 2048 * k), k);
            wgmma_commit();
            TS(16);
#pragma unroll 1
            for (int m = 0; m < N_O; m++) {
                CWAIT();
                uint32_t js; asm volatile("ld.shared.u32 %0, [%1];" : "=r"(js) : "r"(sb + OSRC_OFF + 4 * m) : "memory");
                const uint32_t as = sb + RING_OFF + r.slot * SLOT + wg * 8192;
                const uint32_t bs = sb + X_OFF + (js & 7) * 8192;
                wgmma_fence();
#pragma unroll
                for (int k = 0; k < 4; k++) wgmma_ss_n64(acc, desc_a(as + 32 * k), desc_b(bs + 2048 * k), 1);
                wgmma_commit();
                if (m == 0) { wgmma_wait<0>(); if (lane0) mbar_arrive(sb + B_EMPTY + 8 * r.slot); }
                r.next();
            }
            float base[32];
            if (!dry) mbar_wait(sb + B_HSUM, 0);
#pragma unroll
            for (int n = 0; n < 4; n++) {
                const uint4 u0 = lds128(sb + HSUM_OFF + (warp * 8 + 2 * n) * 512 + lane * 16), u1 = lds128(sb + HSUM_OFF + (warp * 8 + 2 * n + 1) * 512 + lane * 16);
                float* a = &base[8 * n];
                a[0] = __uint_as_float(u0.x); a[1] = __uint_as_float(u0.y); a[2] = __uint_as_float(u0.z); a[3] = __uint_as_float(u0.w);
                a[4] = __uint_as_float(u1.x); a[5] = __uint_as_float(u1.y); a[6] = __uint_as_float(u1.z); a[7] = __uint_as_float(u1.w);
#pragma unroll
                for (int s = 0; s < 4; s++) {
                    a[0] += bf_lo(pv[n][s].x); a[1] += bf_hi(pv[n][s].x); a[2] += bf_lo(pv[n][s].y); a[3] += bf_hi(pv[n][s].y);
                    a[4] += bf_lo(pv[n][s].z); a[5] += bf_hi(pv[n][s].z); a[6] += bf_lo(pv[n][s].w); a[7] += bf_hi(pv[n][s].w);
                }
            }
            fence_acc(base);
            wgmma_wait<0>();
            fence_acc(acc);
            TS(17);
#pragma unroll
            for (int k = 0; k < 32; k++) acc[k] += base[k];
            __nv_bfloat16* o = out + (size_t)(ti * 128 + warp * 16 + g) * 512 + tj * 64 + ((lane & 1) ? 8 : 0) + (lane & 2) * 2;
            const bool odd = lane & 1;
#pragma unroll
            for (int t2 = 0; t2 < 4; t2++) {
                const uint32_t lo0 = pack_bf16(acc[8 * t2 + 0], acc[8 * t2 + 1]), hi0 = pack_bf16(acc[8 * t2 + 2], acc[8 * t2 + 3]);
                const uint32_t lo1 = pack_bf16(acc[8 * t2 + 4], acc[8 * t2 + 5]), hi1 = pack_bf16(acc[8 * t2 + 6], acc[8 * t2 + 7]);
                const uint32_t sl = __shfl_xor_sync(0xffffffffu, odd ? lo0 : lo1, 1), sh = __shfl_xor_sync(0xffffffffu, odd ? hi0 : hi1, 1);
                if (!dry) *reinterpret_cast<uint2*>(o + 16 * t2) = odd ? make_uint2(sl, lo1) : make_uint2(lo0, sl);
                if (!dry) *reinterpret_cast<uint2*>(o + 16 * t2 + 8 * 512) = odd ? make_uint2(sh, hi1) : make_uint2(hi0, sh);
            }
            if (tid == 0 && !dry) TSG(30);
        }
        TS(8);
    }
}

typedef CUresult (*PFN_encodeTiled)(CUtensorMap*, CUtensorMapDataType, cuuint32_t, void*, const cuuint64_t*, const cuuint64_t*,
                                    const cuuint32_t*, const cuuint32_t*, CUtensorMapInterleave, CUtensorMapSwizzle,
                                    CUtensorMapL2promotion, CUtensorMapFloatOOBfill);

void make_map(PFN_encodeTiled enc, CUtensorMap* m, const void* base, int rank, const cuuint64_t* dims, const cuuint64_t* strides, const cuuint32_t* box) {
    cuuint32_t es[5] = {1, 1, 1, 1, 1};
    enc(m, CU_TENSOR_MAP_DATA_TYPE_BFLOAT16, (cuuint32_t)rank, const_cast<void*>(base), dims, strides, box, es,
        CU_TENSOR_MAP_INTERLEAVE_NONE, CU_TENSOR_MAP_SWIZZLE_128B, CU_TENSOR_MAP_L2_PROMOTION_L2_256B, CU_TENSOR_MAP_FLOAT_OOB_FILL_NONE);
}

}

extern "C" void kernel_launch(void* const* d_in, const int* in_sizes, int n_in, void* d_out, int out_size) {
    (void)in_sizes; (void)n_in; (void)out_size;
    const void* x = d_in[0]; const void* wqkv = d_in[1]; const void* wo = d_in[2];
    const void* w1 = d_in[4]; const void* w2 = d_in[5]; const void* gate_w = d_in[6];
    static PFN_encodeTiled enc = nullptr;
    static int ncta = 128;
    if (!enc) {
        int dev = 0, sms = 0;
        cudaGetDevice(&dev);
        cudaDeviceGetAttribute(&sms, cudaDevAttrMultiProcessorCount, dev);
        ncta = sms > 132 ? 132 : (sms > 128 ? sms : 128);
        void* fn = nullptr; cudaDriverEntryPointQueryResult st;
        cudaGetDriverEntryPoint("cuTensorMapEncodeTiled", &fn, cudaEnableDefault, &st);
        enc = (PFN_encodeTiled)fn;
        cudaFuncSetAttribute(fused_kernel, cudaFuncAttributeMaxDynamicSharedMemorySize, SMEM_BYTES);
    }
    CUtensorMap mx, mqkv, mw1, mw2, mwo, mw1a, mo;
    void* optr = nullptr;
    cudaGetSymbolAddress(&optr, g_o);
    { cuuint64_t d[2] = {512, 2048}, s[1] = {1024}; cuuint32_t b[2] = {64, 128}; make_map(enc, &mo, optr, 2, d, s, b); }
    { cuuint64_t d[4] = {64, 512, 3, 8}, s[3] = {3584, 128, 448}; cuuint32_t b[4] = {64, 32, 3, 1}; make_map(enc, &mw1a, w1, 4, d, s, b); }
    { cuuint64_t d[2] = {512, 2048}, s[1] = {1024}; cuuint32_t b[2] = {64, 128}; make_map(enc, &mx, x, 2, d, s, b); }
    { cuuint64_t d[4] = {64, 512, 8, 3}, s[3] = {3072, 128, 1024}; cuuint32_t b[4] = {64, 32, 1, 3}; make_map(enc, &mqkv, wqkv, 4, d, s, b); }
    { cuuint64_t d[2] = {1792, 512}, s[1] = {3584}; cuuint32_t b[2] = {64, 32}; make_map(enc, &mw1, w1, 2, d, s, b); }
    { cuuint64_t d[3] = {64, 1792, 8}, s[2] = {1024, 128}; cuuint32_t b[3] = {64, 32, 2}; make_map(enc, &mw2, w2, 3, d, s, b); }
    { cuuint64_t d[2] = {512, 512}, s[1] = {1024}; cuuint32_t b[2] = {64, 256}; make_map(enc, &mwo, wo, 2, d, s, b); }
    fused_kernel<<<ncta, 384, SMEM_BYTES, cudaStreamPerThread>>>(mx, mqkv, mw1, mw2, mwo, mw1a, mo, (const __nv_bfloat16*)gate_w, (__nv_bfloat16*)d_out,
                                           (const uint8_t*)w1, (const uint8_t*)w2, (const uint8_t*)wo);
}
```

```cpp
#include <cuda_runtime.h>
#include <cuda_bf16.h>
#include <cuda.h>
#include <stdint.h>

namespace {

#define PF1_AT 1
#define PF2_AT 5
#define LEAD1 1
constexpr int RING = 6;
constexpr int SLOT = 16384;
constexpr uint32_t X_OFF = 0;
constexpr uint32_t STG_OFF = X_OFF + 4 * 16384;
constexpr uint32_t RING_OFF = 131072;
constexpr uint32_t BAR_OFF = RING_OFF + RING * SLOT;
constexpr uint32_t B_FULL = BAR_OFF, B_EMPTY = BAR_OFF + 64, B_XFULL = BAR_OFF + 128, B_HDEAD = BAR_OFF + 192,
                   B_EREADY = BAR_OFF + 200, B_KVDONE = BAR_OFF + 208, B_ODONE = BAR_OFF + 224,
                   B_KVREADY = BAR_OFF + 232, B_WOFULL = BAR_OFF + 240, B_HSUM = BAR_OFF + 248, B_PREADY = BAR_OFF + 264,
                   B_SQ = BAR_OFF + 272, B_SF = BAR_OFF + 304, B_XDEAD = BAR_OFF + 320;
constexpr uint32_t EPOCH_OFF = BAR_OFF + 256, ITEM_OFF = BAR_OFF + 260;
constexpr uint32_t OWN_OFF = X_OFF + 4 * 16384;
constexpr uint32_t HSUM_OFF = X_OFF + 6 * 16384;
constexpr uint32_t SMEM_BYTES = BAR_OFF + 1024;

constexpr int N_QKV = 16, N_FFN1 = 16, N_FFN2 = 14, N_KV = 8, N_O = 7;

__device__ uint4 g_kf[32 * 128 * 32];
__device__ uint4 g_vf[32 * 128 * 32];
__device__ uint4 g_part[16 * 8 * 8 * 8 * 4 * 32];
__device__ __nv_bfloat16 g_o[2048 * 512];
__device__ unsigned g_ticket;
__device__ unsigned g_kvcnt[128 * 32];
__device__ unsigned g_pcnt[128 * 32];
__device__ unsigned g_ocnt[128 * 32];
#define TS(k) do {} while (0)
#define TS2(k) do {} while (0)
#define TS2X(k) do {} while (0)
#define TSX(k) do {} while (0)
#define TSG(k) do {} while (0)

__device__ __forceinline__ uint32_t smem_u32(const void* p) { return (uint32_t)__cvta_generic_to_shared(p); }
__device__ __forceinline__ void mbar_init(uint32_t bar, uint32_t cnt) { asm volatile("mbarrier.init.shared::cta.b64 [%0], %1;" :: "r"(bar), "r"(cnt) : "memory"); }
__device__ __forceinline__ void mbar_expect_tx(uint32_t bar, uint32_t bytes) { asm volatile("mbarrier.arrive.expect_tx.shared::cta.b64 _, [%0], %1;" :: "r"(bar), "r"(bytes) : "memory"); }
__device__ __forceinline__ void mbar_expect_only(uint32_t bar, uint32_t bytes) { asm volatile("mbarrier.expect_tx.relaxed.cta.shared::cta.b64 [%0], %1;" :: "r"(bar), "r"(bytes) : "memory"); }
__device__ __forceinline__ void mbar_arrive(uint32_t bar) { asm volatile("mbarrier.arrive.shared::cta.b64 _, [%0];" :: "r"(bar) : "memory"); }
__device__ __forceinline__ void mbar_wait(uint32_t bar, uint32_t parity) {
    asm volatile("{\n.reg .pred P1, P2;\n.reg .u32 n;\nmov.u32 n, 0;\n"
                 "WAIT_LOOP:\n"
                 "mbarrier.try_wait.parity.shared::cta.b64 P1, [%0], %1;\n"
                 "@P1 bra WAIT_DONE;\n"
                 "add.u32 n, n, 1;\n"
                 "setp.lt.u32 P2, n, 0x400000;\n"
                 "@P2 bra WAIT_LOOP;\n"
                 "WAIT_DONE:\n}" :: "r"(bar), "r"(parity) : "memory");
}
__device__ __forceinline__ void mbar_wait_idle(uint32_t bar, uint32_t parity) {
    asm volatile("{\n.reg .pred P1, P2;\n.reg .u32 n;\nmov.u32 n, 0;\n"
                 "WAIT_LOOP:\n"
                 "mbarrier.try_wait.parity.shared::cta.b64 P1, [%0], %1, 2000;\n"
                 "@P1 bra WAIT_DONE;\n"
                 "add.u32 n, n, 1;\n"
                 "setp.lt.u32 P2, n, 0x100000;\n"
                 "@P2 bra WAIT_LOOP;\n"
                 "WAIT_DONE:\n}" :: "r"(bar), "r"(parity) : "memory");
}
__device__ __forceinline__ void tma_2d(uint32_t dst, const void* map, uint32_t bar, int c0, int c1) {
    asm volatile("cp.async.bulk.tensor.2d.shared::cluster.global.mbarrier::complete_tx::bytes [%0], [%1, {%3, %4}], [%2];"
        :: "r"(dst), "l"(map), "r"(bar), "r"(c0), "r"(c1) : "memory");
}
__device__ __forceinline__ void tma_3d(uint32_t dst, const void* map, uint32_t bar, int c0, int c1, int c2) {
    asm volatile("cp.async.bulk.tensor.3d.shared::cluster.global.mbarrier::complete_tx::bytes [%0], [%1, {%3, %4, %5}], [%2];"
        :: "r"(dst), "l"(map), "r"(bar), "r"(c0), "r"(c1), "r"(c2) : "memory");
}
__device__ __forceinline__ void tma_4d(uint32_t dst, const void* map, uint32_t bar, int c0, int c1, int c2, int c3) {
    asm volatile("cp.async.bulk.tensor.4d.shared::cluster.global.mbarrier::complete_tx::bytes [%0], [%1, {%3, %4, %5, %6}], [%2];"
        :: "r"(dst), "l"(map), "r"(bar), "r"(c0), "r"(c1), "r"(c2), "r"(c3) : "memory");
}
__device__ __forceinline__ void bulk_g2s(uint32_t dst, const void* src, uint32_t bytes, uint32_t bar) {
    asm volatile("cp.async.bulk.shared::cluster.global.mbarrier::complete_tx::bytes [%0], [%1], %2, [%3];"
        :: "r"(dst), "l"(src), "r"(bytes), "r"(bar) : "memory");
}
__device__ __forceinline__ void prefetch_l2(const void* src, uint32_t bytes) {
    asm volatile("cp.async.bulk.prefetch.L2.global [%0], %1;" :: "l"(src), "r"(bytes) : "memory");
}
__device__ __forceinline__ bool elect_one() {
    uint32_t p;
    asm volatile("{\n.reg .pred P;\nelect.sync _|P, 0xffffffff;\nselp.u32 %0, 1, 0, P;\n}" : "=r"(p));
    return p != 0;
}
__device__ __forceinline__ void wgmma_fence() { asm volatile("wgmma.fence.sync.aligned;" ::: "memory"); }
__device__ __forceinline__ void wgmma_commit() { asm volatile("wgmma.commit_group.sync.aligned;" ::: "memory"); }
template <int N> __device__ __forceinline__ void wgmma_wait() { asm volatile("wgmma.wait_group.sync.aligned %0;" :: "n"(N) : "memory"); }
__device__ __forceinline__ void fence_async_smem() { asm volatile("fence.proxy.async.shared::cta;" ::: "memory"); }
__device__ __forceinline__ uint64_t desc_a(uint32_t addr) {
    return (uint64_t)((addr & 0x3FFFF) >> 4) | ((uint64_t)1 << 16) | ((uint64_t)(1024 >> 4) << 32) | ((uint64_t)1 << 62);
}
__device__ __forceinline__ uint64_t desc_b(uint32_t addr) {
    return (uint64_t)((addr & 0x3FFFF) >> 4) | ((uint64_t)(4096 >> 4) << 16) | ((uint64_t)(1024 >> 4) << 32) | ((uint64_t)1 << 62);
}
__device__ __forceinline__ uint32_t pack_bf16(float lo, float hi) {
    uint32_t r; asm("cvt.rn.bf16x2.f32 %0, %1, %2;" : "=r"(r) : "f"(hi), "f"(lo)); return r;
}
__device__ __forceinline__ uint32_t pack_bf16_relu(float lo, float hi) {
    uint32_t r; asm("cvt.rn.relu.bf16x2.f32 %0, %1, %2;" : "=r"(r) : "f"(hi), "f"(lo)); return r;
}
__device__ __forceinline__ uint32_t movmatrix(uint32_t a) {
    uint32_t d; asm volatile("movmatrix.sync.aligned.m8n8.trans.b16 %0, %1;" : "=r"(d) : "r"(a)); return d;
}
__device__ __forceinline__ void stmatrix_x4(uint32_t addr, uint32_t r0, uint32_t r1, uint32_t r2, uint32_t r3) {
    asm volatile("stmatrix.sync.aligned.m8n8.x4.shared.b16 [%0], {%1, %2, %3, %4};" :: "r"(addr), "r"(r0), "r"(r1), "r"(r2), "r"(r3) : "memory");
}
__device__ __forceinline__ uint4 lds128(uint32_t addr) {
    uint4 v; asm volatile("ld.shared.v4.b32 {%0, %1, %2, %3}, [%4];" : "=r"(v.x), "=r"(v.y), "=r"(v.z), "=r"(v.w) : "r"(addr) : "memory"); return v;
}
__device__ __forceinline__ uint4 lds128_free(uint32_t addr) {
    uint4 v; asm("ld.shared.v4.b32 {%0, %1, %2, %3}, [%4];" : "=r"(v.x), "=r"(v.y), "=r"(v.z), "=r"(v.w) : "r"(addr)); return v;
}
__device__ __forceinline__ void mma16816(float (&c)[4], uint32_t a0, uint32_t a1, uint32_t a2, uint32_t a3, uint32_t b0, uint32_t b1) {
    asm("mma.sync.aligned.m16n8k16.row.col.f32.bf16.bf16.f32 {%0,%1,%2,%3}, {%4,%5,%6,%7}, {%8,%9}, {%0,%1,%2,%3};"
        : "+f"(c[0]), "+f"(c[1]), "+f"(c[2]), "+f"(c[3]) : "r"(a0), "r"(a1), "r"(a2), "r"(a3), "r"(b0), "r"(b1));
}
__device__ __forceinline__ void mma16816_c(float (&c)[4], uint32_t a0, uint32_t a1, uint32_t a2, uint32_t a3, uint32_t b0, uint32_t b1, float ci) {
    asm("mma.sync.aligned.m16n8k16.row.col.f32.bf16.bf16.f32 {%0,%1,%2,%3}, {%4,%5,%6,%7}, {%8,%9}, {%10,%10,%10,%10};"
        : "=f"(c[0]), "=f"(c[1]), "=f"(c[2]), "=f"(c[3]) : "r"(a0), "r"(a1), "r"(a2), "r"(a3), "r"(b0), "r"(b1), "f"(ci));
}
__device__ __forceinline__ int opaque(int v) { asm volatile("" : "+r"(v)); return v; }
__device__ __forceinline__ float ex2(float x) { float y; asm("ex2.approx.ftz.f32 %0, %1;" : "=f"(y) : "f"(x)); return y; }
__device__ __forceinline__ unsigned ld_acquire(const unsigned* p) {
    unsigned v; asm volatile("ld.acquire.gpu.global.u32 %0, [%1];" : "=r"(v) : "l"(p) : "memory"); return v;
}
__device__ __forceinline__ void red_release(unsigned* p, unsigned v) {
    asm volatile("red.release.gpu.global.add.u32 [%0], %1;" :: "l"(p), "r"(v) : "memory");
}
__device__ __forceinline__ void wait_counter(const unsigned* p, unsigned target) {
    uint32_t n = 0;
    while ((int)(ld_acquire(p) - target) < 0) { if (++n > (1u << 20)) break; }
}
__device__ __forceinline__ uint4 ldg_weak(const uint4* p) {
    uint4 v; asm volatile("ld.global.L1::no_allocate.v4.b32 {%0, %1, %2, %3}, [%4];" : "=r"(v.x), "=r"(v.y), "=r"(v.z), "=r"(v.w) : "l"(p) : "memory"); return v;
}
__device__ __forceinline__ float bf_lo(uint32_t v) { return __uint_as_float(v << 16); }
__device__ __forceinline__ float bf_hi(uint32_t v) { return __uint_as_float(v & 0xFFFF0000u); }

__device__ __forceinline__ void wgmma_ss_n64(float (&d)[32], uint64_t da, uint64_t db, int scale_d) {
    asm volatile("{\n.reg .pred p;\nsetp.ne.b32 p, %34, 0;\n"
        "wgmma.mma_async.sync.aligned.m64n64k16.f32.bf16.bf16 {%0, %1, %2, %3, %4, %5, %6, %7, %8, %9, %10, %11, %12, %13, %14, %15, %16, %17, %18, %19, %20, %21, %22, %23, %24, %25, %26, %27, %28, %29, %30, %31}, %32, %33, p, 1, 1, 0, 1;\n}\n"
        : "+f"(d[0]), "+f"(d[1]), "+f"(d[2]), "+f"(d[3]), "+f"(d[4]), "+f"(d[5]), "+f"(d[6]), "+f"(d[7]), "+f"(d[8]), "+f"(d[9]), "+f"(d[10]), "+f"(d[11]), "+f"(d[12]), "+f"(d[13]), "+f"(d[14]), "+f"(d[15]), "+f"(d[16]), "+f"(d[17]), "+f"(d[18]), "+f"(d[19]), "+f"(d[20]), "+f"(d[21]), "+f"(d[22]), "+f"(d[23]), "+f"(d[24]), "+f"(d[25]), "+f"(d[26]), "+f"(d[27]), "+f"(d[28]), "+f"(d[29]), "+f"(d[30]), "+f"(d[31])
        : "l"(da), "l"(db), "r"(scale_d));
}
__device__ __forceinline__ void wgmma_ss_n128(float (&d)[64], uint64_t da, uint64_t db, int scale_d) {
    asm volatile("{\n.reg .pred p;\nsetp.ne.b32 p, %66, 0;\n"
        "wgmma.mma_async.sync.aligned.m64n128k16.f32.bf16.bf16 {%0, %1, %2, %3, %4, %5, %6, %7, %8, %9, %10, %11, %12, %13, %14, %15, %16, %17, %18, %19, %20, %21, %22, %23, %24, %25, %26, %27, %28, %29, %30, %31, %32, %33, %34, %35, %36, %37, %38, %39, %40, %41, %42, %43, %44, %45, %46, %47, %48, %49, %50, %51, %52, %53, %54, %55, %56, %57, %58, %59, %60, %61, %62, %63}, %64, %65, p, 1, 1, 0, 1;\n}\n"
        : "+f"(d[0]), "+f"(d[1]), "+f"(d[2]), "+f"(d[3]), "+f"(d[4]), "+f"(d[5]), "+f"(d[6]), "+f"(d[7]), "+f"(d[8]), "+f"(d[9]), "+f"(d[10]), "+f"(d[11]), "+f"(d[12]), "+f"(d[13]), "+f"(d[14]), "+f"(d[15]), "+f"(d[16]), "+f"(d[17]), "+f"(d[18]), "+f"(d[19]), "+f"(d[20]), "+f"(d[21]), "+f"(d[22]), "+f"(d[23]), "+f"(d[24]), "+f"(d[25]), "+f"(d[26]), "+f"(d[27]), "+f"(d[28]), "+f"(d[29]), "+f"(d[30]), "+f"(d[31]), "+f"(d[32]), "+f"(d[33]), "+f"(d[34]), "+f"(d[35]), "+f"(d[36]), "+f"(d[37]), "+f"(d[38]), "+f"(d[39]), "+f"(d[40]), "+f"(d[41]), "+f"(d[42]), "+f"(d[43]), "+f"(d[44]), "+f"(d[45]), "+f"(d[46]), "+f"(d[47]), "+f"(d[48]), "+f"(d[49]), "+f"(d[50]), "+f"(d[51]), "+f"(d[52]), "+f"(d[53]), "+f"(d[54]), "+f"(d[55]), "+f"(d[56]), "+f"(d[57]), "+f"(d[58]), "+f"(d[59]), "+f"(d[60]), "+f"(d[61]), "+f"(d[62]), "+f"(d[63])
        : "l"(da), "l"(db), "r"(scale_d));
}
__device__ __forceinline__ void wgmma_ss_n200(float (&d)[100], uint64_t da, uint64_t db, int scale_d) {
    asm volatile("{\n.reg .pred p;\nsetp.ne.b32 p, %102, 0;\n"
        "wgmma.mma_async.sync.aligned.m64n200k16.f32.bf16.bf16 {%0, %1, %2, %3, %4, %5, %6, %7, %8, %9, %10, %11, %12, %13, %14, %15, %16, %17, %18, %19, %20, %21, %22, %23, %24, %25, %26, %27, %28, %29, %30, %31, %32, %33, %34, %35, %36, %37, %38, %39, %40, %41, %42, %43, %44, %45, %46, %47, %48, %49, %50, %51, %52, %53, %54, %55, %56, %57, %58, %59, %60, %61, %62, %63, %64, %65, %66, %67, %68, %69, %70, %71, %72, %73, %74, %75, %76, %77, %78, %79, %80, %81, %82, %83, %84, %85, %86, %87, %88, %89, %90, %91, %92, %93, %94, %95, %96, %97, %98, %99}, %100, %101, p, 1, 1, 0, 1;\n}\n"
        : "+f"(d[0]), "+f"(d[1]), "+f"(d[2]), "+f"(d[3]), "+f"(d[4]), "+f"(d[5]), "+f"(d[6]), "+f"(d[7]), "+f"(d[8]), "+f"(d[9]), "+f"(d[10]), "+f"(d[11]), "+f"(d[12]), "+f"(d[13]), "+f"(d[14]), "+f"(d[15]), "+f"(d[16]), "+f"(d[17]), "+f"(d[18]), "+f"(d[19]), "+f"(d[20]), "+f"(d[21]), "+f"(d[22]), "+f"(d[23]), "+f"(d[24]), "+f"(d[25]), "+f"(d[26]), "+f"(d[27]), "+f"(d[28]), "+f"(d[29]), "+f"(d[30]), "+f"(d[31]), "+f"(d[32]), "+f"(d[33]), "+f"(d[34]), "+f"(d[35]), "+f"(d[36]), "+f"(d[37]), "+f"(d[38]), "+f"(d[39]), "+f"(d[40]), "+f"(d[41]), "+f"(d[42]), "+f"(d[43]), "+f"(d[44]), "+f"(d[45]), "+f"(d[46]), "+f"(d[47]), "+f"(d[48]), "+f"(d[49]), "+f"(d[50]), "+f"(d[51]), "+f"(d[52]), "+f"(d[53]), "+f"(d[54]), "+f"(d[55]), "+f"(d[56]), "+f"(d[57]), "+f"(d[58]), "+f"(d[59]), "+f"(d[60]), "+f"(d[61]), "+f"(d[62]), "+f"(d[63]), "+f"(d[64]), "+f"(d[65]), "+f"(d[66]), "+f"(d[67]), "+f"(d[68]), "+f"(d[69]), "+f"(d[70]), "+f"(d[71]), "+f"(d[72]), "+f"(d[73]), "+f"(d[74]), "+f"(d[75]), "+f"(d[76]), "+f"(d[77]), "+f"(d[78]), "+f"(d[79]), "+f"(d[80]), "+f"(d[81]), "+f"(d[82]), "+f"(d[83]), "+f"(d[84]), "+f"(d[85]), "+f"(d[86]), "+f"(d[87]), "+f"(d[88]), "+f"(d[89]), "+f"(d[90]), "+f"(d[91]), "+f"(d[92]), "+f"(d[93]), "+f"(d[94]), "+f"(d[95]), "+f"(d[96]), "+f"(d[97]), "+f"(d[98]), "+f"(d[99])
        : "l"(da), "l"(db), "r"(scale_d));
}
__device__ __forceinline__ void wgmma_ss_n224(float (&d)[112], uint64_t da, uint64_t db, int scale_d) {
    asm volatile("{\n.reg .pred p;\nsetp.ne.b32 p, %114, 0;\n"
        "wgmma.mma_async.sync.aligned.m64n224k16.f32.bf16.bf16 {%0, %1, %2, %3, %4, %5, %6, %7, %8, %9, %10, %11, %12, %13, %14, %15, %16, %17, %18, %19, %20, %21, %22, %23, %24, %25, %26, %27, %28, %29, %30, %31, %32, %33, %34, %35, %36, %37, %38, %39, %40, %41, %42, %43, %44, %45, %46, %47, %48, %49, %50, %51, %52, %53, %54, %55, %56, %57, %58, %59, %60, %61, %62, %63, %64, %65, %66, %67, %68, %69, %70, %71, %72, %73, %74, %75, %76, %77, %78, %79, %80, %81, %82, %83, %84, %85, %86, %87, %88, %89, %90, %91, %92, %93, %94, %95, %96, %97, %98, %99, %100, %101, %102, %103, %104, %105, %106, %107, %108, %109, %110, %111}, %112, %113, p, 1, 1, 0, 1;\n}\n"
        : "+f"(d[0]), "+f"(d[1]), "+f"(d[2]), "+f"(d[3]), "+f"(d[4]), "+f"(d[5]), "+f"(d[6]), "+f"(d[7]), "+f"(d[8]), "+f"(d[9]), "+f"(d[10]), "+f"(d[11]), "+f"(d[12]), "+f"(d[13]), "+f"(d[14]), "+f"(d[15]), "+f"(d[16]), "+f"(d[17]), "+f"(d[18]), "+f"(d[19]), "+f"(d[20]), "+f"(d[21]), "+f"(d[22]), "+f"(d[23]), "+f"(d[24]), "+f"(d[25]), "+f"(d[26]), "+f"(d[27]), "+f"(d[28]), "+f"(d[29]), "+f"(d[30]), "+f"(d[31]), "+f"(d[32]), "+f"(d[33]), "+f"(d[34]), "+f"(d[35]), "+f"(d[36]), "+f"(d[37]), "+f"(d[38]), "+f"(d[39]), "+f"(d[40]), "+f"(d[41]), "+f"(d[42]), "+f"(d[43]), "+f"(d[44]), "+f"(d[45]), "+f"(d[46]), "+f"(d[47]), "+f"(d[48]), "+f"(d[49]), "+f"(d[50]), "+f"(d[51]), "+f"(d[52]), "+f"(d[53]), "+f"(d[54]), "+f"(d[55]), "+f"(d[56]), "+f"(d[57]), "+f"(d[58]), "+f"(d[59]), "+f"(d[60]), "+f"(d[61]), "+f"(d[62]), "+f"(d[63]), "+f"(d[64]), "+f"(d[65]), "+f"(d[66]), "+f"(d[67]), "+f"(d[68]), "+f"(d[69]), "+f"(d[70]), "+f"(d[71]), "+f"(d[72]), "+f"(d[73]), "+f"(d[74]), "+f"(d[75]), "+f"(d[76]), "+f"(d[77]), "+f"(d[78]), "+f"(d[79]), "+f"(d[80]), "+f"(d[81]), "+f"(d[82]), "+f"(d[83]), "+f"(d[84]), "+f"(d[85]), "+f"(d[86]), "+f"(d[87]), "+f"(d[88]), "+f"(d[89]), "+f"(d[90]), "+f"(d[91]), "+f"(d[92]), "+f"(d[93]), "+f"(d[94]), "+f"(d[95]), "+f"(d[96]), "+f"(d[97]), "+f"(d[98]), "+f"(d[99]), "+f"(d[100]), "+f"(d[101]), "+f"(d[102]), "+f"(d[103]), "+f"(d[104]), "+f"(d[105]), "+f"(d[106]), "+f"(d[107]), "+f"(d[108]), "+f"(d[109]), "+f"(d[110]), "+f"(d[111])
        : "l"(da), "l"(db), "r"(scale_d));
}
template <int N> __device__ __forceinline__ void fence_acc(float (&d)[N]) {
#pragma unroll
    for (int i = 0; i < N; i++) asm volatile("" : "+f"(d[i]) :: "memory");
}

__device__ __forceinline__ void bulk_s2g(void* dst, uint32_t src, uint32_t bytes) {
    asm volatile("cp.async.bulk.global.shared::cta.bulk_group [%0], [%1], %2;" :: "l"(dst), "r"(src), "r"(bytes) : "memory");
}
__device__ __forceinline__ void sts128(uint32_t addr, uint4 v) {
    asm volatile("st.shared.v4.b32 [%0], {%1, %2, %3, %4};" :: "r"(addr), "r"(v.x), "r"(v.y), "r"(v.z), "r"(v.w) : "memory");
}
__device__ __forceinline__ void sum_partials(uint32_t sb, int ti, int tj, int lane) {
    for (;;) {
        uint32_t item = 0;
        if (lane == 0) asm volatile("atom.shared.add.u32 %0, [%1], 1;" : "=r"(item) : "r"(sb + ITEM_OFF) : "memory");
        item = __shfl_sync(0xffffffffu, item, 0);
        if (item >= 8) break;
        const uint4* p = g_part + (size_t)((ti * 8 + tj) * 8) * 1024 + item * 128 + lane;
        uint4 v[4][4];
#pragma unroll
        for (int s = 0; s < 4; s++)
#pragma unroll
            for (int n = 0; n < 4; n++) v[n][s] = ldg_weak(p + s * 1024 + n * 32);
#pragma unroll
        for (int n = 0; n < 4; n++) {
            float a[8];
#pragma unroll
            for (int e = 0; e < 8; e++) a[e] = 0.f;
#pragma unroll
            for (int s = 0; s < 4; s++) {
                a[0] += bf_lo(v[n][s].x); a[1] += bf_hi(v[n][s].x); a[2] += bf_lo(v[n][s].y); a[3] += bf_hi(v[n][s].y);
                a[4] += bf_lo(v[n][s].z); a[5] += bf_hi(v[n][s].z); a[6] += bf_lo(v[n][s].w); a[7] += bf_hi(v[n][s].w);
            }
            const uint32_t d = sb + HSUM_OFF + (item * 8 + n * 2) * 512 + lane * 16;
            sts128(d, make_uint4(__float_as_uint(a[0]), __float_as_uint(a[1]), __float_as_uint(a[2]), __float_as_uint(a[3])));
            sts128(d + 512, make_uint4(__float_as_uint(a[4]), __float_as_uint(a[5]), __float_as_uint(a[6]), __float_as_uint(a[7])));
        }
    }
    __syncwarp();
    if (lane == 0) mbar_arrive(sb + B_HSUM);
}

#define PWAIT() mbar_wait_idle(sb + B_EMPTY + 8 * r.slot, r.phase)
#define CWAIT() do { if (!dry) mbar_wait(sb + B_FULL + 8 * r.slot, r.phase); } while (0)
template <bool B> struct BoolTag { static constexpr bool value = B; };
struct Ring {
    int slot; uint32_t phase;
    __device__ __forceinline__ void next() { if (++slot == RING) { slot = 0; phase ^= 1; } }
};

__global__ void __launch_bounds__(384, 1)
fused_kernel(const __grid_constant__ CUtensorMap map_x, const __grid_constant__ CUtensorMap map_qkv,
             const __grid_constant__ CUtensorMap map_w1, const __grid_constant__ CUtensorMap map_w2,
             const __grid_constant__ CUtensorMap map_wo, const __grid_constant__ CUtensorMap map_w1a,
             const __grid_constant__ CUtensorMap map_o,
             const __nv_bfloat16* __restrict__ gate_w, __nv_bfloat16* __restrict__ out,
             const uint8_t* __restrict__ w1p, const uint8_t* __restrict__ w2p, const uint8_t* __restrict__ wop)
{
    extern __shared__ __align__(1024) uint8_t smem_raw[];
    const uint32_t sb = smem_u32(smem_raw);
    const int tid = threadIdx.x, warp = tid >> 5, lane = tid & 31;
    const bool dry = blockIdx.x >= 128;
    const int ti = dry ? (int)(blockIdx.x & 1) * 2 : blockIdx.x >> 3, tj = blockIdx.x & 7;
    if (dry && warp >= 8) {
        asm volatile("setmaxnreg.dec.sync.aligned.u32 88;");
        return;
    }

    if (tid == 0 && !dry) { TSG(31); TSX(0); }
    if (tid == 320) {
        asm volatile("prefetch.tensormap [%0];" :: "l"(&map_x) : "memory");
        asm volatile("prefetch.tensormap [%0];" :: "l"(&map_qkv) : "memory");
        asm volatile("prefetch.tensormap [%0];" :: "l"(&map_w1) : "memory");
        asm volatile("prefetch.tensormap [%0];" :: "l"(&map_w1a) : "memory");
        asm volatile("prefetch.tensormap [%0];" :: "l"(&map_w2) : "memory");
        asm volatile("prefetch.tensormap [%0];" :: "l"(&map_wo) : "memory");
        asm volatile("prefetch.tensormap [%0];" :: "l"(&map_o) : "memory");
    }
    if (tid == 256) {
        mbar_init(sb + B_FULL, 1); mbar_init(sb + B_XFULL, 1);
        fence_async_smem();
        mbar_expect_tx(sb + B_XFULL, 16384);
        tma_2d(sb + X_OFF, &map_x, sb + B_XFULL, 0, ti * 128);
        mbar_expect_only(sb + B_FULL, 12288);
        tma_4d(sb + RING_OFF, &map_qkv, sb + B_FULL, 0, 0, tj, 0);
    }
    uint32_t gwv[N_QKV / 2];
    if (warp == 8) {
        const unsigned short* gws = reinterpret_cast<const unsigned short*>(gate_w);
#pragma unroll
        for (int n = 0; n < N_QKV / 2; n++) gwv[n] = (uint32_t)__ldg(gws + 64 * n + lane) | ((uint32_t)__ldg(gws + 64 * n + 32 + lane) << 16);
    }
    if (tid == 288) {
        for (int s = 1; s < RING; s++) mbar_init(sb + B_FULL + 8 * s, 1);
        for (int s = 0; s < RING; s++) mbar_init(sb + B_EMPTY + 8 * s, 8);
        for (int s = 1; s < 8; s++) mbar_init(sb + B_XFULL + 8 * s, 1);
        fence_async_smem();
    }
    if (tid == 352) {
        mbar_init(sb + B_HDEAD, 8); mbar_init(sb + B_EREADY, 1); mbar_init(sb + B_KVDONE, 8); mbar_init(sb + B_KVREADY, 1);
        mbar_init(sb + B_ODONE, 8); mbar_init(sb + B_WOFULL, 1); mbar_init(sb + B_HSUM, 3);
        mbar_init(sb + B_XDEAD, 8); mbar_init(sb + B_PREADY, 1); mbar_init(sb + B_SF, 1); mbar_init(sb + B_SF + 8, 1);
        for (int s = 0; s < 4; s++) mbar_init(sb + B_SQ + 8 * s, 8);
        asm volatile("st.shared.u32 [%0], %1;" :: "r"(sb + ITEM_OFF), "r"(0) : "memory");
        fence_async_smem();
    }
    if (!dry) __syncthreads();

    if (warp >= 8) {
        asm volatile("setmaxnreg.dec.sync.aligned.u32 88;");
        if (warp == 8) {
            Ring r{0, 1};
            const bool leader = elect_one();
#pragma unroll
            for (int n = 0; n < N_QKV; n++) {
                const uint32_t full = sb + B_FULL + 8 * r.slot, dst = sb + RING_OFF + r.slot * SLOT;
                if (n > 0) {
                    if (!(n & 1) && leader) {
                        mbar_expect_tx(sb + B_XFULL + 8 * (n >> 1), 16384);
                        tma_2d(sb + X_OFF + (n >> 1) * 16384, &map_x, sb + B_XFULL + 8 * (n >> 1), (n >> 1) * 64, ti * 128);
                    }
                    if (n >= RING) PWAIT();
                    if (leader) {
                        mbar_expect_only(full, 12288);
                        tma_4d(dst, &map_qkv, full, 0, 32 * n, tj, 0);
                    }
                }
                const uint32_t gv = (n & 1) ? (gwv[n >> 1] >> 16) : (gwv[n >> 1] & 0xFFFFu);
                asm volatile("st.shared.v4.b32 [%0], {%1, %2, %2, %2};" :: "r"(dst + 12288 + lane * 128 + ((lane & 7) << 4)), "r"(gv), "r"(0) : "memory");
                fence_async_smem();
                __syncwarp();
                if (leader) mbar_arrive(full);
                r.next();
            }
#pragma unroll 1
            for (int n = 0; n < N_FFN1; n++) {
                const uint32_t full = sb + B_FULL + 8 * r.slot, dst = sb + RING_OFF + r.slot * SLOT;
                PWAIT();
                if (leader) {
                    mbar_expect_tx(full, 16384);
                    tma_4d(dst, &map_w1a, full, 0, 32 * n, 0, tj);
                    tma_2d(dst + 3 * 4096, &map_w1, full, 224 * tj + 192, 32 * n);
                }
                r.next();
            }
            {
                int q = 0, rr = 0;
#pragma unroll 1
                for (int n = 0; n < N_FFN2; n++) {
                    const uint32_t full = sb + B_FULL + 8 * r.slot, dst = sb + RING_OFF + r.slot * SLOT;
                    PWAIT();
                    if (leader) mbar_expect_tx(full, 16384);
#pragma unroll
                    for (int h = 0; h < 2; h++) {
                        if (leader) tma_3d(dst + h * 8192, &map_w2, full, 0, 224 * tj + 32 * rr, 2 * q);
                        if (++rr == 7) { rr = 0; q++; }
                    }
                    r.next();
                }
            }
            mbar_wait_idle(sb + B_KVREADY, 0);
            asm volatile("fence.proxy.async.global;" ::: "memory");
            {
                const int bbase = 8 * ti - 16, b0 = bbase < 0 ? 0 : bbase;
                const uint32_t bytes = (uint32_t)(8 * ti + 8 - b0) * 512;
#pragma unroll 1
                for (int m = 0; m < N_KV; m++) {
                    const uint32_t full = sb + B_FULL + 8 * r.slot, dst = sb + RING_OFF + r.slot * SLOT;
                    if (m == RING) {
                        mbar_wait_idle(sb + B_HDEAD, 0);
                        if (leader) {
                            mbar_expect_tx(sb + B_WOFULL, 65536);
#pragma unroll
                            for (int e = 0; e < 2; e++) tma_2d(sb + X_OFF + e * 32768, &map_wo, sb + B_WOFULL, 64 * tj, 256 * e);
                        }
                    }
                    PWAIT();
                    if (leader) {
                        const uint4* src = ((m & 1) ? g_vf : g_kf) + ((tj * 4 + (m >> 1)) * 128 + b0) * 32;
                        mbar_expect_tx(full, bytes);
                        bulk_g2s(dst + (b0 - bbase) * 512, src, bytes, full);
                    }
                    r.next();
                }
            }
            {
                mbar_wait_idle(sb + B_EREADY, 0);
                unsigned epoch; asm volatile("ld.shared.u32 %0, [%1];" : "=r"(epoch) : "r"(sb + EPOCH_OFF) : "memory");
                uint32_t ready = 0;
                mbar_wait_idle(sb + B_HSUM, 0);
#pragma unroll 1
                for (int m = 0; m < N_O; m++) {
                    const uint32_t full = sb + B_FULL + 8 * r.slot, dst = sb + RING_OFF + r.slot * SLOT;
                    PWAIT();
                    const int js = (tj + 1 + m) & 7;
                    for (int it = 0; it < (1 << 20) && !((ready >> js) & 1); it++) {
                        bool ok = false;
                        if (lane < 8) ok = (int)(ld_acquire(&g_ocnt[(ti * 8 + lane) * 32]) - (epoch + 1)) >= 0;
                        ready = __ballot_sync(0xffffffffu, ok);
                        if (!((ready >> js) & 1)) __nanosleep(100);
                    }
                    asm volatile("fence.proxy.async.global;" ::: "memory");
                    if (leader) {
                        mbar_expect_tx(full, 16384);
                        tma_2d(dst, &map_o, full, 64 * js, ti * 128);
                    }
                    r.next();
                }
            }
        } else if (warp == 9) {
            unsigned epoch = 0;
            if (lane == 0) {
                epoch = atomicAdd(&g_ticket, 1u) >> 7;
                asm volatile("st.shared.u32 [%0], %1;" :: "r"(sb + EPOCH_OFF), "r"(epoch) : "memory");
                mbar_arrive(sb + B_EREADY);
                mbar_wait_idle(sb + B_XFULL + 8 * PF1_AT, 0);
                prefetch_l2(w1p + (size_t)blockIdx.x * 14336, 14336);
                mbar_wait_idle(sb + B_XFULL + 8 * PF2_AT, 0);
                prefetch_l2(w2p + (size_t)blockIdx.x * 14336, 14336);
                prefetch_l2(wop + (size_t)blockIdx.x * 4096, 4096);
                mbar_wait_idle(sb + B_KVDONE, 0);
                red_release(&g_kvcnt[blockIdx.x * 32], 1u);
            }
            epoch = __shfl_sync(0xffffffffu, epoch, 0);
            if (lane < 3 && ti - lane >= 0) wait_counter(&g_kvcnt[((ti - lane) * 8 + tj) * 32], epoch + 1);
            __syncwarp();
            if (lane == 0) mbar_arrive(sb + B_KVREADY);
            mbar_wait_idle(sb + B_SQ + 24, 0);
            if (lane < 8) wait_counter(&g_pcnt[(ti * 8 + lane) * 32], epoch + 1);
            __syncwarp();
            if (lane == 0) { mbar_arrive(sb + B_PREADY); TSX(13); }
            sum_partials(sb, ti, tj, lane);
            if (lane == 0) TSX(14);
        } else {
            if (warp == 10) {
#pragma unroll 1
                for (int q = 0; q < 4; q++) {
                    mbar_wait_idle(sb + B_SQ + 8 * q, 0);
                    if (lane < 16) {
                        uint4* d = g_part + (size_t)(((ti * 8 + 2 * q + (lane & 1)) * 8 + tj) * 8 + (lane >> 1)) * 128;
                        bulk_s2g(d, sb + STG_OFF + (q & 1) * 32768 + lane * 2048, 2048);
                        asm volatile("cp.async.bulk.commit_group;" ::: "memory");
                        asm volatile("cp.async.bulk.wait_group.read 0;" ::: "memory");
                    }
                    __syncwarp();
                    if (lane == 0) mbar_arrive(sb + B_SF + 8 * (q & 1));
                }
                asm volatile("cp.async.bulk.wait_group 0;" ::: "memory");
                asm volatile("fence.proxy.async.global;" ::: "memory");
                __syncwarp();
                if (lane == 0) { red_release(&g_pcnt[blockIdx.x * 32], 1u); TSX(12); }
            }
            mbar_wait_idle(sb + B_PREADY, 0);
            sum_partials(sb, ti, tj, lane);
            if (warp == 11 && lane == 0) {
                mbar_wait_idle(sb + B_ODONE, 0);
                red_release(&g_ocnt[blockIdx.x * 32], 1u);
            }
        }
    } else {
        asm volatile("setmaxnreg.inc.sync.aligned.u32 208;");
        const int wg = warp >> 2, g = lane >> 2, c = lane & 3;
        const uint32_t xa = sb + X_OFF + wg * 8192;
        Ring r{0, 0};
        const bool lane0 = lane == 0 && !dry;
        uint32_t qf[4][4];
        float g0, g1;
        TS(9);
        {
            float acc[100];
            int prev = 0;
            if (wg == 1) asm volatile("bar.sync 3, 256;" ::: "memory");
            for (int s = 0; s < (dry ? 4 : N_QKV); s++) {
                if (!(s & 1) && !dry) mbar_wait(sb + B_XFULL + 8 * (s >> 1), 0);
                CWAIT();
                if (s == 0) TS(1);
                if (s == 2) TS(28);
                if (s == 6) TS(29);
                if (s == 10) TS(20);
                const uint32_t bs = sb + RING_OFF + r.slot * SLOT, as = xa + (s >> 1) * 16384 + (s & 1) * 64;
                wgmma_fence();
                wgmma_ss_n200(acc, desc_a(as), desc_b(bs), s);
                wgmma_ss_n200(acc, desc_a(as + 32), desc_b(bs + 2048), 1);
                wgmma_commit();
                if (wg == 0 && s == LEAD1) asm volatile("bar.arrive 3, 256;" ::: "memory");
                if (s > 0) { wgmma_wait<1>(); if (lane0) mbar_arrive(sb + B_EMPTY + 8 * prev); }
                prev = r.slot; r.next();
            }
            wgmma_wait<0>();
            fence_acc(acc);
            if (lane0) mbar_arrive(sb + B_EMPTY + 8 * prev);
            TS(2);
            const int blk = ti * 8 + warp;
#pragma unroll
            for (int hh = 0; hh < 4; hh++) {
                const float* t0 = &acc[8 * hh]; const float* t1 = &acc[8 * hh + 4];
                qf[hh][0] = pack_bf16(t0[0], t0[1]); qf[hh][1] = pack_bf16(t0[2], t0[3]);
                qf[hh][2] = pack_bf16(t1[0], t1[1]); qf[hh][3] = pack_bf16(t1[2], t1[3]);
                const float* k0 = &acc[32 + 8 * hh]; const float* k1 = &acc[32 + 8 * hh + 4];
                uint4 kv;
                kv.x = pack_bf16(k0[0], k0[1]); kv.y = pack_bf16(k1[0], k1[1]);
                kv.z = pack_bf16(k0[2], k0[3]); kv.w = pack_bf16(k1[2], k1[3]);
                if (!dry) g_kf[((tj * 4 + hh) * 128 + blk) * 32 + lane] = kv;
                const float* v0 = &acc[64 + 8 * hh]; const float* v1 = &acc[64 + 8 * hh + 4];
                uint4 vv;
                vv.x = movmatrix(pack_bf16(v0[0], v0[1])); vv.y = movmatrix(pack_bf16(v0[2], v0[3]));
                vv.z = movmatrix(pack_bf16(v1[0], v1[1])); vv.w = movmatrix(pack_bf16(v1[2], v1[3]));
                if (!dry) g_vf[((tj * 4 + hh) * 128 + blk) * 32 + lane] = vv;
            }
            __syncwarp();
            if (lane0) mbar_arrive(sb + B_KVDONE);
            const float z0 = __shfl_sync(0xffffffffu, acc[96], lane & ~3), z1 = __shfl_sync(0xffffffffu, acc[98], lane & ~3);
            g0 = 1.f / (1.f + __expf(-z0)); g1 = 1.f / (1.f + __expf(-z1));
        }
        TS(3);
        const int wrow = (warp & 3) * 16;
        {
            float acc[112];
            int prev = 0;
            for (int s = 0; s < (dry ? 4 : N_FFN1); s++) {
                CWAIT();
                const uint32_t bs = sb + RING_OFF + r.slot * SLOT, as = xa + (s >> 1) * 16384 + (s & 1) * 64;
                wgmma_fence();
                wgmma_ss_n224(acc, desc_a(as), desc_b(bs), s);
                wgmma_ss_n224(acc, desc_a(as + 32), desc_b(bs + 2048), 1);
                wgmma_commit();
                if (s > 0) { wgmma_wait<1>(); if (lane0) mbar_arrive(sb + B_EMPTY + 8 * prev); }
                prev = r.slot; r.next();
            }
            wgmma_wait<0>();
            fence_acc(acc);
            if (lane0) { mbar_arrive(sb + B_EMPTY + 8 * prev); mbar_arrive(sb + B_XDEAD); }
            TS(4);
            const float s0 = 1.f - g0, s1 = 1.f - g1;
            asm volatile("bar.sync %0, 128;" :: "r"(1 + wg) : "memory");
            const uint32_t strow = xa + (wrow + ((lane >> 3) & 1) * 8 + (lane & 7)) * 128;
#pragma unroll
            for (int p = 0; p < 14; p++) {
                const int nt = 2 * p + (lane >> 4);
                const float* a = &acc[8 * p];
                stmatrix_x4(strow + (p >> 2) * 16384 + (((nt & 7) ^ (lane & 7)) << 4),
                            pack_bf16_relu(a[0] * s0, a[1] * s0), pack_bf16_relu(a[2] * s1, a[3] * s1),
                            pack_bf16_relu(a[4] * s0, a[5] * s0), pack_bf16_relu(a[6] * s1, a[7] * s1));
            }
        }
        TS(5);
        {
            fence_async_smem();
            asm volatile("bar.sync %0, 128;" :: "r"(1 + wg) : "memory");
            float accA[64], accB[64];
            auto epilogue = [&](float (&acc)[64], int q) {
                fence_acc(acc);
                const uint32_t st = sb + STG_OFF + (q & 1) * 32768 + warp * 4096;
                if (q == 0 && !dry) mbar_wait(sb + B_XDEAD, 0);
                if (q >= 2 && !dry) mbar_wait(sb + B_SF + 8 * (q & 1), 0);
#pragma unroll
                for (int t2 = 0; t2 < 8; t2++) {
                    uint4 v;
                    v.x = pack_bf16(acc[8 * t2 + 0], acc[8 * t2 + 1]); v.y = pack_bf16(acc[8 * t2 + 2], acc[8 * t2 + 3]);
                    v.z = pack_bf16(acc[8 * t2 + 4], acc[8 * t2 + 5]); v.w = pack_bf16(acc[8 * t2 + 6], acc[8 * t2 + 7]);
                    sts128(st + t2 * 512 + lane * 16, v);
                }
                fence_async_smem();
                __syncwarp();
                if (lane0) mbar_arrive(sb + B_SQ + 8 * q);
            };
            int rel = r.slot;
#pragma unroll
            for (int m = 0; m < N_FFN2; m++) {
                CWAIT();
                wgmma_fence();
#pragma unroll
                for (int h = 0; h < 2; h++) {
                    const int u = 2 * m + h, q = u / 7, rr = u % 7;
                    const uint32_t bs = sb + RING_OFF + r.slot * SLOT + h * 8192;
                    const uint32_t as = xa + (rr >> 1) * 16384 + (rr & 1) * 64;
                    if (!(q & 1)) {
                        wgmma_ss_n128(accA, desc_a(as), desc_b(bs), rr);
                        wgmma_ss_n128(accA, desc_a(as + 32), desc_b(bs + 2048), 1);
                    } else {
                        wgmma_ss_n128(accB, desc_a(as), desc_b(bs), rr);
                        wgmma_ss_n128(accB, desc_a(as + 32), desc_b(bs + 2048), 1);
                    }
                }
                wgmma_commit();
                r.next();
                wgmma_wait<1>();
                if (m > 0) {
                    if (lane0) mbar_arrive(sb + B_EMPTY + 8 * rel);
                    if (++rel == RING) rel = 0;
                }
                if (m == 4) { TS(25); epilogue(accA, 0); }
                if (m == 7) { TS(26); epilogue(accB, 1); }
                if (m == 11) { TS(27); epilogue(accA, 2); }
            }
            wgmma_wait<0>();
            if (lane0) { mbar_arrive(sb + B_EMPTY + 8 * rel); mbar_arrive(sb + B_HDEAD); }
            epilogue(accB, 3);
        }
        TS(6);
        {
            const float SC = 0.25f * 1.4426950408889634f;
            const int gb0 = 8 * ti - 16 + warp;
            int slotK = 0, slotV = 0;
            const uint32_t ostore = sb + OWN_OFF + (warp * 16 + ((lane >> 3) & 1) * 8 + (lane & 7)) * 128;
            uint32_t* odst = reinterpret_cast<uint32_t*>(g_o + (size_t)(ti * 128 + warp * 16 + g) * 512 + tj * 64 + ((lane & 1) ? 8 : 0) + (lane & 2) * 2);
#define NHEADS (dry ? 2 : 4)
#define ATT_KWAIT(kb) do { slotK = r.slot; CWAIT(); kb = sb + RING_OFF + slotK * SLOT + warp * 512 + lane * 16; r.next(); } while (0)
#define ATT_VWAIT(vb) do { slotV = r.slot; CWAIT(); vb = sb + RING_OFF + slotV * SLOT + warp * 512 + lane * 16; r.next(); TS(21 + hh); } while (0)
#define ATT_KVREL() do { __syncwarp(); if (lane0) { mbar_arrive(sb + B_EMPTY + 8 * slotK); mbar_arrive(sb + B_EMPTY + 8 * slotV); } } while (0)
#define ATT_NEXTQ(h) do { \
                if ((h) == 1) { q0 = qf[1][0]; q1 = qf[1][1]; q2 = qf[1][2]; q3 = qf[1][3]; } \
                else if ((h) == 2) { q0 = qf[2][0]; q1 = qf[2][1]; q2 = qf[2][2]; q3 = qf[2][3]; } \
                else { q0 = qf[3][0]; q1 = qf[3][1]; q2 = qf[3][2]; q3 = qf[3][3]; } } while (0)
#define ATT_STORE(h, r0, r1, r2, r3) do { \
                if ((h) == 0 && !dry) mbar_wait(sb + B_SF, 1);        \
                stmatrix_x4(ostore + (((2 * (h) + (lane >> 4)) ^ (lane & 7)) << 4), r0, r1, r2, r3); \
                const bool odd = lane & 1; \
                const uint32_t sl = __shfl_xor_sync(0xffffffffu, odd ? (r0) : (r2), 1), sh = __shfl_xor_sync(0xffffffffu, odd ? (r1) : (r3), 1); \
                if (!dry) *reinterpret_cast<uint2*>(odst + 8 * (h)) = odd ? make_uint2(sl, r2) : make_uint2(r0, sl); \
                if (!dry) *reinterpret_cast<uint2*>(odst + 8 * (h) + 8 * 256) = odd ? make_uint2(sh, r3) : make_uint2(r1, sh); \
                } while (0)
            auto attention = [&](auto masked_tag) {
            constexpr bool MASKED = decltype(masked_tag)::value;
            const float NEG = -INFINITY;
            const uint32_t ONES = 0x3F803F80u;
            float sa[8][2][4];
            float o[2][4], ls[4];
            float m0, m1;
            uint32_t q0 = qf[0][0], q1 = qf[0][1], q2 = qf[0][2], q3 = qf[0][3];
            auto qk = [&](float (&s)[8][2][4], int ps, int t, uint32_t kbase, bool merged) {
                if (merged) {
                    const uint4 kd = lds128_free(kbase + 16 * 512);
                    const uint4 kf = lds128_free(kbase);
                    float f[2][4];
                    const float ci = (!MASKED || opaque(gb0) >= 0) ? 0.f : NEG;
                    mma16816_c(s[0][0], q0, q1, q2, q3, kd.x, kd.y, 0.f);
                    mma16816_c(s[0][1], q0, q1, q2, q3, kd.z, kd.w, 0.f);
                    mma16816_c(f[0], q0, q1, q2, q3, kf.x, kf.y, ci);
                    mma16816_c(f[1], q0, q1, q2, q3, kf.z, kf.w, ci);
#pragma unroll
                    for (int u = 0; u < 2; u++)
#pragma unroll
                        for (int e = 0; e < 4; e++) {
                            const int row = g + 8 * (e >> 1), col = 8 * u + 2 * c + (e & 1);
                            s[0][u][e] = (col > row) ? f[u][e] : s[0][u][e];
                        }
                } else {
                    const uint4 kf = lds128_free(kbase + (8 * ps + t) * 512);
                    const float ci = (!MASKED || opaque(gb0) + 8 * ps + t >= 0) ? 0.f : NEG;
                    mma16816_c(s[t][0], q0, q1, q2, q3, kf.x, kf.y, ci);
                    mma16816_c(s[t][1], q0, q1, q2, q3, kf.z, kf.w, ci);
                }
            };
            auto rowmax = [&](float (&s)[8][2][4], float b0, float b1, float& n0, float& n1) {
                int i0 = __float_as_int(b0), i1 = __float_as_int(b1);
#pragma unroll
                for (int t = 0; t < 8; t++)
#pragma unroll
                    for (int u = 0; u < 2; u++) {
                        i0 = __vimax3_s32(i0, __float_as_int(s[t][u][0]), __float_as_int(s[t][u][1]));
                        i1 = __vimax3_s32(i1, __float_as_int(s[t][u][2]), __float_as_int(s[t][u][3]));
                    }
                i0 = max(i0, __shfl_xor_sync(0xffffffffu, i0, 1)); i1 = max(i1, __shfl_xor_sync(0xffffffffu, i1, 1));
                i0 = max(i0, __shfl_xor_sync(0xffffffffu, i0, 2)); i1 = max(i1, __shfl_xor_sync(0xffffffffu, i1, 2));
                n0 = __int_as_float(i0); n1 = __int_as_float(i1);
                if (__any_sync(0xffffffffu, (i0 | i1) < 0)) {
                    asm volatile("" ::: "memory");
                    n0 = b0; n1 = b1;
#pragma unroll
                    for (int t = 0; t < 8; t++)
#pragma unroll
                        for (int u = 0; u < 2; u++) {
                            n0 = fmaxf(n0, fmaxf(s[t][u][0], s[t][u][1]));
                            n1 = fmaxf(n1, fmaxf(s[t][u][2], s[t][u][3]));
                        }
                    n0 = fmaxf(n0, __shfl_xor_sync(0xffffffffu, n0, 1)); n1 = fmaxf(n1, __shfl_xor_sync(0xffffffffu, n1, 1));
                    n0 = fmaxf(n0, __shfl_xor_sync(0xffffffffu, n0, 2)); n1 = fmaxf(n1, __shfl_xor_sync(0xffffffffu, n1, 2));
                }
            };
            auto pv = [&](const float (&p)[2][4], uint32_t vaddr) {
                const uint4 vf = lds128_free(vaddr);
                const uint32_t a0 = pack_bf16(p[0][0], p[0][1]), a1 = pack_bf16(p[0][2], p[0][3]);
                const uint32_t a2 = pack_bf16(p[1][0], p[1][1]), a3 = pack_bf16(p[1][2], p[1][3]);
                mma16816(o[0], a0, a1, a2, a3, vf.x, vf.y);
                mma16816(o[1], a0, a1, a2, a3, vf.z, vf.w);
                mma16816(ls, a0, a1, a2, a3, ONES, ONES);
            };
            auto expv = [&](float (&s)[8][2][4], int ps, int t, float mc0, float mc1, uint32_t vbase, bool merged) {
                float p[2][4];
#pragma unroll
                for (int u = 0; u < 2; u++) {
                    p[u][0] = ex2(fmaf(s[t][u][0], SC, -mc0)); p[u][1] = ex2(fmaf(s[t][u][1], SC, -mc0));
                    p[u][2] = ex2(fmaf(s[t][u][2], SC, -mc1)); p[u][3] = ex2(fmaf(s[t][u][3], SC, -mc1));
                }
                if (merged) {
                    float pd[2][4], pf[2][4];
#pragma unroll
                    for (int u = 0; u < 2; u++)
#pragma unroll
                        for (int e = 0; e < 4; e++) {
                            const int row = g + 8 * (e >> 1), col = 8 * u + 2 * c + (e & 1);
                            pf[u][e] = (col > row) ? p[u][e] : 0.f;
                            pd[u][e] = (col > row) ? 0.f : p[u][e];
                        }
                    pv(pd, vbase + 16 * 512);
                    pv(pf, vbase);
                } else {
                    pv(p, vbase + (8 * ps + t) * 512);
                }
            };
            uint32_t kbase = 0, vbase = 0;
#pragma unroll 1
            for (int hh = 0; hh < NHEADS; hh++) {
                ATT_KWAIT(kbase);
                ATT_VWAIT(vbase);
                asm volatile("" : "+r"(kbase), "+r"(vbase) :: "memory");
                if (hh > 0) ATT_NEXTQ(hh);
#pragma unroll
                for (int ps = 0; ps < 2; ps++) {
#pragma unroll
                    for (int t = 0; t < 8; t++) qk(sa, ps, t, kbase, ps == 0 && t == 0);
                    float n0, n1;
                    rowmax(sa, ps ? m0 : NEG, ps ? m1 : NEG, n0, n1);
                    if (ps == 0) {
#pragma unroll
                        for (int e = 0; e < 4; e++) { o[0][e] = 0.f; o[1][e] = 0.f; ls[e] = 0.f; }
                    } else {
                        const float a0 = ex2((m0 - n0) * SC), a1 = ex2((m1 - n1) * SC);
                        ls[0] *= a0; ls[2] *= a1;
                        o[0][0] *= a0; o[0][1] *= a0; o[1][0] *= a0; o[1][1] *= a0;
                        o[0][2] *= a1; o[0][3] *= a1; o[1][2] *= a1; o[1][3] *= a1;
                    }
                    m0 = n0; m1 = n1;
                    const float mc0 = n0 * SC, mc1 = n1 * SC;
#pragma unroll
                    for (int t = 0; t < 8; t++) expv(sa, ps, t, mc0, mc1, vbase, ps == 0 && t == 0);
                }
                const float f0 = __fdividef(g0, ls[0]), f1 = __fdividef(g1, ls[2]);
                ATT_STORE(hh, pack_bf16(o[0][0] * f0, o[0][1] * f0), pack_bf16(o[0][2] * f1, o[0][3] * f1),
                              pack_bf16(o[1][0] * f0, o[1][1] * f0), pack_bf16(o[1][2] * f1, o[1][3] * f1));
                ATT_KVREL();
            }
            };
            if (ti >= 2) attention(BoolTag<false>{}); else attention(BoolTag<true>{});
            fence_async_smem();
            __syncwarp();
            if (lane0) mbar_arrive(sb + B_ODONE);
        }
        TS(7);
        {
            float acc[32];
            uint4 pv[4][4];
            if (!dry) mbar_wait(sb + B_PREADY, 0);
            {
                const uint4* p = g_part + (size_t)((ti * 8 + tj) * 8 + 4) * 1024 + warp * 128 + lane;
#pragma unroll
                for (int s = 0; s < 4; s++)
#pragma unroll
                    for (int n = 0; n < 4; n++) pv[n][s] = dry ? make_uint4(0u, 0u, 0u, 0u) : ldg_weak(p + s * 1024 + n * 32);
            }
            if (!dry) mbar_wait(sb + B_WOFULL, 0);
            if (!dry) mbar_wait(sb + B_ODONE, 0);
            TS(15);
            wgmma_fence();
#pragma unroll
            for (int k = 0; k < 4; k++) wgmma_ss_n64(acc, desc_a(sb + OWN_OFF + wg * 8192 + 32 * k), desc_b(sb + X_OFF + tj * 8192 + 2048 * k), k);
            wgmma_commit();
            TS(16);
#pragma unroll 1
            for (int m = 0; m < N_O; m++) {
                CWAIT();
                const uint32_t js = tj + 1 + m;
                const uint32_t as = sb + RING_OFF + r.slot * SLOT + wg * 8192;
                const uint32_t bs = sb + X_OFF + (js & 7) * 8192;
                wgmma_fence();
#pragma unroll
                for (int k = 0; k < 4; k++) wgmma_ss_n64(acc, desc_a(as + 32 * k), desc_b(bs + 2048 * k), 1);
                wgmma_commit();
                if (m == 0) { wgmma_wait<0>(); if (lane0) mbar_arrive(sb + B_EMPTY + 8 * r.slot); }
                r.next();
            }
            float base[32];
            if (!dry) mbar_wait(sb + B_HSUM, 0);
#pragma unroll
            for (int n = 0; n < 4; n++) {
                const uint4 u0 = lds128(sb + HSUM_OFF + (warp * 8 + 2 * n) * 512 + lane * 16), u1 = lds128(sb + HSUM_OFF + (warp * 8 + 2 * n + 1) * 512 + lane * 16);
                float* a = &base[8 * n];
                a[0] = __uint_as_float(u0.x); a[1] = __uint_as_float(u0.y); a[2] = __uint_as_float(u0.z); a[3] = __uint_as_float(u0.w);
                a[4] = __uint_as_float(u1.x); a[5] = __uint_as_float(u1.y); a[6] = __uint_as_float(u1.z); a[7] = __uint_as_float(u1.w);
#pragma unroll
                for (int s = 0; s < 4; s++) {
                    a[0] += bf_lo(pv[n][s].x); a[1] += bf_hi(pv[n][s].x); a[2] += bf_lo(pv[n][s].y); a[3] += bf_hi(pv[n][s].y);
                    a[4] += bf_lo(pv[n][s].z); a[5] += bf_hi(pv[n][s].z); a[6] += bf_lo(pv[n][s].w); a[7] += bf_hi(pv[n][s].w);
                }
            }
            fence_acc(base);
            wgmma_wait<0>();
            fence_acc(acc);
            TS(17);
#pragma unroll
            for (int k = 0; k < 32; k++) acc[k] += base[k];
            __nv_bfloat16* o = out + (size_t)(ti * 128 + warp * 16 + g) * 512 + tj * 64 + ((lane & 1) ? 8 : 0) + (lane & 2) * 2;
            const bool odd = lane & 1;
#pragma unroll
            for (int t2 = 0; t2 < 4; t2++) {
                const uint32_t lo0 = pack_bf16(acc[8 * t2 + 0], acc[8 * t2 + 1]), hi0 = pack_bf16(acc[8 * t2 + 2], acc[8 * t2 + 3]);
                const uint32_t lo1 = pack_bf16(acc[8 * t2 + 4], acc[8 * t2 + 5]), hi1 = pack_bf16(acc[8 * t2 + 6], acc[8 * t2 + 7]);
                const uint32_t sl = __shfl_xor_sync(0xffffffffu, odd ? lo0 : lo1, 1), sh = __shfl_xor_sync(0xffffffffu, odd ? hi0 : hi1, 1);
                if (!dry) *reinterpret_cast<uint2*>(o + 16 * t2) = odd ? make_uint2(sl, lo1) : make_uint2(lo0, sl);
                if (!dry) *reinterpret_cast<uint2*>(o + 16 * t2 + 8 * 512) = odd ? make_uint2(sh, hi1) : make_uint2(hi0, sh);
            }
            if (tid == 0 && !dry) TSG(30);
        }
        TS(8);
    }
}

typedef CUresult (*PFN_encodeTiled)(CUtensorMap*, CUtensorMapDataType, cuuint32_t, void*, const cuuint64_t*, const cuuint64_t*,
                                    const cuuint32_t*, const cuuint32_t*, CUtensorMapInterleave, CUtensorMapSwizzle,
                                    CUtensorMapL2promotion, CUtensorMapFloatOOBfill);

void make_map(PFN_encodeTiled enc, CUtensorMap* m, const void* base, int rank, const cuuint64_t* dims, const cuuint64_t* strides, const cuuint32_t* box) {
    cuuint32_t es[5] = {1, 1, 1, 1, 1};
    enc(m, CU_TENSOR_MAP_DATA_TYPE_BFLOAT16, (cuuint32_t)rank, const_cast<void*>(base), dims, strides, box, es,
        CU_TENSOR_MAP_INTERLEAVE_NONE, CU_TENSOR_MAP_SWIZZLE_128B, CU_TENSOR_MAP_L2_PROMOTION_L2_256B, CU_TENSOR_MAP_FLOAT_OOB_FILL_NONE);
}

}

extern "C" void kernel_launch(void* const* d_in, const int* in_sizes, int n_in, void* d_out, int out_size) {
    (void)in_sizes; (void)n_in; (void)out_size;
    const void* x = d_in[0]; const void* wqkv = d_in[1]; const void* wo = d_in[2];
    const void* w1 = d_in[4]; const void* w2 = d_in[5]; const void* gate_w = d_in[6];
    static PFN_encodeTiled enc = nullptr;
    static int ncta = 128;
    if (!enc) {
        int dev = 0, sms = 0;
        cudaGetDevice(&dev);
        cudaDeviceGetAttribute(&sms, cudaDevAttrMultiProcessorCount, dev);
        ncta = sms > 132 ? 132 : (sms > 128 ? sms : 128);
        void* fn = nullptr; cudaDriverEntryPointQueryResult st;
        cudaGetDriverEntryPoint("cuTensorMapEncodeTiled", &fn, cudaEnableDefault, &st);
        enc = (PFN_encodeTiled)fn;
        cudaFuncSetAttribute(fused_kernel, cudaFuncAttributeMaxDynamicSharedMemorySize, SMEM_BYTES);
    }
    CUtensorMap mx, mqkv, mw1, mw2, mwo, mw1a, mo;
    void* optr = nullptr;
    cudaGetSymbolAddress(&optr, g_o);
    { cuuint64_t d[2] = {512, 2048}, s[1] = {1024}; cuuint32_t b[2] = {64, 128}; make_map(enc, &mo, optr, 2, d, s, b); }
    { cuuint64_t d[4] = {64, 512, 3, 8}, s[3] = {3584, 128, 448}; cuuint32_t b[4] = {64, 32, 3, 1}; make_map(enc, &mw1a, w1, 4, d, s, b); }
    { cuuint64_t d[2] = {512, 2048}, s[1] = {1024}; cuuint32_t b[2] = {64, 128}; make_map(enc, &mx, x, 2, d, s, b); }
    { cuuint64_t d[4] = {64, 512, 8, 3}, s[3] = {3072, 128, 1024}; cuuint32_t b[4] = {64, 32, 1, 3}; make_map(enc, &mqkv, wqkv, 4, d, s, b); }
    { cuuint64_t d[2] = {1792, 512}, s[1] = {3584}; cuuint32_t b[2] = {64, 32}; make_map(enc, &mw1, w1, 2, d, s, b); }
    { cuuint64_t d[3] = {64, 1792, 8}, s[2] = {1024, 128}; cuuint32_t b[3] = {64, 32, 2}; make_map(enc, &mw2, w2, 3, d, s, b); }
    { cuuint64_t d[2] = {512, 512}, s[1] = {1024}; cuuint32_t b[2] = {64, 256}; make_map(enc, &mwo, wo, 2, d, s, b); }
    fused_kernel<<<ncta, 384, SMEM_BYTES, cudaStreamPerThread>>>(mx, mqkv, mw1, mw2, mwo, mw1a, mo, (const __nv_bfloat16*)gate_w, (__nv_bfloat16*)d_out,
                                           (const uint8_t*)w1, (const uint8_t*)w2, (const uint8_t*)wo);
}
```

```cpp
#include <cuda_runtime.h>
#include <cuda_bf16.h>
#include <cuda.h>
#include <stdint.h>

namespace {

#define PF1_AT 1
#define PF2_AT 5
#define LEAD1 0
constexpr int RING = 6;
constexpr int SLOT = 16384;
constexpr uint32_t X_OFF = 0;
constexpr uint32_t STG_OFF = X_OFF + 4 * 16384;
constexpr uint32_t RING_OFF = 131072;
constexpr uint32_t BAR_OFF = RING_OFF + RING * SLOT;
constexpr uint32_t B_FULL = BAR_OFF, B_EMPTY = BAR_OFF + 64, B_XFULL = BAR_OFF + 128, B_HDEAD = BAR_OFF + 192,
                   B_EREADY = BAR_OFF + 200, B_KVDONE = BAR_OFF + 208, B_ODONE = BAR_OFF + 224,
                   B_KVREADY = BAR_OFF + 232, B_WOFULL = BAR_OFF + 240, B_HSUM = BAR_OFF + 248, B_PREADY = BAR_OFF + 264,
                   B_SQ = BAR_OFF + 272, B_SF = BAR_OFF + 304, B_XDEAD = BAR_OFF + 320;
constexpr uint32_t EPOCH_OFF = BAR_OFF + 256, ITEM_OFF = BAR_OFF + 260;
constexpr uint32_t OWN_OFF = X_OFF + 4 * 16384;
constexpr uint32_t HSUM_OFF = X_OFF + 6 * 16384;
constexpr uint32_t SMEM_BYTES = BAR_OFF + 1024;

constexpr int N_QKV = 16, N_FFN1 = 16, N_FFN2 = 14, N_KV = 8, N_O = 7;

__device__ uint4 g_kf[32 * 128 * 32];
__device__ uint4 g_vf[32 * 128 * 32];
__device__ uint4 g_part[16 * 8 * 8 * 8 * 4 * 32];
__device__ __nv_bfloat16 g_o[2048 * 512];
__device__ unsigned g_ticket;
__device__ unsigned g_kvcnt[128 * 32];
__device__ unsigned g_pcnt[128 * 32];
__device__ unsigned g_ocnt[128 * 32];
#define TS(k) do {} while (0)
#define TS2(k) do {} while (0)
#define TS2X(k) do {} while (0)
#define TSX(k) do {} while (0)
#define TSG(k) do {} while (0)

__device__ __forceinline__ uint32_t smem_u32(const void* p) { return (uint32_t)__cvta_generic_to_shared(p); }
__device__ __forceinline__ void mbar_init(uint32_t bar, uint32_t cnt) { asm volatile("mbarrier.init.shared::cta.b64 [%0], %1;" :: "r"(bar), "r"(cnt) : "memory"); }
__device__ __forceinline__ void mbar_expect_tx(uint32_t bar, uint32_t bytes) { asm volatile("mbarrier.arrive.expect_tx.shared::cta.b64 _, [%0], %1;" :: "r"(bar), "r"(bytes) : "memory"); }
__device__ __forceinline__ void mbar_expect_only(uint32_t bar, uint32_t bytes) { asm volatile("mbarrier.expect_tx.relaxed.cta.shared::cta.b64 [%0], %1;" :: "r"(bar), "r"(bytes) : "memory"); }
__device__ __forceinline__ void mbar_arrive(uint32_t bar) { asm volatile("mbarrier.arrive.shared::cta.b64 _, [%0];" :: "r"(bar) : "memory"); }
__device__ __forceinline__ void mbar_wait(uint32_t bar, uint32_t parity) {
    asm volatile("{\n.reg .pred P1, P2;\n.reg .u32 n;\nmov.u32 n, 0;\n"
                 "WAIT_LOOP:\n"
                 "mbarrier.try_wait.parity.shared::cta.b64 P1, [%0], %1;\n"
                 "@P1 bra WAIT_DONE;\n"
                 "add.u32 n, n, 1;\n"
                 "setp.lt.u32 P2, n, 0x400000;\n"
                 "@P2 bra WAIT_LOOP;\n"
                 "WAIT_DONE:\n}" :: "r"(bar), "r"(parity) : "memory");
}
__device__ __forceinline__ void mbar_wait_idle(uint32_t bar, uint32_t parity) {
    asm volatile("{\n.reg .pred P1, P2;\n.reg .u32 n;\nmov.u32 n, 0;\n"
                 "WAIT_LOOP:\n"
                 "mbarrier.try_wait.parity.shared::cta.b64 P1, [%0], %1, 2000;\n"
                 "@P1 bra WAIT_DONE;\n"
                 "add.u32 n, n, 1;\n"
                 "setp.lt.u32 P2, n, 0x100000;\n"
                 "@P2 bra WAIT_LOOP;\n"
                 "WAIT_DONE:\n}" :: "r"(bar), "r"(parity) : "memory");
}
__device__ __forceinline__ void tma_2d(uint32_t dst, const void* map, uint32_t bar, int c0, int c1) {
    asm volatile("cp.async.bulk.tensor.2d.shared::cluster.global.mbarrier::complete_tx::bytes [%0], [%1, {%3, %4}], [%2];"
        :: "r"(dst), "l"(map), "r"(bar), "r"(c0), "r"(c1) : "memory");
}
__device__ __forceinline__ void tma_3d(uint32_t dst, const void* map, uint32_t bar, int c0, int c1, int c2) {
    asm volatile("cp.async.bulk.tensor.3d.shared::cluster.global.mbarrier::complete_tx::bytes [%0], [%1, {%3, %4, %5}], [%2];"
        :: "r"(dst), "l"(map), "r"(bar), "r"(c0), "r"(c1), "r"(c2) : "memory");
}
__device__ __forceinline__ void tma_4d(uint32_t dst, const void* map, uint32_t bar, int c0, int c1, int c2, int c3) {
    asm volatile("cp.async.bulk.tensor.4d.shared::cluster.global.mbarrier::complete_tx::bytes [%0], [%1, {%3, %4, %5, %6}], [%2];"
        :: "r"(dst), "l"(map), "r"(bar), "r"(c0), "r"(c1), "r"(c2), "r"(c3) : "memory");
}
__device__ __forceinline__ void bulk_g2s(uint32_t dst, const void* src, uint32_t bytes, uint32_t bar) {
    asm volatile("cp.async.bulk.shared::cluster.global.mbarrier::complete_tx::bytes [%0], [%1], %2, [%3];"
        :: "r"(dst), "l"(src), "r"(bytes), "r"(bar) : "memory");
}
__device__ __forceinline__ void prefetch_l2(const void* src, uint32_t bytes) {
    asm volatile("cp.async.bulk.prefetch.L2.global [%0], %1;" :: "l"(src), "r"(bytes) : "memory");
}
__device__ __forceinline__ bool elect_one() {
    uint32_t p;
    asm volatile("{\n.reg .pred P;\nelect.sync _|P, 0xffffffff;\nselp.u32 %0, 1, 0, P;\n}" : "=r"(p));
    return p != 0;
}
__device__ __forceinline__ void wgmma_fence() { asm volatile("wgmma.fence.sync.aligned;" ::: "memory"); }
__device__ __forceinline__ void wgmma_commit() { asm volatile("wgmma.commit_group.sync.aligned;" ::: "memory"); }
template <int N> __device__ __forceinline__ void wgmma_wait() { asm volatile("wgmma.wait_group.sync.aligned %0;" :: "n"(N) : "memory"); }
__device__ __forceinline__ void fence_async_smem() { asm volatile("fence.proxy.async.shared::cta;" ::: "memory"); }
__device__ __forceinline__ uint64_t desc_a(uint32_t addr) {
    return (uint64_t)((addr & 0x3FFFF) >> 4) | ((uint64_t)1 << 16) | ((uint64_t)(1024 >> 4) << 32) | ((uint64_t)1 << 62);
}
__device__ __forceinline__ uint64_t desc_b(uint32_t addr) {
    return (uint64_t)((addr & 0x3FFFF) >> 4) | ((uint64_t)(4096 >> 4) << 16) | ((uint64_t)(1024 >> 4) << 32) | ((uint64_t)1 << 62);
}
__device__ __forceinline__ uint32_t pack_bf16(float lo, float hi) {
    uint32_t r; asm("cvt.rn.bf16x2.f32 %0, %1, %2;" : "=r"(r) : "f"(hi), "f"(lo)); return r;
}
__device__ __forceinline__ uint32_t pack_bf16_relu(float lo, float hi) {
    uint32_t r; asm("cvt.rn.relu.bf16x2.f32 %0, %1, %2;" : "=r"(r) : "f"(hi), "f"(lo)); return r;
}
__device__ __forceinline__ uint32_t movmatrix(uint32_t a) {
    uint32_t d; asm volatile("movmatrix.sync.aligned.m8n8.trans.b16 %0, %1;" : "=r"(d) : "r"(a)); return d;
}
__device__ __forceinline__ void stmatrix_x4(uint32_t addr, uint32_t r0, uint32_t r1, uint32_t r2, uint32_t r3) {
    asm volatile("stmatrix.sync.aligned.m8n8.x4.shared.b16 [%0], {%1, %2, %3, %4};" :: "r"(addr), "r"(r0), "r"(r1), "r"(r2), "r"(r3) : "memory");
}
__device__ __forceinline__ uint4 lds128(uint32_t addr) {
    uint4 v; asm volatile("ld.shared.v4.b32 {%0, %1, %2, %3}, [%4];" : "=r"(v.x), "=r"(v.y), "=r"(v.z), "=r"(v.w) : "r"(addr) : "memory"); return v;
}
__device__ __forceinline__ uint4 lds128_free(uint32_t addr) {
    uint4 v; asm("ld.shared.v4.b32 {%0, %1, %2, %3}, [%4];" : "=r"(v.x), "=r"(v.y), "=r"(v.z), "=r"(v.w) : "r"(addr)); return v;
}
__device__ __forceinline__ void mma16816(float (&c)[4], uint32_t a0, uint32_t a1, uint32_t a2, uint32_t a3, uint32_t b0, uint32_t b1) {
    asm("mma.sync.aligned.m16n8k16.row.col.f32.bf16.bf16.f32 {%0,%1,%2,%3}, {%4,%5,%6,%7}, {%8,%9}, {%0,%1,%2,%3};"
        : "+f"(c[0]), "+f"(c[1]), "+f"(c[2]), "+f"(c[3]) : "r"(a0), "r"(a1), "r"(a2), "r"(a3), "r"(b0), "r"(b1));
}
__device__ __forceinline__ void mma16816_c(float (&c)[4], uint32_t a0, uint32_t a1, uint32_t a2, uint32_t a3, uint32_t b0, uint32_t b1, float ci) {
    asm("mma.sync.aligned.m16n8k16.row.col.f32.bf16.bf16.f32 {%0,%1,%2,%3}, {%4,%5,%6,%7}, {%8,%9}, {%10,%10,%10,%10};"
        : "=f"(c[0]), "=f"(c[1]), "=f"(c[2]), "=f"(c[3]) : "r"(a0), "r"(a1), "r"(a2), "r"(a3), "r"(b0), "r"(b1), "f"(ci));
}
__device__ __forceinline__ int opaque(int v) { asm volatile("" : "+r"(v)); return v; }
__device__ __forceinline__ float ex2(float x) { float y; asm("ex2.approx.ftz.f32 %0, %1;" : "=f"(y) : "f"(x)); return y; }
__device__ __forceinline__ unsigned ld_acquire(const unsigned* p) {
    unsigned v; asm volatile("ld.acquire.gpu.global.u32 %0, [%1];" : "=r"(v) : "l"(p) : "memory"); return v;
}
__device__ __forceinline__ void red_release(unsigned* p, unsigned v) {
    asm volatile("red.release.gpu.global.add.u32 [%0], %1;" :: "l"(p), "r"(v) : "memory");
}
__device__ __forceinline__ void wait_counter(const unsigned* p, unsigned target) {
    uint32_t n = 0;
    while ((int)(ld_acquire(p) - target) < 0) { if (++n > (1u << 20)) break; }
}
__device__ __forceinline__ uint4 ldg_weak(const uint4* p) {
    uint4 v; asm volatile("ld.global.L1::no_allocate.v4.b32 {%0, %1, %2, %3}, [%4];" : "=r"(v.x), "=r"(v.y), "=r"(v.z), "=r"(v.w) : "l"(p) : "memory"); return v;
}
__device__ __forceinline__ float bf_lo(uint32_t v) { return __uint_as_float(v << 16); }
__device__ __forceinline__ float bf_hi(uint32_t v) { return __uint_as_float(v & 0xFFFF0000u); }

__device__ __forceinline__ void wgmma_ss_n64(float (&d)[32], uint64_t da, uint64_t db, int scale_d) {
    asm volatile("{\n.reg .pred p;\nsetp.ne.b32 p, %34, 0;\n"
        "wgmma.mma_async.sync.aligned.m64n64k16.f32.bf16.bf16 {%0, %1, %2, %3, %4, %5, %6, %7, %8, %9, %10, %11, %12, %13, %14, %15, %16, %17, %18, %19, %20, %21, %22, %23, %24, %25, %26, %27, %28, %29, %30, %31}, %32, %33, p, 1, 1, 0, 1;\n}\n"
        : "+f"(d[0]), "+f"(d[1]), "+f"(d[2]), "+f"(d[3]), "+f"(d[4]), "+f"(d[5]), "+f"(d[6]), "+f"(d[7]), "+f"(d[8]), "+f"(d[9]), "+f"(d[10]), "+f"(d[11]), "+f"(d[12]), "+f"(d[13]), "+f"(d[14]), "+f"(d[15]), "+f"(d[16]), "+f"(d[17]), "+f"(d[18]), "+f"(d[19]), "+f"(d[20]), "+f"(d[21]), "+f"(d[22]), "+f"(d[23]), "+f"(d[24]), "+f"(d[25]), "+f"(d[26]), "+f"(d[27]), "+f"(d[28]), "+f"(d[29]), "+f"(d[30]), "+f"(d[31])
        : "l"(da), "l"(db), "r"(scale_d));
}
__device__ __forceinline__ void wgmma_ss_n128(float (&d)[64], uint64_t da, uint64_t db, int scale_d) {
    asm volatile("{\n.reg .pred p;\nsetp.ne.b32 p, %66, 0;\n"
        "wgmma.mma_async.sync.aligned.m64n128k16.f32.bf16.bf16 {%0, %1, %2, %3, %4, %5, %6, %7, %8, %9, %10, %11, %12, %13, %14, %15, %16, %17, %18, %19, %20, %21, %22, %23, %24, %25, %26, %27, %28, %29, %30, %31, %32, %33, %34, %35, %36, %37, %38, %39, %40, %41, %42, %43, %44, %45, %46, %47, %48, %49, %50, %51, %52, %53, %54, %55, %56, %57, %58, %59, %60, %61, %62, %63}, %64, %65, p, 1, 1, 0, 1;\n}\n"
        : "+f"(d[0]), "+f"(d[1]), "+f"(d[2]), "+f"(d[3]), "+f"(d[4]), "+f"(d[5]), "+f"(d[6]), "+f"(d[7]), "+f"(d[8]), "+f"(d[9]), "+f"(d[10]), "+f"(d[11]), "+f"(d[12]), "+f"(d[13]), "+f"(d[14]), "+f"(d[15]), "+f"(d[16]), "+f"(d[17]), "+f"(d[18]), "+f"(d[19]), "+f"(d[20]), "+f"(d[21]), "+f"(d[22]), "+f"(d[23]), "+f"(d[24]), "+f"(d[25]), "+f"(d[26]), "+f"(d[27]), "+f"(d[28]), "+f"(d[29]), "+f"(d[30]), "+f"(d[31]), "+f"(d[32]), "+f"(d[33]), "+f"(d[34]), "+f"(d[35]), "+f"(d[36]), "+f"(d[37]), "+f"(d[38]), "+f"(d[39]), "+f"(d[40]), "+f"(d[41]), "+f"(d[42]), "+f"(d[43]), "+f"(d[44]), "+f"(d[45]), "+f"(d[46]), "+f"(d[47]), "+f"(d[48]), "+f"(d[49]), "+f"(d[50]), "+f"(d[51]), "+f"(d[52]), "+f"(d[53]), "+f"(d[54]), "+f"(d[55]), "+f"(d[56]), "+f"(d[57]), "+f"(d[58]), "+f"(d[59]), "+f"(d[60]), "+f"(d[61]), "+f"(d[62]), "+f"(d[63])
        : "l"(da), "l"(db), "r"(scale_d));
}
__device__ __forceinline__ void wgmma_ss_n200(float (&d)[100], uint64_t da, uint64_t db, int scale_d) {
    asm volatile("{\n.reg .pred p;\nsetp.ne.b32 p, %102, 0;\n"
        "wgmma.mma_async.sync.aligned.m64n200k16.f32.bf16.bf16 {%0, %1, %2, %3, %4, %5, %6, %7, %8, %9, %10, %11, %12, %13, %14, %15, %16, %17, %18, %19, %20, %21, %22, %23, %24, %25, %26, %27, %28, %29, %30, %31, %32, %33, %34, %35, %36, %37, %38, %39, %40, %41, %42, %43, %44, %45, %46, %47, %48, %49, %50, %51, %52, %53, %54, %55, %56, %57, %58, %59, %60, %61, %62, %63, %64, %65, %66, %67, %68, %69, %70, %71, %72, %73, %74, %75, %76, %77, %78, %79, %80, %81, %82, %83, %84, %85, %86, %87, %88, %89, %90, %91, %92, %93, %94, %95, %96, %97, %98, %99}, %100, %101, p, 1, 1, 0, 1;\n}\n"
        : "+f"(d[0]), "+f"(d[1]), "+f"(d[2]), "+f"(d[3]), "+f"(d[4]), "+f"(d[5]), "+f"(d[6]), "+f"(d[7]), "+f"(d[8]), "+f"(d[9]), "+f"(d[10]), "+f"(d[11]), "+f"(d[12]), "+f"(d[13]), "+f"(d[14]), "+f"(d[15]), "+f"(d[16]), "+f"(d[17]), "+f"(d[18]), "+f"(d[19]), "+f"(d[20]), "+f"(d[21]), "+f"(d[22]), "+f"(d[23]), "+f"(d[24]), "+f"(d[25]), "+f"(d[26]), "+f"(d[27]), "+f"(d[28]), "+f"(d[29]), "+f"(d[30]), "+f"(d[31]), "+f"(d[32]), "+f"(d[33]), "+f"(d[34]), "+f"(d[35]), "+f"(d[36]), "+f"(d[37]), "+f"(d[38]), "+f"(d[39]), "+f"(d[40]), "+f"(d[41]), "+f"(d[42]), "+f"(d[43]), "+f"(d[44]), "+f"(d[45]), "+f"(d[46]), "+f"(d[47]), "+f"(d[48]), "+f"(d[49]), "+f"(d[50]), "+f"(d[51]), "+f"(d[52]), "+f"(d[53]), "+f"(d[54]), "+f"(d[55]), "+f"(d[56]), "+f"(d[57]), "+f"(d[58]), "+f"(d[59]), "+f"(d[60]), "+f"(d[61]), "+f"(d[62]), "+f"(d[63]), "+f"(d[64]), "+f"(d[65]), "+f"(d[66]), "+f"(d[67]), "+f"(d[68]), "+f"(d[69]), "+f"(d[70]), "+f"(d[71]), "+f"(d[72]), "+f"(d[73]), "+f"(d[74]), "+f"(d[75]), "+f"(d[76]), "+f"(d[77]), "+f"(d[78]), "+f"(d[79]), "+f"(d[80]), "+f"(d[81]), "+f"(d[82]), "+f"(d[83]), "+f"(d[84]), "+f"(d[85]), "+f"(d[86]), "+f"(d[87]), "+f"(d[88]), "+f"(d[89]), "+f"(d[90]), "+f"(d[91]), "+f"(d[92]), "+f"(d[93]), "+f"(d[94]), "+f"(d[95]), "+f"(d[96]), "+f"(d[97]), "+f"(d[98]), "+f"(d[99])
        : "l"(da), "l"(db), "r"(scale_d));
}
__device__ __forceinline__ void wgmma_ss_n224(float (&d)[112], uint64_t da, uint64_t db, int scale_d) {
    asm volatile("{\n.reg .pred p;\nsetp.ne.b32 p, %114, 0;\n"
        "wgmma.mma_async.sync.aligned.m64n224k16.f32.bf16.bf16 {%0, %1, %2, %3, %4, %5, %6, %7, %8, %9, %10, %11, %12, %13, %14, %15, %16, %17, %18, %19, %20, %21, %22, %23, %24, %25, %26, %27, %28, %29, %30, %31, %32, %33, %34, %35, %36, %37, %38, %39, %40, %41, %42, %43, %44, %45, %46, %47, %48, %49, %50, %51, %52, %53, %54, %55, %56, %57, %58, %59, %60, %61, %62, %63, %64, %65, %66, %67, %68, %69, %70, %71, %72, %73, %74, %75, %76, %77, %78, %79, %80, %81, %82, %83, %84, %85, %86, %87, %88, %89, %90, %91, %92, %93, %94, %95, %96, %97, %98, %99, %100, %101, %102, %103, %104, %105, %106, %107, %108, %109, %110, %111}, %112, %113, p, 1, 1, 0, 1;\n}\n"
        : "+f"(d[0]), "+f"(d[1]), "+f"(d[2]), "+f"(d[3]), "+f"(d[4]), "+f"(d[5]), "+f"(d[6]), "+f"(d[7]), "+f"(d[8]), "+f"(d[9]), "+f"(d[10]), "+f"(d[11]), "+f"(d[12]), "+f"(d[13]), "+f"(d[14]), "+f"(d[15]), "+f"(d[16]), "+f"(d[17]), "+f"(d[18]), "+f"(d[19]), "+f"(d[20]), "+f"(d[21]), "+f"(d[22]), "+f"(d[23]), "+f"(d[24]), "+f"(d[25]), "+f"(d[26]), "+f"(d[27]), "+f"(d[28]), "+f"(d[29]), "+f"(d[30]), "+f"(d[31]), "+f"(d[32]), "+f"(d[33]), "+f"(d[34]), "+f"(d[35]), "+f"(d[36]), "+f"(d[37]), "+f"(d[38]), "+f"(d[39]), "+f"(d[40]), "+f"(d[41]), "+f"(d[42]), "+f"(d[43]), "+f"(d[44]), "+f"(d[45]), "+f"(d[46]), "+f"(d[47]), "+f"(d[48]), "+f"(d[49]), "+f"(d[50]), "+f"(d[51]), "+f"(d[52]), "+f"(d[53]), "+f"(d[54]), "+f"(d[55]), "+f"(d[56]), "+f"(d[57]), "+f"(d[58]), "+f"(d[59]), "+f"(d[60]), "+f"(d[61]), "+f"(d[62]), "+f"(d[63]), "+f"(d[64]), "+f"(d[65]), "+f"(d[66]), "+f"(d[67]), "+f"(d[68]), "+f"(d[69]), "+f"(d[70]), "+f"(d[71]), "+f"(d[72]), "+f"(d[73]), "+f"(d[74]), "+f"(d[75]), "+f"(d[76]), "+f"(d[77]), "+f"(d[78]), "+f"(d[79]), "+f"(d[80]), "+f"(d[81]), "+f"(d[82]), "+f"(d[83]), "+f"(d[84]), "+f"(d[85]), "+f"(d[86]), "+f"(d[87]), "+f"(d[88]), "+f"(d[89]), "+f"(d[90]), "+f"(d[91]), "+f"(d[92]), "+f"(d[93]), "+f"(d[94]), "+f"(d[95]), "+f"(d[96]), "+f"(d[97]), "+f"(d[98]), "+f"(d[99]), "+f"(d[100]), "+f"(d[101]), "+f"(d[102]), "+f"(d[103]), "+f"(d[104]), "+f"(d[105]), "+f"(d[106]), "+f"(d[107]), "+f"(d[108]), "+f"(d[109]), "+f"(d[110]), "+f"(d[111])
        : "l"(da), "l"(db), "r"(scale_d));
}
template <int N> __device__ __forceinline__ void fence_acc(float (&d)[N]) {
#pragma unroll
    for (int i = 0; i < N; i++) asm volatile("" : "+f"(d[i]) :: "memory");
}

__device__ __forceinline__ void bulk_s2g(void* dst, uint32_t src, uint32_t bytes) {
    asm volatile("cp.async.bulk.global.shared::cta.bulk_group [%0], [%1], %2;" :: "l"(dst), "r"(src), "r"(bytes) : "memory");
}
__device__ __forceinline__ void sts128(uint32_t addr, uint4 v) {
    asm volatile("st.shared.v4.b32 [%0], {%1, %2, %3, %4};" :: "r"(addr), "r"(v.x), "r"(v.y), "r"(v.z), "r"(v.w) : "memory");
}
__device__ __forceinline__ void sum_partials(uint32_t sb, int ti, int tj, int lane) {
    for (;;) {
        uint32_t item = 0;
        if (lane == 0) asm volatile("atom.shared.add.u32 %0, [%1], 1;" : "=r"(item) : "r"(sb + ITEM_OFF) : "memory");
        item = __shfl_sync(0xffffffffu, item, 0);
        if (item >= 8) break;
        const uint4* p = g_part + (size_t)((ti * 8 + tj) * 8) * 1024 + item * 128 + lane;
        uint4 v[4][4];
#pragma unroll
        for (int s = 0; s < 4; s++)
#pragma unroll
            for (int n = 0; n < 4; n++) v[n][s] = ldg_weak(p + s * 1024 + n * 32);
#pragma unroll
        for (int n = 0; n < 4; n++) {
            float a[8];
#pragma unroll
            for (int e = 0; e < 8; e++) a[e] = 0.f;
#pragma unroll
            for (int s = 0; s < 4; s++) {
                a[0] += bf_lo(v[n][s].x); a[1] += bf_hi(v[n][s].x); a[2] += bf_lo(v[n][s].y); a[3] += bf_hi(v[n][s].y);
                a[4] += bf_lo(v[n][s].z); a[5] += bf_hi(v[n][s].z); a[6] += bf_lo(v[n][s].w); a[7] += bf_hi(v[n][s].w);
            }
            const uint32_t d = sb + HSUM_OFF + (item * 8 + n * 2) * 512 + lane * 16;
            sts128(d, make_uint4(__float_as_uint(a[0]), __float_as_uint(a[1]), __float_as_uint(a[2]), __float_as_uint(a[3])));
            sts128(d + 512, make_uint4(__float_as_uint(a[4]), __float_as_uint(a[5]), __float_as_uint(a[6]), __float_as_uint(a[7])));
        }
    }
    __syncwarp();
    if (lane == 0) mbar_arrive(sb + B_HSUM);
}

#define PWAIT() mbar_wait_idle(sb + B_EMPTY + 8 * r.slot, r.phase)
#define CWAIT() do { if (!dry) mbar_wait(sb + B_FULL + 8 * r.slot, r.phase); } while (0)
template <bool B> struct BoolTag { static constexpr bool value = B; };
struct Ring {
    int slot; uint32_t phase;
    __device__ __forceinline__ void next() { if (++slot == RING) { slot = 0; phase ^= 1; } }
};

__global__ void __launch_bounds__(384, 1)
fused_kernel(const __grid_constant__ CUtensorMap map_x, const __grid_constant__ CUtensorMap map_qkv,
             const __grid_constant__ CUtensorMap map_w1, const __grid_constant__ CUtensorMap map_w2,
             const __grid_constant__ CUtensorMap map_wo, const __grid_constant__ CUtensorMap map_w1a,
             const __grid_constant__ CUtensorMap map_o,
             const __nv_bfloat16* __restrict__ gate_w, __nv_bfloat16* __restrict__ out,
             const uint8_t* __restrict__ w1p, const uint8_t* __restrict__ w2p, const uint8_t* __restrict__ wop)
{
    extern __shared__ __align__(1024) uint8_t smem_raw[];
    const uint32_t sb = smem_u32(smem_raw);
    const int tid = threadIdx.x, warp = tid >> 5, lane = tid & 31;
    const bool dry = blockIdx.x >= 128;
    const int ti = dry ? (int)(blockIdx.x & 1) * 2 : blockIdx.x >> 3, tj = blockIdx.x & 7;
    if (dry && warp >= 8) {
        asm volatile("setmaxnreg.dec.sync.aligned.u32 88;");
        return;
    }

    if (tid == 0 && !dry) { TSG(31); TSX(0); }
    uint32_t gwv[N_QKV / 2];
    if (warp == 8) {
        const unsigned short* gws = reinterpret_cast<const unsigned short*>(gate_w);
#pragma unroll
        for (int n = 0; n < N_QKV / 2; n++) gwv[n] = (uint32_t)__ldg(gws + 64 * n + lane) | ((uint32_t)__ldg(gws + 64 * n + 32 + lane) << 16);
    }
    if (tid == 321) {
        asm volatile("prefetch.tensormap [%0];" :: "l"(&map_x) : "memory");
        asm volatile("prefetch.tensormap [%0];" :: "l"(&map_qkv) : "memory");
        asm volatile("prefetch.tensormap [%0];" :: "l"(&map_w1) : "memory");
        asm volatile("prefetch.tensormap [%0];" :: "l"(&map_w1a) : "memory");
        asm volatile("prefetch.tensormap [%0];" :: "l"(&map_w2) : "memory");
        asm volatile("prefetch.tensormap [%0];" :: "l"(&map_wo) : "memory");
        asm volatile("prefetch.tensormap [%0];" :: "l"(&map_o) : "memory");
    }
    if (tid == 288) {
        mbar_init(sb + B_FULL, 1); mbar_init(sb + B_XFULL, 1);
        fence_async_smem();
        mbar_expect_tx(sb + B_XFULL, 16384);
        tma_2d(sb + X_OFF, &map_x, sb + B_XFULL, 0, ti * 128);
        mbar_expect_only(sb + B_FULL, 12288);
        tma_4d(sb + RING_OFF, &map_qkv, sb + B_FULL, 0, 0, tj, 0);
    }
    if (tid == 320) {
        for (int s = 1; s < RING; s++) mbar_init(sb + B_FULL + 8 * s, 1);
        for (int s = 0; s < RING; s++) mbar_init(sb + B_EMPTY + 8 * s, 8);
        for (int s = 1; s < 8; s++) mbar_init(sb + B_XFULL + 8 * s, 1);
        fence_async_smem();
    }
    if (tid == 352) {
        mbar_init(sb + B_HDEAD, 8); mbar_init(sb + B_EREADY, 1); mbar_init(sb + B_KVDONE, 8); mbar_init(sb + B_KVREADY, 1);
        mbar_init(sb + B_ODONE, 8); mbar_init(sb + B_WOFULL, 1); mbar_init(sb + B_HSUM, 3);
        mbar_init(sb + B_XDEAD, 8); mbar_init(sb + B_PREADY, 1); mbar_init(sb + B_SF, 1); mbar_init(sb + B_SF + 8, 1);
        for (int s = 0; s < 4; s++) mbar_init(sb + B_SQ + 8 * s, 8);
        asm volatile("st.shared.u32 [%0], %1;" :: "r"(sb + ITEM_OFF), "r"(0) : "memory");
        fence_async_smem();
    }
    if (!dry) __syncthreads();

    if (warp >= 8) {
        asm volatile("setmaxnreg.dec.sync.aligned.u32 88;");
        if (warp == 8) {
            Ring r{0, 1};
            const bool leader = elect_one();
            if (leader) {
#pragma unroll
                for (int n = 1; n < RING; n++) {
                    if (!(n & 1)) {
                        mbar_expect_tx(sb + B_XFULL + 8 * (n >> 1), 16384);
                        tma_2d(sb + X_OFF + (n >> 1) * 16384, &map_x, sb + B_XFULL + 8 * (n >> 1), (n >> 1) * 64, ti * 128);
                    }
                    mbar_expect_only(sb + B_FULL + 8 * n, 12288);
                    tma_4d(sb + RING_OFF + n * SLOT, &map_qkv, sb + B_FULL + 8 * n, 0, 32 * n, tj, 0);
                }
            }
#pragma unroll
            for (int n = 0; n < N_QKV; n++) {
                const uint32_t full = sb + B_FULL + 8 * r.slot, dst = sb + RING_OFF + r.slot * SLOT;
                if (n >= RING) {
                    if (!(n & 1) && leader) {
                        mbar_expect_tx(sb + B_XFULL + 8 * (n >> 1), 16384);
                        tma_2d(sb + X_OFF + (n >> 1) * 16384, &map_x, sb + B_XFULL + 8 * (n >> 1), (n >> 1) * 64, ti * 128);
                    }
                    PWAIT();
                    if (leader) {
                        mbar_expect_only(full, 12288);
                        tma_4d(dst, &map_qkv, full, 0, 32 * n, tj, 0);
                    }
                }
                const uint32_t gv = (n & 1) ? (gwv[n >> 1] >> 16) : (gwv[n >> 1] & 0xFFFFu);
                asm volatile("st.shared.v4.b32 [%0], {%1, %2, %2, %2};" :: "r"(dst + 12288 + lane * 128 + ((lane & 7) << 4)), "r"(gv), "r"(0) : "memory");
                fence_async_smem();
                __syncwarp();
                if (leader) mbar_arrive(full);
                r.next();
            }
#pragma unroll 1
            for (int n = 0; n < N_FFN1; n++) {
                const uint32_t full = sb + B_FULL + 8 * r.slot, dst = sb + RING_OFF + r.slot * SLOT;
                PWAIT();
                if (leader) {
                    mbar_expect_tx(full, 16384);
                    tma_4d(dst, &map_w1a, full, 0, 32 * n, 0, tj);
                    tma_2d(dst + 3 * 4096, &map_w1, full, 224 * tj + 192, 32 * n);
                }
                r.next();
            }
            {
                int q = 0, rr = 0;
#pragma unroll 1
                for (int n = 0; n < N_FFN2; n++) {
                    const uint32_t full = sb + B_FULL + 8 * r.slot, dst = sb + RING_OFF + r.slot * SLOT;
                    PWAIT();
                    if (leader) mbar_expect_tx(full, 16384);
#pragma unroll
                    for (int h = 0; h < 2; h++) {
                        if (leader) tma_3d(dst + h * 8192, &map_w2, full, 0, 224 * tj + 32 * rr, 2 * q);
                        if (++rr == 7) { rr = 0; q++; }
                    }
                    r.next();
                }
            }
            mbar_wait_idle(sb + B_KVREADY, 0);
            asm volatile("fence.proxy.async.global;" ::: "memory");
            {
                const int bbase = 8 * ti - 16, b0 = bbase < 0 ? 0 : bbase;
                const uint32_t bytes = (uint32_t)(8 * ti + 8 - b0) * 512;
#pragma unroll 1
                for (int m = 0; m < N_KV; m++) {
                    const uint32_t full = sb + B_FULL + 8 * r.slot, dst = sb + RING_OFF + r.slot * SLOT;
                    if (m == RING) {
                        mbar_wait_idle(sb + B_HDEAD, 0);
                        if (leader) {
                            mbar_expect_tx(sb + B_WOFULL, 65536);
#pragma unroll
                            for (int e = 0; e < 2; e++) tma_2d(sb + X_OFF + e * 32768, &map_wo, sb + B_WOFULL, 64 * tj, 256 * e);
                        }
                    }
                    PWAIT();
                    if (leader) {
                        const uint4* src = ((m & 1) ? g_vf : g_kf) + ((tj * 4 + (m >> 1)) * 128 + b0) * 32;
                        mbar_expect_tx(full, bytes);
                        bulk_g2s(dst + (b0 - bbase) * 512, src, bytes, full);
                    }
                    r.next();
                }
            }
            {
                mbar_wait_idle(sb + B_EREADY, 0);
                unsigned epoch; asm volatile("ld.shared.u32 %0, [%1];" : "=r"(epoch) : "r"(sb + EPOCH_OFF) : "memory");
                uint32_t ready = 0;
                mbar_wait_idle(sb + B_HSUM, 0);
#pragma unroll 1
                for (int m = 0; m < N_O; m++) {
                    const uint32_t full = sb + B_FULL + 8 * r.slot, dst = sb + RING_OFF + r.slot * SLOT;
                    PWAIT();
                    const int js = (tj + 1 + m) & 7;
                    for (int it = 0; it < (1 << 20) && !((ready >> js) & 1); it++) {
                        bool ok = false;
                        if (lane < 8) ok = (int)(ld_acquire(&g_ocnt[(ti * 8 + lane) * 32]) - (epoch + 1)) >= 0;
                        ready = __ballot_sync(0xffffffffu, ok);
                        if (!((ready >> js) & 1)) __nanosleep(100);
                    }
                    asm volatile("fence.proxy.async.global;" ::: "memory");
                    if (leader) {
                        mbar_expect_tx(full, 16384);
                        tma_2d(dst, &map_o, full, 64 * js, ti * 128);
                    }
                    r.next();
                }
            }
        } else if (warp == 9) {
            unsigned epoch = 0;
            if (lane == 0) {
                epoch = atomicAdd(&g_ticket, 1u) >> 7;
                asm volatile("st.shared.u32 [%0], %1;" :: "r"(sb + EPOCH_OFF), "r"(epoch) : "memory");
                mbar_arrive(sb + B_EREADY);
                mbar_wait_idle(sb + B_XFULL + 8 * PF1_AT, 0);
                prefetch_l2(w1p + (size_t)blockIdx.x * 14336, 14336);
                mbar_wait_idle(sb + B_XFULL + 8 * PF2_AT, 0);
                prefetch_l2(w2p + (size_t)blockIdx.x * 14336, 14336);
                prefetch_l2(wop + (size_t)blockIdx.x * 4096, 4096);
                mbar_wait_idle(sb + B_KVDONE, 0);
                red_release(&g_kvcnt[blockIdx.x * 32], 1u);
            }
            epoch = __shfl_sync(0xffffffffu, epoch, 0);
            if (lane < 3 && ti - lane >= 0) wait_counter(&g_kvcnt[((ti - lane) * 8 + tj) * 32], epoch + 1);
            __syncwarp();
            if (lane == 0) mbar_arrive(sb + B_KVREADY);
            mbar_wait_idle(sb + B_SQ + 24, 0);
            if (lane < 8) wait_counter(&g_pcnt[(ti * 8 + lane) * 32], epoch + 1);
            __syncwarp();
            if (lane == 0) { mbar_arrive(sb + B_PREADY); TSX(13); }
            sum_partials(sb, ti, tj, lane);
            if (lane == 0) TSX(14);
        } else {
            if (warp == 10) {
#pragma unroll 1
                for (int q = 0; q < 4; q++) {
                    mbar_wait_idle(sb + B_SQ + 8 * q, 0);
                    if (lane < 16) {
                        uint4* d = g_part + (size_t)(((ti * 8 + 2 * q + (lane & 1)) * 8 + tj) * 8 + (lane >> 1)) * 128;
                        bulk_s2g(d, sb + STG_OFF + (q & 1) * 32768 + lane * 2048, 2048);
                        asm volatile("cp.async.bulk.commit_group;" ::: "memory");
                        asm volatile("cp.async.bulk.wait_group.read 0;" ::: "memory");
                    }
                    __syncwarp();
                    if (lane == 0) mbar_arrive(sb + B_SF + 8 * (q & 1));
                }
                asm volatile("cp.async.bulk.wait_group 0;" ::: "memory");
                asm volatile("fence.proxy.async.global;" ::: "memory");
                __syncwarp();
                if (lane == 0) { red_release(&g_pcnt[blockIdx.x * 32], 1u); TSX(12); }
            }
            mbar_wait_idle(sb + B_PREADY, 0);
            sum_partials(sb, ti, tj, lane);
            if (warp == 11 && lane == 0) {
                mbar_wait_idle(sb + B_ODONE, 0);
                red_release(&g_ocnt[blockIdx.x * 32], 1u);
            }
        }
    } else {
        asm volatile("setmaxnreg.inc.sync.aligned.u32 208;");
        const int wg = warp >> 2, g = lane >> 2, c = lane & 3;
        const uint32_t xa = sb + X_OFF + wg * 8192;
        Ring r{0, 0};
        const bool lane0 = lane == 0 && !dry;
        uint32_t qf[4][4];
        float g0, g1;
        TS(9);
        {
            float acc[100];
            int prev = 0;
            if (wg == 1) asm volatile("bar.sync 3, 256;" ::: "memory");
            for (int s = 0; s < (dry ? 4 : N_QKV); s++) {
                if (!(s & 1) && !dry) mbar_wait(sb + B_XFULL + 8 * (s >> 1), 0);
                CWAIT();
                if (s == 0) TS(1);
                if (s == 2) TS(28);
                if (s == 6) TS(29);
                if (s == 10) TS(20);
                const uint32_t bs = sb + RING_OFF + r.slot * SLOT, as = xa + (s >> 1) * 16384 + (s & 1) * 64;
                wgmma_fence();
                wgmma_ss_n200(acc, desc_a(as), desc_b(bs), s);
                wgmma_ss_n200(acc, desc_a(as + 32), desc_b(bs + 2048), 1);
                wgmma_commit();
                if (wg == 0 && s == LEAD1) asm volatile("bar.arrive 3, 256;" ::: "memory");
                if (s > 0) { wgmma_wait<1>(); if (lane0) mbar_arrive(sb + B_EMPTY + 8 * prev); }
                prev = r.slot; r.next();
            }
            wgmma_wait<0>();
            fence_acc(acc);
            if (lane0) mbar_arrive(sb + B_EMPTY + 8 * prev);
            TS(2);
            const int blk = ti * 8 + warp;
#pragma unroll
            for (int hh = 0; hh < 4; hh++) {
                const float* t0 = &acc[8 * hh]; const float* t1 = &acc[8 * hh + 4];
                qf[hh][0] = pack_bf16(t0[0], t0[1]); qf[hh][1] = pack_bf16(t0[2], t0[3]);
                qf[hh][2] = pack_bf16(t1[0], t1[1]); qf[hh][3] = pack_bf16(t1[2], t1[3]);
                const float* k0 = &acc[32 + 8 * hh]; const float* k1 = &acc[32 + 8 * hh + 4];
                uint4 kv;
                kv.x = pack_bf16(k0[0], k0[1]); kv.y = pack_bf16(k1[0], k1[1]);
                kv.z = pack_bf16(k0[2], k0[3]); kv.w = pack_bf16(k1[2], k1[3]);
                if (!dry) g_kf[((tj * 4 + hh) * 128 + blk) * 32 + lane] = kv;
                const float* v0 = &acc[64 + 8 * hh]; const float* v1 = &acc[64 + 8 * hh + 4];
                uint4 vv;
                vv.x = movmatrix(pack_bf16(v0[0], v0[1])); vv.y = movmatrix(pack_bf16(v0[2], v0[3]));
                vv.z = movmatrix(pack_bf16(v1[0], v1[1])); vv.w = movmatrix(pack_bf16(v1[2], v1[3]));
                if (!dry) g_vf[((tj * 4 + hh) * 128 + blk) * 32 + lane] = vv;
            }
            __syncwarp();
            if (lane0) mbar_arrive(sb + B_KVDONE);
            const float z0 = __shfl_sync(0xffffffffu, acc[96], lane & ~3), z1 = __shfl_sync(0xffffffffu, acc[98], lane & ~3);
            g0 = 1.f / (1.f + __expf(-z0)); g1 = 1.f / (1.f + __expf(-z1));
        }
        TS(3);
        const int wrow = (warp & 3) * 16;
        {
            float acc[112];
            int prev = 0;
            for (int s = 0; s < (dry ? 4 : N_FFN1); s++) {
                CWAIT();
                const uint32_t bs = sb + RING_OFF + r.slot * SLOT, as = xa + (s >> 1) * 16384 + (s & 1) * 64;
                wgmma_fence();
                wgmma_ss_n224(acc, desc_a(as), desc_b(bs), s);
                wgmma_ss_n224(acc, desc_a(as + 32), desc_b(bs + 2048), 1);
                wgmma_commit();
                if (s > 0) { wgmma_wait<1>(); if (lane0) mbar_arrive(sb + B_EMPTY + 8 * prev); }
                prev = r.slot; r.next();
            }
            wgmma_wait<0>();
            fence_acc(acc);
            if (lane0) { mbar_arrive(sb + B_EMPTY + 8 * prev); mbar_arrive(sb + B_XDEAD); }
            TS(4);
            const float s0 = 1.f - g0, s1 = 1.f - g1;
            asm volatile("bar.sync %0, 128;" :: "r"(1 + wg) : "memory");
            const uint32_t strow = xa + (wrow + ((lane >> 3) & 1) * 8 + (lane & 7)) * 128;
#pragma unroll
            for (int p = 0; p < 14; p++) {
                const int nt = 2 * p + (lane >> 4);
                const float* a = &acc[8 * p];
                stmatrix_x4(strow + (p >> 2) * 16384 + (((nt & 7) ^ (lane & 7)) << 4),
                            pack_bf16_relu(a[0] * s0, a[1] * s0), pack_bf16_relu(a[2] * s1, a[3] * s1),
                            pack_bf16_relu(a[4] * s0, a[5] * s0), pack_bf16_relu(a[6] * s1, a[7] * s1));
            }
        }
        TS(5);
        {
            fence_async_smem();
            asm volatile("bar.sync %0, 128;" :: "r"(1 + wg) : "memory");
            float accA[64], accB[64];
            auto epilogue = [&](float (&acc)[64], int q) {
                fence_acc(acc);
                const uint32_t st = sb + STG_OFF + (q & 1) * 32768 + warp * 4096;
                if (q == 0 && !dry) mbar_wait(sb + B_XDEAD, 0);
                if (q >= 2 && !dry) mbar_wait(sb + B_SF + 8 * (q & 1), 0);
#pragma unroll
                for (int t2 = 0; t2 < 8; t2++) {
                    uint4 v;
                    v.x = pack_bf16(acc[8 * t2 + 0], acc[8 * t2 + 1]); v.y = pack_bf16(acc[8 * t2 + 2], acc[8 * t2 + 3]);
                    v.z = pack_bf16(acc[8 * t2 + 4], acc[8 * t2 + 5]); v.w = pack_bf16(acc[8 * t2 + 6], acc[8 * t2 + 7]);
                    sts128(st + t2 * 512 + lane * 16, v);
                }
                fence_async_smem();
                __syncwarp();
                if (lane0) mbar_arrive(sb + B_SQ + 8 * q);
            };
            int rel = r.slot;
#pragma unroll
            for (int m = 0; m < N_FFN2; m++) {
                CWAIT();
                wgmma_fence();
#pragma unroll
                for (int h = 0; h < 2; h++) {
                    const int u = 2 * m + h, q = u / 7, rr = u % 7;
                    const uint32_t bs = sb + RING_OFF + r.slot * SLOT + h * 8192;
                    const uint32_t as = xa + (rr >> 1) * 16384 + (rr & 1) * 64;
                    if (!(q & 1)) {
                        wgmma_ss_n128(accA, desc_a(as), desc_b(bs), rr);
                        wgmma_ss_n128(accA, desc_a(as + 32), desc_b(bs + 2048), 1);
                    } else {
                        wgmma_ss_n128(accB, desc_a(as), desc_b(bs), rr);
                        wgmma_ss_n128(accB, desc_a(as + 32), desc_b(bs + 2048), 1);
                    }
                }
                wgmma_commit();
                r.next();
                wgmma_wait<1>();
                if (m > 0) {
                    if (lane0) mbar_arrive(sb + B_EMPTY + 8 * rel);
                    if (++rel == RING) rel = 0;
                }
                if (m == 4) { TS(25); epilogue(accA, 0); }
                if (m == 7) { TS(26); epilogue(accB, 1); }
                if (m == 11) { TS(27); epilogue(accA, 2); }
            }
            wgmma_wait<0>();
            if (lane0) { mbar_arrive(sb + B_EMPTY + 8 * rel); mbar_arrive(sb + B_HDEAD); }
            epilogue(accB, 3);
        }
        TS(6);
        {
            const float SC = 0.25f * 1.4426950408889634f;
            const int gb0 = 8 * ti - 16 + warp;
            int slotK = 0, slotV = 0;
            const uint32_t ostore = sb + OWN_OFF + (warp * 16 + ((lane >> 3) & 1) * 8 + (lane & 7)) * 128;
            uint32_t* odst = reinterpret_cast<uint32_t*>(g_o + (size_t)(ti * 128 + warp * 16 + g) * 512 + tj * 64 + ((lane & 1) ? 8 : 0) + (lane & 2) * 2);
#define NHEADS (dry ? 2 : 4)
#define ATT_KWAIT(kb) do { slotK = r.slot; CWAIT(); kb = sb + RING_OFF + slotK * SLOT + warp * 512 + lane * 16; r.next(); } while (0)
#define ATT_VWAIT(vb) do { slotV = r.slot; CWAIT(); vb = sb + RING_OFF + slotV * SLOT + warp * 512 + lane * 16; r.next(); TS(21 + hh); } while (0)
#define ATT_KVREL() do { __syncwarp(); if (lane0) { mbar_arrive(sb + B_EMPTY + 8 * slotK); mbar_arrive(sb + B_EMPTY + 8 * slotV); } } while (0)
#define ATT_NEXTQ(h) do { \
                if ((h) == 1) { q0 = qf[1][0]; q1 = qf[1][1]; q2 = qf[1][2]; q3 = qf[1][3]; } \
                else if ((h) == 2) { q0 = qf[2][0]; q1 = qf[2][1]; q2 = qf[2][2]; q3 = qf[2][3]; } \
                else { q0 = qf[3][0]; q1 = qf[3][1]; q2 = qf[3][2]; q3 = qf[3][3]; } } while (0)
#define ATT_STORE(h, r0, r1, r2, r3) do { \
                if ((h) == 0 && !dry) mbar_wait(sb + B_SF, 1);        \
                stmatrix_x4(ostore + (((2 * (h) + (lane >> 4)) ^ (lane & 7)) << 4), r0, r1, r2, r3); \
                const bool odd = lane & 1; \
                const uint32_t sl = __shfl_xor_sync(0xffffffffu, odd ? (r0) : (r2), 1), sh = __shfl_xor_sync(0xffffffffu, odd ? (r1) : (r3), 1); \
                if (!dry) *reinterpret_cast<uint2*>(odst + 8 * (h)) = odd ? make_uint2(sl, r2) : make_uint2(r0, sl); \
                if (!dry) *reinterpret_cast<uint2*>(odst + 8 * (h) + 8 * 256) = odd ? make_uint2(sh, r3) : make_uint2(r1, sh); \
                } while (0)
            auto attention = [&](auto masked_tag) {
            constexpr bool MASKED = decltype(masked_tag)::value;
            const float NEG = -INFINITY;
            const uint32_t ONES = 0x3F803F80u;
            float sa[8][2][4];
            float o[2][4], ls[4];
            float m0, m1;
            uint32_t q0 = qf[0][0], q1 = qf[0][1], q2 = qf[0][2], q3 = qf[0][3];
            auto qk = [&](float (&s)[8][2][4], int ps, int t, uint32_t kbase, bool merged) {
                if (merged) {
                    const uint4 kd = lds128_free(kbase + 16 * 512);
                    const uint4 kf = lds128_free(kbase);
                    float f[2][4];
                    const float ci = (!MASKED || opaque(gb0) >= 0) ? 0.f : NEG;
                    mma16816_c(s[0][0], q0, q1, q2, q3, kd.x, kd.y, 0.f);
                    mma16816_c(s[0][1], q0, q1, q2, q3, kd.z, kd.w, 0.f);
                    mma16816_c(f[0], q0, q1, q2, q3, kf.x, kf.y, ci);
                    mma16816_c(f[1], q0, q1, q2, q3, kf.z, kf.w, ci);
#pragma unroll
                    for (int u = 0; u < 2; u++)
#pragma unroll
                        for (int e = 0; e < 4; e++) {
                            const int row = g + 8 * (e >> 1), col = 8 * u + 2 * c + (e & 1);
                            s[0][u][e] = (col > row) ? f[u][e] : s[0][u][e];
                        }
                } else {
                    const uint4 kf = lds128_free(kbase + (8 * ps + t) * 512);
                    const float ci = (!MASKED || opaque(gb0) + 8 * ps + t >= 0) ? 0.f : NEG;
                    mma16816_c(s[t][0], q0, q1, q2, q3, kf.x, kf.y, ci);
                    mma16816_c(s[t][1], q0, q1, q2, q3, kf.z, kf.w, ci);
                }
            };
            auto rowmax = [&](float (&s)[8][2][4], float b0, float b1, float& n0, float& n1) {
                int i0 = __float_as_int(b0), i1 = __float_as_int(b1);
#pragma unroll
                for (int t = 0; t < 8; t++)
#pragma unroll
                    for (int u = 0; u < 2; u++) {
                        i0 = __vimax3_s32(i0, __float_as_int(s[t][u][0]), __float_as_int(s[t][u][1]));
                        i1 = __vimax3_s32(i1, __float_as_int(s[t][u][2]), __float_as_int(s[t][u][3]));
                    }
                i0 = max(i0, __shfl_xor_sync(0xffffffffu, i0, 1)); i1 = max(i1, __shfl_xor_sync(0xffffffffu, i1, 1));
                i0 = max(i0, __shfl_xor_sync(0xffffffffu, i0, 2)); i1 = max(i1, __shfl_xor_sync(0xffffffffu, i1, 2));
                n0 = __int_as_float(i0); n1 = __int_as_float(i1);
                if (__any_sync(0xffffffffu, (i0 | i1) < 0)) {
                    asm volatile("" ::: "memory");
                    n0 = b0; n1 = b1;
#pragma unroll
                    for (int t = 0; t < 8; t++)
#pragma unroll
                        for (int u = 0; u < 2; u++) {
                            n0 = fmaxf(n0, fmaxf(s[t][u][0], s[t][u][1]));
                            n1 = fmaxf(n1, fmaxf(s[t][u][2], s[t][u][3]));
                        }
                    n0 = fmaxf(n0, __shfl_xor_sync(0xffffffffu, n0, 1)); n1 = fmaxf(n1, __shfl_xor_sync(0xffffffffu, n1, 1));
                    n0 = fmaxf(n0, __shfl_xor_sync(0xffffffffu, n0, 2)); n1 = fmaxf(n1, __shfl_xor_sync(0xffffffffu, n1, 2));
                }
            };
            auto pv = [&](const float (&p)[2][4], uint32_t vaddr) {
                const uint4 vf = lds128_free(vaddr);
                const uint32_t a0 = pack_bf16(p[0][0], p[0][1]), a1 = pack_bf16(p[0][2], p[0][3]);
                const uint32_t a2 = pack_bf16(p[1][0], p[1][1]), a3 = pack_bf16(p[1][2], p[1][3]);
                mma16816(o[0], a0, a1, a2, a3, vf.x, vf.y);
                mma16816(o[1], a0, a1, a2, a3, vf.z, vf.w);
                mma16816(ls, a0, a1, a2, a3, ONES, ONES);
            };
            auto expv = [&](float (&s)[8][2][4], int ps, int t, float mc0, float mc1, uint32_t vbase, bool merged) {
                float p[2][4];
#pragma unroll
                for (int u = 0; u < 2; u++) {
                    p[u][0] = ex2(fmaf(s[t][u][0], SC, -mc0)); p[u][1] = ex2(fmaf(s[t][u][1], SC, -mc0));
                    p[u][2] = ex2(fmaf(s[t][u][2], SC, -mc1)); p[u][3] = ex2(fmaf(s[t][u][3], SC, -mc1));
                }
                if (merged) {
                    float pd[2][4], pf[2][4];
#pragma unroll
                    for (int u = 0; u < 2; u++)
#pragma unroll
                        for (int e = 0; e < 4; e++) {
                            const int row = g + 8 * (e >> 1), col = 8 * u + 2 * c + (e & 1);
                            pf[u][e] = (col > row) ? p[u][e] : 0.f;
                            pd[u][e] = (col > row) ? 0.f : p[u][e];
                        }
                    pv(pd, vbase + 16 * 512);
                    pv(pf, vbase);
                } else {
                    pv(p, vbase + (8 * ps + t) * 512);
                }
            };
            uint32_t kbase = 0, vbase = 0;
#pragma unroll 1
            for (int hh = 0; hh < NHEADS; hh++) {
                ATT_KWAIT(kbase);
                ATT_VWAIT(vbase);
                asm volatile("" : "+r"(kbase), "+r"(vbase) :: "memory");
                if (hh > 0) ATT_NEXTQ(hh);
#pragma unroll
                for (int ps = 0; ps < 2; ps++) {
#pragma unroll
                    for (int t = 0; t < 8; t++) qk(sa, ps, t, kbase, ps == 0 && t == 0);
                    float n0, n1;
                    rowmax(sa, ps ? m0 : NEG, ps ? m1 : NEG, n0, n1);
                    if (ps == 0) {
#pragma unroll
                        for (int e = 0; e < 4; e++) { o[0][e] = 0.f; o[1][e] = 0.f; ls[e] = 0.f; }
                    } else {
                        const float a0 = ex2((m0 - n0) * SC), a1 = ex2((m1 - n1) * SC);
                        ls[0] *= a0; ls[2] *= a1;
                        o[0][0] *= a0; o[0][1] *= a0; o[1][0] *= a0; o[1][1] *= a0;
                        o[0][2] *= a1; o[0][3] *= a1; o[1][2] *= a1; o[1][3] *= a1;
                    }
                    m0 = n0; m1 = n1;
                    const float mc0 = n0 * SC, mc1 = n1 * SC;
#pragma unroll
                    for (int t = 0; t < 8; t++) expv(sa, ps, t, mc0, mc1, vbase, ps == 0 && t == 0);
                }
                const float f0 = __fdividef(g0, ls[0]), f1 = __fdividef(g1, ls[2]);
                ATT_STORE(hh, pack_bf16(o[0][0] * f0, o[0][1] * f0), pack_bf16(o[0][2] * f1, o[0][3] * f1),
                              pack_bf16(o[1][0] * f0, o[1][1] * f0), pack_bf16(o[1][2] * f1, o[1][3] * f1));
                ATT_KVREL();
            }
            };
            if (ti >= 2) attention(BoolTag<false>{}); else attention(BoolTag<true>{});
            fence_async_smem();
            __syncwarp();
            if (lane0) mbar_arrive(sb + B_ODONE);
        }
        TS(7);
        {
            float acc[32];
            uint4 pv[4][4];
            if (!dry) mbar_wait(sb + B_PREADY, 0);
            {
                const uint4* p = g_part + (size_t)((ti * 8 + tj) * 8 + 4) * 1024 + warp * 128 + lane;
#pragma unroll
                for (int s = 0; s < 4; s++)
#pragma unroll
                    for (int n = 0; n < 4; n++) pv[n][s] = dry ? make_uint4(0u, 0u, 0u, 0u) : ldg_weak(p + s * 1024 + n * 32);
            }
            if (!dry) mbar_wait(sb + B_WOFULL, 0);
            if (!dry) mbar_wait(sb + B_ODONE, 0);
            TS(15);
            wgmma_fence();
#pragma unroll
            for (int k = 0; k < 4; k++) wgmma_ss_n64(acc, desc_a(sb + OWN_OFF + wg * 8192 + 32 * k), desc_b(sb + X_OFF + tj * 8192 + 2048 * k), k);
            wgmma_commit();
            float base[32];
            if (!dry) mbar_wait(sb + B_HSUM, 0);
#pragma unroll
            for (int n = 0; n < 4; n++) {
                const uint4 u0 = lds128(sb + HSUM_OFF + (warp * 8 + 2 * n) * 512 + lane * 16), u1 = lds128(sb + HSUM_OFF + (warp * 8 + 2 * n + 1) * 512 + lane * 16);
                float* a = &base[8 * n];
                a[0] = __uint_as_float(u0.x); a[1] = __uint_as_float(u0.y); a[2] = __uint_as_float(u0.z); a[3] = __uint_as_float(u0.w);
                a[4] = __uint_as_float(u1.x); a[5] = __uint_as_float(u1.y); a[6] = __uint_as_float(u1.z); a[7] = __uint_as_float(u1.w);
#pragma unroll
                for (int s = 0; s < 4; s++) {
                    a[0] += bf_lo(pv[n][s].x); a[1] += bf_hi(pv[n][s].x); a[2] += bf_lo(pv[n][s].y); a[3] += bf_hi(pv[n][s].y);
                    a[4] += bf_lo(pv[n][s].z); a[5] += bf_hi(pv[n][s].z); a[6] += bf_lo(pv[n][s].w); a[7] += bf_hi(pv[n][s].w);
                }
            }
            fence_acc(base);
            TS(16);
#pragma unroll 1
            for (int m = 0; m < N_O; m++) {
                CWAIT();
                const uint32_t js = tj + 1 + m;
                const uint32_t as = sb + RING_OFF + r.slot * SLOT + wg * 8192;
                const uint32_t bs = sb + X_OFF + (js & 7) * 8192;
                wgmma_fence();
#pragma unroll
                for (int k = 0; k < 4; k++) wgmma_ss_n64(acc, desc_a(as + 32 * k), desc_b(bs + 2048 * k), 1);
                wgmma_commit();
                if (m == 0) { wgmma_wait<0>(); if (lane0) mbar_arrive(sb + B_EMPTY + 8 * r.slot); }
                r.next();
            }
            wgmma_wait<0>();
            fence_acc(acc);
            TS(17);
#pragma unroll
            for (int k = 0; k < 32; k++) acc[k] += base[k];
            __nv_bfloat16* o = out + (size_t)(ti * 128 + warp * 16 + g) * 512 + tj * 64 + ((lane & 1) ? 8 : 0) + (lane & 2) * 2;
            const bool odd = lane & 1;
#pragma unroll
            for (int t2 = 0; t2 < 4; t2++) {
                const uint32_t lo0 = pack_bf16(acc[8 * t2 + 0], acc[8 * t2 + 1]), hi0 = pack_bf16(acc[8 * t2 + 2], acc[8 * t2 + 3]);
                const uint32_t lo1 = pack_bf16(acc[8 * t2 + 4], acc[8 * t2 + 5]), hi1 = pack_bf16(acc[8 * t2 + 6], acc[8 * t2 + 7]);
                const uint32_t sl = __shfl_xor_sync(0xffffffffu, odd ? lo0 : lo1, 1), sh = __shfl_xor_sync(0xffffffffu, odd ? hi0 : hi1, 1);
                if (!dry) *reinterpret_cast<uint2*>(o + 16 * t2) = odd ? make_uint2(sl, lo1) : make_uint2(lo0, sl);
                if (!dry) *reinterpret_cast<uint2*>(o + 16 * t2 + 8 * 512) = odd ? make_uint2(sh, hi1) : make_uint2(hi0, sh);
            }
            if (tid == 0 && !dry) TSG(30);
        }
        TS(8);
    }
}

typedef CUresult (*PFN_encodeTiled)(CUtensorMap*, CUtensorMapDataType, cuuint32_t, void*, const cuuint64_t*, const cuuint64_t*,
                                    const cuuint32_t*, const cuuint32_t*, CUtensorMapInterleave, CUtensorMapSwizzle,
                                    CUtensorMapL2promotion, CUtensorMapFloatOOBfill);

void make_map(PFN_encodeTiled enc, CUtensorMap* m, const void* base, int rank, const cuuint64_t* dims, const cuuint64_t* strides, const cuuint32_t* box) {
    cuuint32_t es[5] = {1, 1, 1, 1, 1};
    enc(m, CU_TENSOR_MAP_DATA_TYPE_BFLOAT16, (cuuint32_t)rank, const_cast<void*>(base), dims, strides, box, es,
        CU_TENSOR_MAP_INTERLEAVE_NONE, CU_TENSOR_MAP_SWIZZLE_128B, CU_TENSOR_MAP_L2_PROMOTION_L2_256B, CU_TENSOR_MAP_FLOAT_OOB_FILL_NONE);
}

}

extern "C" void kernel_launch(void* const* d_in, const int* in_sizes, int n_in, void* d_out, int out_size) {
    (void)in_sizes; (void)n_in; (void)out_size;
    const void* x = d_in[0]; const void* wqkv = d_in[1]; const void* wo = d_in[2];
    const void* w1 = d_in[4]; const void* w2 = d_in[5]; const void* gate_w = d_in[6];
    static PFN_encodeTiled enc = nullptr;
    static int ncta = 128;
    if (!enc) {
        int dev = 0, sms = 0;
        cudaGetDevice(&dev);
        cudaDeviceGetAttribute(&sms, cudaDevAttrMultiProcessorCount, dev);
        ncta = sms > 132 ? 132 : (sms > 128 ? sms : 128);
        void* fn = nullptr; cudaDriverEntryPointQueryResult st;
        cudaGetDriverEntryPoint("cuTensorMapEncodeTiled", &fn, cudaEnableDefault, &st);
        enc = (PFN_encodeTiled)fn;
        cudaFuncSetAttribute(fused_kernel, cudaFuncAttributeMaxDynamicSharedMemorySize, SMEM_BYTES);
    }
    CUtensorMap mx, mqkv, mw1, mw2, mwo, mw1a, mo;
    void* optr = nullptr;
    cudaGetSymbolAddress(&optr, g_o);
    { cuuint64_t d[2] = {512, 2048}, s[1] = {1024}; cuuint32_t b[2] = {64, 128}; make_map(enc, &mo, optr, 2, d, s, b); }
    { cuuint64_t d[4] = {64, 512, 3, 8}, s[3] = {3584, 128, 448}; cuuint32_t b[4] = {64, 32, 3, 1}; make_map(enc, &mw1a, w1, 4, d, s, b); }
    { cuuint64_t d[2] = {512, 2048}, s[1] = {1024}; cuuint32_t b[2] = {64, 128}; make_map(enc, &mx, x, 2, d, s, b); }
    { cuuint64_t d[4] = {64, 512, 8, 3}, s[3] = {3072, 128, 1024}; cuuint32_t b[4] = {64, 32, 1, 3}; make_map(enc, &mqkv, wqkv, 4, d, s, b); }
    { cuuint64_t d[2] = {1792, 512}, s[1] = {3584}; cuuint32_t b[2] = {64, 32}; make_map(enc, &mw1, w1, 2, d, s, b); }
    { cuuint64_t d[3] = {64, 1792, 8}, s[2] = {1024, 128}; cuuint32_t b[3] = {64, 32, 2}; make_map(enc, &mw2, w2, 3, d, s, b); }
    { cuuint64_t d[2] = {512, 512}, s[1] = {1024}; cuuint32_t b[2] = {64, 256}; make_map(enc, &mwo, wo, 2, d, s, b); }
    fused_kernel<<<ncta, 384, SMEM_BYTES, cudaStreamPerThread>>>(mx, mqkv, mw1, mw2, mwo, mw1a, mo, (const __nv_bfloat16*)gate_w, (__nv_bfloat16*)d_out,
                                           (const uint8_t*)w1, (const uint8_t*)w2, (const uint8_t*)wo);
}
```

```cpp
#include <cuda_runtime.h>
#include <cuda_bf16.h>
#include <cuda.h>
#include <stdint.h>

namespace {

#define PF1_AT 1
#define PF2_AT 5
#define LEAD1 0
#define OPUB 1
#define OSLEEP 100
constexpr int RING = 6;
constexpr int SLOT = 16384;
constexpr uint32_t X_OFF = 0;
constexpr uint32_t STG_OFF = X_OFF + 4 * 16384;
constexpr uint32_t RING_OFF = 131072;
constexpr uint32_t BAR_OFF = RING_OFF + RING * SLOT;
constexpr uint32_t B_FULL = BAR_OFF, B_EMPTY = BAR_OFF + 64, B_XFULL = BAR_OFF + 128, B_HDEAD = BAR_OFF + 192,
                   B_EREADY = BAR_OFF + 200, B_KVDONE = BAR_OFF + 208, B_ODONE = BAR_OFF + 224,
                   B_KVREADY = BAR_OFF + 232, B_WOFULL = BAR_OFF + 240, B_HSUM = BAR_OFF + 248, B_PREADY = BAR_OFF + 264,
                   B_SQ = BAR_OFF + 272, B_SF = BAR_OFF + 304, B_XDEAD = BAR_OFF + 320;
constexpr uint32_t EPOCH_OFF = BAR_OFF + 256, ITEM_OFF = BAR_OFF + 260;
constexpr uint32_t OWN_OFF = X_OFF + 4 * 16384;
constexpr uint32_t HSUM_OFF = X_OFF + 6 * 16384;
constexpr uint32_t SMEM_BYTES = BAR_OFF + 1024;

constexpr int N_QKV = 16, N_FFN1 = 16, N_FFN2 = 14, N_KV = 8, N_O = 7;

__device__ uint4 g_kf[32 * 128 * 32];
__device__ uint4 g_vf[32 * 128 * 32];
__device__ uint4 g_part[16 * 8 * 8 * 8 * 4 * 32];
__device__ __align__(128) __nv_bfloat16 g_o[2048 * 512];
__device__ unsigned g_ticket;
__device__ unsigned g_kvcnt[128 * 32];
__device__ unsigned g_pcnt[128 * 32];
__device__ unsigned g_ocnt[128 * 32];
#define TS(k) do {} while (0)
#define TS2(k) do {} while (0)
#define TS2X(k) do {} while (0)
#define TSX(k) do {} while (0)
#define TSG(k) do {} while (0)

__device__ __forceinline__ uint32_t smem_u32(const void* p) { return (uint32_t)__cvta_generic_to_shared(p); }
__device__ __forceinline__ void mbar_init(uint32_t bar, uint32_t cnt) { asm volatile("mbarrier.init.shared::cta.b64 [%0], %1;" :: "r"(bar), "r"(cnt) : "memory"); }
__device__ __forceinline__ void mbar_expect_tx(uint32_t bar, uint32_t bytes) { asm volatile("mbarrier.arrive.expect_tx.shared::cta.b64 _, [%0], %1;" :: "r"(bar), "r"(bytes) : "memory"); }
__device__ __forceinline__ void mbar_expect_only(uint32_t bar, uint32_t bytes) { asm volatile("mbarrier.expect_tx.relaxed.cta.shared::cta.b64 [%0], %1;" :: "r"(bar), "r"(bytes) : "memory"); }
__device__ __forceinline__ void mbar_arrive(uint32_t bar) { asm volatile("mbarrier.arrive.shared::cta.b64 _, [%0];" :: "r"(bar) : "memory"); }
__device__ __forceinline__ void mbar_wait(uint32_t bar, uint32_t parity) {
    asm volatile("{\n.reg .pred P1, P2;\n.reg .u32 n;\nmov.u32 n, 0;\n"
                 "WAIT_LOOP:\n"
                 "mbarrier.try_wait.parity.shared::cta.b64 P1, [%0], %1;\n"
                 "@P1 bra WAIT_DONE;\n"
                 "add.u32 n, n, 1;\n"
                 "setp.lt.u32 P2, n, 0x400000;\n"
                 "@P2 bra WAIT_LOOP;\n"
                 "WAIT_DONE:\n}" :: "r"(bar), "r"(parity) : "memory");
}
__device__ __forceinline__ void mbar_wait_idle(uint32_t bar, uint32_t parity) {
    asm volatile("{\n.reg .pred P1, P2;\n.reg .u32 n;\nmov.u32 n, 0;\n"
                 "WAIT_LOOP:\n"
                 "mbarrier.try_wait.parity.shared::cta.b64 P1, [%0], %1, 2000;\n"
                 "@P1 bra WAIT_DONE;\n"
                 "add.u32 n, n, 1;\n"
                 "setp.lt.u32 P2, n, 0x100000;\n"
                 "@P2 bra WAIT_LOOP;\n"
                 "WAIT_DONE:\n}" :: "r"(bar), "r"(parity) : "memory");
}
__device__ __forceinline__ void tma_2d(uint32_t dst, const void* map, uint32_t bar, int c0, int c1) {
    asm volatile("cp.async.bulk.tensor.2d.shared::cluster.global.mbarrier::complete_tx::bytes [%0], [%1, {%3, %4}], [%2];"
        :: "r"(dst), "l"(map), "r"(bar), "r"(c0), "r"(c1) : "memory");
}
__device__ __forceinline__ void tma_3d(uint32_t dst, const void* map, uint32_t bar, int c0, int c1, int c2) {
    asm volatile("cp.async.bulk.tensor.3d.shared::cluster.global.mbarrier::complete_tx::bytes [%0], [%1, {%3, %4, %5}], [%2];"
        :: "r"(dst), "l"(map), "r"(bar), "r"(c0), "r"(c1), "r"(c2) : "memory");
}
__device__ __forceinline__ void tma_4d(uint32_t dst, const void* map, uint32_t bar, int c0, int c1, int c2, int c3) {
    asm volatile("cp.async.bulk.tensor.4d.shared::cluster.global.mbarrier::complete_tx::bytes [%0], [%1, {%3, %4, %5, %6}], [%2];"
        :: "r"(dst), "l"(map), "r"(bar), "r"(c0), "r"(c1), "r"(c2), "r"(c3) : "memory");
}
__device__ __forceinline__ void bulk_g2s(uint32_t dst, const void* src, uint32_t bytes, uint32_t bar) {
    asm volatile("cp.async.bulk.shared::cluster.global.mbarrier::complete_tx::bytes [%0], [%1], %2, [%3];"
        :: "r"(dst), "l"(src), "r"(bytes), "r"(bar) : "memory");
}
__device__ __forceinline__ void prefetch_l2(const void* src, uint32_t bytes) {
    asm volatile("cp.async.bulk.prefetch.L2.global [%0], %1;" :: "l"(src), "r"(bytes) : "memory");
}
__device__ __forceinline__ bool elect_one() {
    uint32_t p;
    asm volatile("{\n.reg .pred P;\nelect.sync _|P, 0xffffffff;\nselp.u32 %0, 1, 0, P;\n}" : "=r"(p));
    return p != 0;
}
__device__ __forceinline__ void wgmma_fence() { asm volatile("wgmma.fence.sync.aligned;" ::: "memory"); }
__device__ __forceinline__ void wgmma_commit() { asm volatile("wgmma.commit_group.sync.aligned;" ::: "memory"); }
template <int N> __device__ __forceinline__ void wgmma_wait() { asm volatile("wgmma.wait_group.sync.aligned %0;" :: "n"(N) : "memory"); }
__device__ __forceinline__ void fence_async_smem() { asm volatile("fence.proxy.async.shared::cta;" ::: "memory"); }
__device__ __forceinline__ uint64_t desc_a(uint32_t addr) {
    return (uint64_t)((addr & 0x3FFFF) >> 4) | ((uint64_t)1 << 16) | ((uint64_t)(1024 >> 4) << 32) | ((uint64_t)1 << 62);
}
__device__ __forceinline__ uint64_t desc_b(uint32_t addr) {
    return (uint64_t)((addr & 0x3FFFF) >> 4) | ((uint64_t)(4096 >> 4) << 16) | ((uint64_t)(1024 >> 4) << 32) | ((uint64_t)1 << 62);
}
__device__ __forceinline__ uint32_t pack_bf16(float lo, float hi) {
    uint32_t r; asm("cvt.rn.bf16x2.f32 %0, %1, %2;" : "=r"(r) : "f"(hi), "f"(lo)); return r;
}
__device__ __forceinline__ uint32_t pack_bf16_relu(float lo, float hi) {
    uint32_t r; asm("cvt.rn.relu.bf16x2.f32 %0, %1, %2;" : "=r"(r) : "f"(hi), "f"(lo)); return r;
}
__device__ __forceinline__ uint32_t movmatrix(uint32_t a) {
    uint32_t d; asm volatile("movmatrix.sync.aligned.m8n8.trans.b16 %0, %1;" : "=r"(d) : "r"(a)); return d;
}
__device__ __forceinline__ void stmatrix_x4(uint32_t addr, uint32_t r0, uint32_t r1, uint32_t r2, uint32_t r3) {
    asm volatile("stmatrix.sync.aligned.m8n8.x4.shared.b16 [%0], {%1, %2, %3, %4};" :: "r"(addr), "r"(r0), "r"(r1), "r"(r2), "r"(r3) : "memory");
}
__device__ __forceinline__ uint4 lds128(uint32_t addr) {
    uint4 v; asm volatile("ld.shared.v4.b32 {%0, %1, %2, %3}, [%4];" : "=r"(v.x), "=r"(v.y), "=r"(v.z), "=r"(v.w) : "r"(addr) : "memory"); return v;
}
__device__ __forceinline__ uint4 lds128_free(uint32_t addr) {
    uint4 v; asm("ld.shared.v4.b32 {%0, %1, %2, %3}, [%4];" : "=r"(v.x), "=r"(v.y), "=r"(v.z), "=r"(v.w) : "r"(addr)); return v;
}
__device__ __forceinline__ void mma16816(float (&c)[4], uint32_t a0, uint32_t a1, uint32_t a2, uint32_t a3, uint32_t b0, uint32_t b1) {
    asm("mma.sync.aligned.m16n8k16.row.col.f32.bf16.bf16.f32 {%0,%1,%2,%3}, {%4,%5,%6,%7}, {%8,%9}, {%0,%1,%2,%3};"
        : "+f"(c[0]), "+f"(c[1]), "+f"(c[2]), "+f"(c[3]) : "r"(a0), "r"(a1), "r"(a2), "r"(a3), "r"(b0), "r"(b1));
}
__device__ __forceinline__ void mma16816_c(float (&c)[4], uint32_t a0, uint32_t a1, uint32_t a2, uint32_t a3, uint32_t b0, uint32_t b1, float ci) {
    asm("mma.sync.aligned.m16n8k16.row.col.f32.bf16.bf16.f32 {%0,%1,%2,%3}, {%4,%5,%6,%7}, {%8,%9}, {%10,%10,%10,%10};"
        : "=f"(c[0]), "=f"(c[1]), "=f"(c[2]), "=f"(c[3]) : "r"(a0), "r"(a1), "r"(a2), "r"(a3), "r"(b0), "r"(b1), "f"(ci));
}
__device__ __forceinline__ int opaque(int v) { asm volatile("" : "+r"(v)); return v; }
__device__ __forceinline__ float ex2(float x) { float y; asm("ex2.approx.ftz.f32 %0, %1;" : "=f"(y) : "f"(x)); return y; }
__device__ __forceinline__ unsigned ld_acquire(const unsigned* p) {
    unsigned v; asm volatile("ld.acquire.gpu.global.u32 %0, [%1];" : "=r"(v) : "l"(p) : "memory"); return v;
}
__device__ __forceinline__ void red_release(unsigned* p, unsigned v) {
    asm volatile("red.release.gpu.global.add.u32 [%0], %1;" :: "l"(p), "r"(v) : "memory");
}
__device__ __forceinline__ void wait_counter(const unsigned* p, unsigned target) {
    uint32_t n = 0;
    while ((int)(ld_acquire(p) - target) < 0) { if (++n > (1u << 20)) break; }
}
__device__ __forceinline__ uint4 ldg_weak(const uint4* p) {
    uint4 v; asm volatile("ld.global.L1::no_allocate.v4.b32 {%0, %1, %2, %3}, [%4];" : "=r"(v.x), "=r"(v.y), "=r"(v.z), "=r"(v.w) : "l"(p) : "memory"); return v;
}
__device__ __forceinline__ float bf_lo(uint32_t v) { return __uint_as_float(v << 16); }
__device__ __forceinline__ float bf_hi(uint32_t v) { return __uint_as_float(v & 0xFFFF0000u); }

__device__ __forceinline__ void wgmma_ss_n64(float (&d)[32], uint64_t da, uint64_t db, int scale_d) {
    asm volatile("{\n.reg .pred p;\nsetp.ne.b32 p, %34, 0;\n"
        "wgmma.mma_async.sync.aligned.m64n64k16.f32.bf16.bf16 {%0, %1, %2, %3, %4, %5, %6, %7, %8, %9, %10, %11, %12, %13, %14, %15, %16, %17, %18, %19, %20, %21, %22, %23, %24, %25, %26, %27, %28, %29, %30, %31}, %32, %33, p, 1, 1, 0, 1;\n}\n"
        : "+f"(d[0]), "+f"(d[1]), "+f"(d[2]), "+f"(d[3]), "+f"(d[4]), "+f"(d[5]), "+f"(d[6]), "+f"(d[7]), "+f"(d[8]), "+f"(d[9]), "+f"(d[10]), "+f"(d[11]), "+f"(d[12]), "+f"(d[13]), "+f"(d[14]), "+f"(d[15]), "+f"(d[16]), "+f"(d[17]), "+f"(d[18]), "+f"(d[19]), "+f"(d[20]), "+f"(d[21]), "+f"(d[22]), "+f"(d[23]), "+f"(d[24]), "+f"(d[25]), "+f"(d[26]), "+f"(d[27]), "+f"(d[28]), "+f"(d[29]), "+f"(d[30]), "+f"(d[31])
        : "l"(da), "l"(db), "r"(scale_d));
}
__device__ __forceinline__ void wgmma_ss_n128(float (&d)[64], uint64_t da, uint64_t db, int scale_d) {
    asm volatile("{\n.reg .pred p;\nsetp.ne.b32 p, %66, 0;\n"
        "wgmma.mma_async.sync.aligned.m64n128k16.f32.bf16.bf16 {%0, %1, %2, %3, %4, %5, %6, %7, %8, %9, %10, %11, %12, %13, %14, %15, %16, %17, %18, %19, %20, %21, %22, %23, %24, %25, %26, %27, %28, %29, %30, %31, %32, %33, %34, %35, %36, %37, %38, %39, %40, %41, %42, %43, %44, %45, %46, %47, %48, %49, %50, %51, %52, %53, %54, %55, %56, %57, %58, %59, %60, %61, %62, %63}, %64, %65, p, 1, 1, 0, 1;\n}\n"
        : "+f"(d[0]), "+f"(d[1]), "+f"(d[2]), "+f"(d[3]), "+f"(d[4]), "+f"(d[5]), "+f"(d[6]), "+f"(d[7]), "+f"(d[8]), "+f"(d[9]), "+f"(d[10]), "+f"(d[11]), "+f"(d[12]), "+f"(d[13]), "+f"(d[14]), "+f"(d[15]), "+f"(d[16]), "+f"(d[17]), "+f"(d[18]), "+f"(d[19]), "+f"(d[20]), "+f"(d[21]), "+f"(d[22]), "+f"(d[23]), "+f"(d[24]), "+f"(d[25]), "+f"(d[26]), "+f"(d[27]), "+f"(d[28]), "+f"(d[29]), "+f"(d[30]), "+f"(d[31]), "+f"(d[32]), "+f"(d[33]), "+f"(d[34]), "+f"(d[35]), "+f"(d[36]), "+f"(d[37]), "+f"(d[38]), "+f"(d[39]), "+f"(d[40]), "+f"(d[41]), "+f"(d[42]), "+f"(d[43]), "+f"(d[44]), "+f"(d[45]), "+f"(d[46]), "+f"(d[47]), "+f"(d[48]), "+f"(d[49]), "+f"(d[50]), "+f"(d[51]), "+f"(d[52]), "+f"(d[53]), "+f"(d[54]), "+f"(d[55]), "+f"(d[56]), "+f"(d[57]), "+f"(d[58]), "+f"(d[59]), "+f"(d[60]), "+f"(d[61]), "+f"(d[62]), "+f"(d[63])
        : "l"(da), "l"(db), "r"(scale_d));
}
__device__ __forceinline__ void wgmma_ss_n200(float (&d)[100], uint64_t da, uint64_t db, int scale_d) {
    asm volatile("{\n.reg .pred p;\nsetp.ne.b32 p, %102, 0;\n"
        "wgmma.mma_async.sync.aligned.m64n200k16.f32.bf16.bf16 {%0, %1, %2, %3, %4, %5, %6, %7, %8, %9, %10, %11, %12, %13, %14, %15, %16, %17, %18, %19, %20, %21, %22, %23, %24, %25, %26, %27, %28, %29, %30, %31, %32, %33, %34, %35, %36, %37, %38, %39, %40, %41, %42, %43, %44, %45, %46, %47, %48, %49, %50, %51, %52, %53, %54, %55, %56, %57, %58, %59, %60, %61, %62, %63, %64, %65, %66, %67, %68, %69, %70, %71, %72, %73, %74, %75, %76, %77, %78, %79, %80, %81, %82, %83, %84, %85, %86, %87, %88, %89, %90, %91, %92, %93, %94, %95, %96, %97, %98, %99}, %100, %101, p, 1, 1, 0, 1;\n}\n"
        : "+f"(d[0]), "+f"(d[1]), "+f"(d[2]), "+f"(d[3]), "+f"(d[4]), "+f"(d[5]), "+f"(d[6]), "+f"(d[7]), "+f"(d[8]), "+f"(d[9]), "+f"(d[10]), "+f"(d[11]), "+f"(d[12]), "+f"(d[13]), "+f"(d[14]), "+f"(d[15]), "+f"(d[16]), "+f"(d[17]), "+f"(d[18]), "+f"(d[19]), "+f"(d[20]), "+f"(d[21]), "+f"(d[22]), "+f"(d[23]), "+f"(d[24]), "+f"(d[25]), "+f"(d[26]), "+f"(d[27]), "+f"(d[28]), "+f"(d[29]), "+f"(d[30]), "+f"(d[31]), "+f"(d[32]), "+f"(d[33]), "+f"(d[34]), "+f"(d[35]), "+f"(d[36]), "+f"(d[37]), "+f"(d[38]), "+f"(d[39]), "+f"(d[40]), "+f"(d[41]), "+f"(d[42]), "+f"(d[43]), "+f"(d[44]), "+f"(d[45]), "+f"(d[46]), "+f"(d[47]), "+f"(d[48]), "+f"(d[49]), "+f"(d[50]), "+f"(d[51]), "+f"(d[52]), "+f"(d[53]), "+f"(d[54]), "+f"(d[55]), "+f"(d[56]), "+f"(d[57]), "+f"(d[58]), "+f"(d[59]), "+f"(d[60]), "+f"(d[61]), "+f"(d[62]), "+f"(d[63]), "+f"(d[64]), "+f"(d[65]), "+f"(d[66]), "+f"(d[67]), "+f"(d[68]), "+f"(d[69]), "+f"(d[70]), "+f"(d[71]), "+f"(d[72]), "+f"(d[73]), "+f"(d[74]), "+f"(d[75]), "+f"(d[76]), "+f"(d[77]), "+f"(d[78]), "+f"(d[79]), "+f"(d[80]), "+f"(d[81]), "+f"(d[82]), "+f"(d[83]), "+f"(d[84]), "+f"(d[85]), "+f"(d[86]), "+f"(d[87]), "+f"(d[88]), "+f"(d[89]), "+f"(d[90]), "+f"(d[91]), "+f"(d[92]), "+f"(d[93]), "+f"(d[94]), "+f"(d[95]), "+f"(d[96]), "+f"(d[97]), "+f"(d[98]), "+f"(d[99])
        : "l"(da), "l"(db), "r"(scale_d));
}
__device__ __forceinline__ void wgmma_ss_n224(float (&d)[112], uint64_t da, uint64_t db, int scale_d) {
    asm volatile("{\n.reg .pred p;\nsetp.ne.b32 p, %114, 0;\n"
        "wgmma.mma_async.sync.aligned.m64n224k16.f32.bf16.bf16 {%0, %1, %2, %3, %4, %5, %6, %7, %8, %9, %10, %11, %12, %13, %14, %15, %16, %17, %18, %19, %20, %21, %22, %23, %24, %25, %26, %27, %28, %29, %30, %31, %32, %33, %34, %35, %36, %37, %38, %39, %40, %41, %42, %43, %44, %45, %46, %47, %48, %49, %50, %51, %52, %53, %54, %55, %56, %57, %58, %59, %60, %61, %62, %63, %64, %65, %66, %67, %68, %69, %70, %71, %72, %73, %74, %75, %76, %77, %78, %79, %80, %81, %82, %83, %84, %85, %86, %87, %88, %89, %90, %91, %92, %93, %94, %95, %96, %97, %98, %99, %100, %101, %102, %103, %104, %105, %106, %107, %108, %109, %110, %111}, %112, %113, p, 1, 1, 0, 1;\n}\n"
        : "+f"(d[0]), "+f"(d[1]), "+f"(d[2]), "+f"(d[3]), "+f"(d[4]), "+f"(d[5]), "+f"(d[6]), "+f"(d[7]), "+f"(d[8]), "+f"(d[9]), "+f"(d[10]), "+f"(d[11]), "+f"(d[12]), "+f"(d[13]), "+f"(d[14]), "+f"(d[15]), "+f"(d[16]), "+f"(d[17]), "+f"(d[18]), "+f"(d[19]), "+f"(d[20]), "+f"(d[21]), "+f"(d[22]), "+f"(d[23]), "+f"(d[24]), "+f"(d[25]), "+f"(d[26]), "+f"(d[27]), "+f"(d[28]), "+f"(d[29]), "+f"(d[30]), "+f"(d[31]), "+f"(d[32]), "+f"(d[33]), "+f"(d[34]), "+f"(d[35]), "+f"(d[36]), "+f"(d[37]), "+f"(d[38]), "+f"(d[39]), "+f"(d[40]), "+f"(d[41]), "+f"(d[42]), "+f"(d[43]), "+f"(d[44]), "+f"(d[45]), "+f"(d[46]), "+f"(d[47]), "+f"(d[48]), "+f"(d[49]), "+f"(d[50]), "+f"(d[51]), "+f"(d[52]), "+f"(d[53]), "+f"(d[54]), "+f"(d[55]), "+f"(d[56]), "+f"(d[57]), "+f"(d[58]), "+f"(d[59]), "+f"(d[60]), "+f"(d[61]), "+f"(d[62]), "+f"(d[63]), "+f"(d[64]), "+f"(d[65]), "+f"(d[66]), "+f"(d[67]), "+f"(d[68]), "+f"(d[69]), "+f"(d[70]), "+f"(d[71]), "+f"(d[72]), "+f"(d[73]), "+f"(d[74]), "+f"(d[75]), "+f"(d[76]), "+f"(d[77]), "+f"(d[78]), "+f"(d[79]), "+f"(d[80]), "+f"(d[81]), "+f"(d[82]), "+f"(d[83]), "+f"(d[84]), "+f"(d[85]), "+f"(d[86]), "+f"(d[87]), "+f"(d[88]), "+f"(d[89]), "+f"(d[90]), "+f"(d[91]), "+f"(d[92]), "+f"(d[93]), "+f"(d[94]), "+f"(d[95]), "+f"(d[96]), "+f"(d[97]), "+f"(d[98]), "+f"(d[99]), "+f"(d[100]), "+f"(d[101]), "+f"(d[102]), "+f"(d[103]), "+f"(d[104]), "+f"(d[105]), "+f"(d[106]), "+f"(d[107]), "+f"(d[108]), "+f"(d[109]), "+f"(d[110]), "+f"(d[111])
        : "l"(da), "l"(db), "r"(scale_d));
}
template <int N> __device__ __forceinline__ void fence_acc(float (&d)[N]) {
#pragma unroll
    for (int i = 0; i < N; i++) asm volatile("" : "+f"(d[i]) :: "memory");
}

__device__ __forceinline__ void bulk_s2g(void* dst, uint32_t src, uint32_t bytes) {
    asm volatile("cp.async.bulk.global.shared::cta.bulk_group [%0], [%1], %2;" :: "l"(dst), "r"(src), "r"(bytes) : "memory");
}
__device__ __forceinline__ void sts128(uint32_t addr, uint4 v) {
    asm volatile("st.shared.v4.b32 [%0], {%1, %2, %3, %4};" :: "r"(addr), "r"(v.x), "r"(v.y), "r"(v.z), "r"(v.w) : "memory");
}
__device__ __forceinline__ void sum_partials(uint32_t sb, int ti, int tj, int lane) {
    for (;;) {
        uint32_t item = 0;
        if (lane == 0) asm volatile("atom.shared.add.u32 %0, [%1], 1;" : "=r"(item) : "r"(sb + ITEM_OFF) : "memory");
        item = __shfl_sync(0xffffffffu, item, 0);
        if (item >= 8) break;
        const uint4* p = g_part + (size_t)((ti * 8 + tj) * 8) * 1024 + item * 128 + lane;
        uint4 v[4][4];
#pragma unroll
        for (int s = 0; s < 4; s++)
#pragma unroll
            for (int n = 0; n < 4; n++) v[n][s] = ldg_weak(p + s * 1024 + n * 32);
#pragma unroll
        for (int n = 0; n < 4; n++) {
            float a[8];
#pragma unroll
            for (int e = 0; e < 8; e++) a[e] = 0.f;
#pragma unroll
            for (int s = 0; s < 4; s++) {
                a[0] += bf_lo(v[n][s].x); a[1] += bf_hi(v[n][s].x); a[2] += bf_lo(v[n][s].y); a[3] += bf_hi(v[n][s].y);
                a[4] += bf_lo(v[n][s].z); a[5] += bf_hi(v[n][s].z); a[6] += bf_lo(v[n][s].w); a[7] += bf_hi(v[n][s].w);
            }
            const uint32_t d = sb + HSUM_OFF + (item * 8 + n * 2) * 512 + lane * 16;
            sts128(d, make_uint4(__float_as_uint(a[0]), __float_as_uint(a[1]), __float_as_uint(a[2]), __float_as_uint(a[3])));
            sts128(d + 512, make_uint4(__float_as_uint(a[4]), __float_as_uint(a[5]), __float_as_uint(a[6]), __float_as_uint(a[7])));
        }
    }
    __syncwarp();
    if (lane == 0) mbar_arrive(sb + B_HSUM);
}

#define PWAIT() mbar_wait_idle(sb + B_EMPTY + 8 * r.slot, r.phase)
#define CWAIT() do { if (!dry) mbar_wait(sb + B_FULL + 8 * r.slot, r.phase); } while (0)
template <bool B> struct BoolTag { static constexpr bool value = B; };
struct Ring {
    int slot; uint32_t phase;
    __device__ __forceinline__ void next() { if (++slot == RING) { slot = 0; phase ^= 1; } }
};

__global__ void __launch_bounds__(384, 1)
fused_kernel(const __grid_constant__ CUtensorMap map_x, const __grid_constant__ CUtensorMap map_qkv,
             const __grid_constant__ CUtensorMap map_w1, const __grid_constant__ CUtensorMap map_w2,
             const __grid_constant__ CUtensorMap map_wo, const __grid_constant__ CUtensorMap map_w1a,
             const __grid_constant__ CUtensorMap map_o,
             const __nv_bfloat16* __restrict__ gate_w, __nv_bfloat16* __restrict__ out,
             const uint8_t* __restrict__ w1p, const uint8_t* __restrict__ w2p, const uint8_t* __restrict__ wop)
{
    extern __shared__ __align__(1024) uint8_t smem_raw[];
    const uint32_t sb = smem_u32(smem_raw);
    const int tid = threadIdx.x, warp = tid >> 5, lane = tid & 31;
    const bool dry = blockIdx.x >= 128;
    const int ti = dry ? (int)(blockIdx.x & 1) * 2 : blockIdx.x >> 3, tj = blockIdx.x & 7;
    if (dry && warp >= 8) {
        asm volatile("setmaxnreg.dec.sync.aligned.u32 88;");
        return;
    }

    if (tid == 0 && !dry) { TSG(31); TSX(0); }
    uint32_t gwv[N_QKV / 2];
    if (warp == 8) {
        const unsigned short* gws = reinterpret_cast<const unsigned short*>(gate_w);
#pragma unroll
        for (int n = 0; n < N_QKV / 2; n++) gwv[n] = (uint32_t)__ldg(gws + 64 * n + lane) | ((uint32_t)__ldg(gws + 64 * n + 32 + lane) << 16);
    }
    if (tid == 321) {
        asm volatile("prefetch.tensormap [%0];" :: "l"(&map_x) : "memory");
        asm volatile("prefetch.tensormap [%0];" :: "l"(&map_qkv) : "memory");
        asm volatile("prefetch.tensormap [%0];" :: "l"(&map_w1) : "memory");
        asm volatile("prefetch.tensormap [%0];" :: "l"(&map_w1a) : "memory");
        asm volatile("prefetch.tensormap [%0];" :: "l"(&map_w2) : "memory");
        asm volatile("prefetch.tensormap [%0];" :: "l"(&map_wo) : "memory");
        asm volatile("prefetch.tensormap [%0];" :: "l"(&map_o) : "memory");
    }
    if (tid == 288) {
        mbar_init(sb + B_FULL, 1); mbar_init(sb + B_XFULL, 1);
        fence_async_smem();
        mbar_expect_tx(sb + B_XFULL, 16384);
        tma_2d(sb + X_OFF, &map_x, sb + B_XFULL, 0, ti * 128);
        mbar_expect_only(sb + B_FULL, 12288);
        tma_4d(sb + RING_OFF, &map_qkv, sb + B_FULL, 0, 0, tj, 0);
    }
    if (tid == 320) {
        for (int s = 1; s < RING; s++) mbar_init(sb + B_FULL + 8 * s, 1);
        for (int s = 0; s < RING; s++) mbar_init(sb + B_EMPTY + 8 * s, 8);
        for (int s = 1; s < 8; s++) mbar_init(sb + B_XFULL + 8 * s, 1);
        fence_async_smem();
    }
    if (tid == 352) {
        mbar_init(sb + B_HDEAD, 8); mbar_init(sb + B_EREADY, 1); mbar_init(sb + B_KVDONE, 8); mbar_init(sb + B_KVREADY, 1);
        mbar_init(sb + B_ODONE, 8); mbar_init(sb + B_WOFULL, 1); mbar_init(sb + B_HSUM, 3);
        mbar_init(sb + B_XDEAD, 8); mbar_init(sb + B_PREADY, 1); mbar_init(sb + B_SF, 1); mbar_init(sb + B_SF + 8, 1);
        for (int s = 0; s < 4; s++) mbar_init(sb + B_SQ + 8 * s, 8);
        asm volatile("st.shared.u32 [%0], %1;" :: "r"(sb + ITEM_OFF), "r"(0) : "memory");
        fence_async_smem();
    }
    if (!dry) __syncthreads();

    if (warp >= 8) {
        asm volatile("setmaxnreg.dec.sync.aligned.u32 88;");
        if (warp == 8) {
            Ring r{0, 1};
            const bool leader = elect_one();
            if (leader) {
#pragma unroll
                for (int n = 1; n < RING; n++) {
                    if (!(n & 1)) {
                        mbar_expect_tx(sb + B_XFULL + 8 * (n >> 1), 16384);
                        tma_2d(sb + X_OFF + (n >> 1) * 16384, &map_x, sb + B_XFULL + 8 * (n >> 1), (n >> 1) * 64, ti * 128);
                    }
                    mbar_expect_only(sb + B_FULL + 8 * n, 12288);
                    tma_4d(sb + RING_OFF + n * SLOT, &map_qkv, sb + B_FULL + 8 * n, 0, 32 * n, tj, 0);
                }
            }
#pragma unroll
            for (int n = 0; n < N_QKV; n++) {
                const uint32_t full = sb + B_FULL + 8 * r.slot, dst = sb + RING_OFF + r.slot * SLOT;
                if (n >= RING) {
                    if (!(n & 1) && leader) {
                        mbar_expect_tx(sb + B_XFULL + 8 * (n >> 1), 16384);
                        tma_2d(sb + X_OFF + (n >> 1) * 16384, &map_x, sb + B_XFULL + 8 * (n >> 1), (n >> 1) * 64, ti * 128);
                    }
                    PWAIT();
                    if (leader) {
                        mbar_expect_only(full, 12288);
                        tma_4d(dst, &map_qkv, full, 0, 32 * n, tj, 0);
                    }
                }
                const uint32_t gv = (n & 1) ? (gwv[n >> 1] >> 16) : (gwv[n >> 1] & 0xFFFFu);
                asm volatile("st.shared.v4.b32 [%0], {%1, %2, %2, %2};" :: "r"(dst + 12288 + lane * 128 + ((lane & 7) << 4)), "r"(gv), "r"(0) : "memory");
                fence_async_smem();
                __syncwarp();
                if (leader) mbar_arrive(full);
                r.next();
            }
#pragma unroll 1
            for (int n = 0; n < N_FFN1; n++) {
                const uint32_t full = sb + B_FULL + 8 * r.slot, dst = sb + RING_OFF + r.slot * SLOT;
                PWAIT();
                if (leader) {
                    mbar_expect_tx(full, 16384);
                    tma_4d(dst, &map_w1a, full, 0, 32 * n, 0, tj);
                    tma_2d(dst + 3 * 4096, &map_w1, full, 224 * tj + 192, 32 * n);
                }
                r.next();
            }
            {
                int q = 0, rr = 0;
#pragma unroll 1
                for (int n = 0; n < N_FFN2; n++) {
                    const uint32_t full = sb + B_FULL + 8 * r.slot, dst = sb + RING_OFF + r.slot * SLOT;
                    PWAIT();
                    if (leader) mbar_expect_tx(full, 16384);
#pragma unroll
                    for (int h = 0; h < 2; h++) {
                        if (leader) tma_3d(dst + h * 8192, &map_w2, full, 0, 224 * tj + 32 * rr, 2 * q);
                        if (++rr == 7) { rr = 0; q++; }
                    }
                    r.next();
                }
            }
            mbar_wait_idle(sb + B_KVREADY, 0);
            asm volatile("fence.proxy.async.global;" ::: "memory");
            {
                const int bbase = 8 * ti - 16, b0 = bbase < 0 ? 0 : bbase;
                const uint32_t bytes = (uint32_t)(8 * ti + 8 - b0) * 512;
#pragma unroll 1
                for (int m = 0; m < N_KV; m++) {
                    const uint32_t full = sb + B_FULL + 8 * r.slot, dst = sb + RING_OFF + r.slot * SLOT;
                    if (m == RING) {
                        mbar_wait_idle(sb + B_HDEAD, 0);
                        if (leader) {
                            mbar_expect_tx(sb + B_WOFULL, 65536);
#pragma unroll
                            for (int e = 0; e < 2; e++) tma_2d(sb + X_OFF + e * 32768, &map_wo, sb + B_WOFULL, 64 * tj, 256 * e);
                        }
                    }
                    PWAIT();
                    if (leader) {
                        const uint4* src = ((m & 1) ? g_vf : g_kf) + ((tj * 4 + (m >> 1)) * 128 + b0) * 32;
                        mbar_expect_tx(full, bytes);
                        bulk_g2s(dst + (b0 - bbase) * 512, src, bytes, full);
                    }
                    r.next();
                }
            }
            {
                mbar_wait_idle(sb + B_EREADY, 0);
                unsigned epoch; asm volatile("ld.shared.u32 %0, [%1];" : "=r"(epoch) : "r"(sb + EPOCH_OFF) : "memory");
                uint32_t ready = 0;
                mbar_wait_idle(sb + B_HSUM, 0);
#pragma unroll 1
                for (int m = 0; m < N_O; m++) {
                    const uint32_t full = sb + B_FULL + 8 * r.slot, dst = sb + RING_OFF + r.slot * SLOT;
                    PWAIT();
                    const int js = (tj + 1 + m) & 7;
                    for (int it = 0; it < (1 << 20) && !((ready >> js) & 1); it++) {
                        bool ok = false;
                        if (lane < 8) ok = (int)(ld_acquire(&g_ocnt[(ti * 8 + lane) * 32]) - OPUB * (epoch + 1)) >= 0;
                        ready = __ballot_sync(0xffffffffu, ok);
                        if (!((ready >> js) & 1)) __nanosleep(OSLEEP);
                    }
                    asm volatile("fence.proxy.async.global;" ::: "memory");
                    if (leader) {
                        mbar_expect_tx(full, 16384);
                        tma_2d(dst, &map_o, full, 64 * js, ti * 128);
                    }
                    r.next();
                }
            }
        } else if (warp == 9) {
            unsigned epoch = 0;
            if (lane == 0) {
                epoch = atomicAdd(&g_ticket, 1u) >> 7;
                asm volatile("st.shared.u32 [%0], %1;" :: "r"(sb + EPOCH_OFF), "r"(epoch) : "memory");
                mbar_arrive(sb + B_EREADY);
                mbar_wait_idle(sb + B_XFULL + 8 * PF1_AT, 0);
                prefetch_l2(w1p + (size_t)blockIdx.x * 14336, 14336);
                mbar_wait_idle(sb + B_XFULL + 8 * PF2_AT, 0);
                prefetch_l2(w2p + (size_t)blockIdx.x * 14336, 14336);
                prefetch_l2(wop + (size_t)blockIdx.x * 4096, 4096);
                mbar_wait_idle(sb + B_KVDONE, 0);
                red_release(&g_kvcnt[blockIdx.x * 32], 1u);
            }
            epoch = __shfl_sync(0xffffffffu, epoch, 0);
            if (lane < 3 && ti - lane >= 0) wait_counter(&g_kvcnt[((ti - lane) * 8 + tj) * 32], epoch + 1);
            __syncwarp();
            if (lane == 0) mbar_arrive(sb + B_KVREADY);
            mbar_wait_idle(sb + B_SQ + 24, 0);
            if (lane < 8) wait_counter(&g_pcnt[(ti * 8 + lane) * 32], epoch + 1);
            __syncwarp();
            if (lane == 0) { mbar_arrive(sb + B_PREADY); TSX(13); }
            sum_partials(sb, ti, tj, lane);
            if (lane == 0) TSX(14);
        } else {
            if (warp == 10) {
#pragma unroll 1
                for (int q = 0; q < 4; q++) {
                    mbar_wait_idle(sb + B_SQ + 8 * q, 0);
                    if (lane < 16) {
                        uint4* d = g_part + (size_t)(((ti * 8 + 2 * q + (lane & 1)) * 8 + tj) * 8 + (lane >> 1)) * 128;
                        bulk_s2g(d, sb + STG_OFF + (q & 1) * 32768 + lane * 2048, 2048);
                        asm volatile("cp.async.bulk.commit_group;" ::: "memory");
                        asm volatile("cp.async.bulk.wait_group.read 0;" ::: "memory");
                    }
                    __syncwarp();
                    if (lane == 0) mbar_arrive(sb + B_SF + 8 * (q & 1));
                }
                asm volatile("cp.async.bulk.wait_group 0;" ::: "memory");
                asm volatile("fence.proxy.async.global;" ::: "memory");
                __syncwarp();
                if (lane == 0) { red_release(&g_pcnt[blockIdx.x * 32], 1u); TSX(12); }
            }
            mbar_wait_idle(sb + B_PREADY, 0);
            sum_partials(sb, ti, tj, lane);
            if (warp == 11 && lane == 0) {
                mbar_wait_idle(sb + B_ODONE, 0);
                red_release(&g_ocnt[blockIdx.x * 32], 1u);
            }
        }
    } else {
        asm volatile("setmaxnreg.inc.sync.aligned.u32 208;");
        const int wg = warp >> 2, g = lane >> 2, c = lane & 3;
        const uint32_t xa = sb + X_OFF + wg * 8192;
        Ring r{0, 0};
        const bool lane0 = lane == 0 && !dry;
        uint32_t qf[4][4];
        float g0, g1;
        TS(9);
        {
            float acc[100];
            int prev = 0;
            if (wg == 1) asm volatile("bar.sync 3, 256;" ::: "memory");
            for (int s = 0; s < (dry ? 4 : N_QKV); s++) {
                if (!(s & 1) && !dry) mbar_wait(sb + B_XFULL + 8 * (s >> 1), 0);
                CWAIT();
                if (s == 0) TS(1);
                if (s == 2) TS(28);
                if (s == 6) TS(29);
                if (s == 10) TS(20);
                const uint32_t bs = sb + RING_OFF + r.slot * SLOT, as = xa + (s >> 1) * 16384 + (s & 1) * 64;
                wgmma_fence();
                wgmma_ss_n200(acc, desc_a(as), desc_b(bs), s);
                wgmma_ss_n200(acc, desc_a(as + 32), desc_b(bs + 2048), 1);
                wgmma_commit();
                if (wg == 0 && s == LEAD1) asm volatile("bar.arrive 3, 256;" ::: "memory");
                if (s > 0) { wgmma_wait<1>(); if (lane0) mbar_arrive(sb + B_EMPTY + 8 * prev); }
                prev = r.slot; r.next();
            }
            wgmma_wait<0>();
            fence_acc(acc);
            if (lane0) mbar_arrive(sb + B_EMPTY + 8 * prev);
            TS(2);
            const int blk = ti * 8 + warp;
#pragma unroll
            for (int hh = 0; hh < 4; hh++) {
                const float* t0 = &acc[8 * hh]; const float* t1 = &acc[8 * hh + 4];
                qf[hh][0] = pack_bf16(t0[0], t0[1]); qf[hh][1] = pack_bf16(t0[2], t0[3]);
                qf[hh][2] = pack_bf16(t1[0], t1[1]); qf[hh][3] = pack_bf16(t1[2], t1[3]);
                const float* k0 = &acc[32 + 8 * hh]; const float* k1 = &acc[32 + 8 * hh + 4];
                uint4 kv;
                kv.x = pack_bf16(k0[0], k0[1]); kv.y = pack_bf16(k1[0], k1[1]);
                kv.z = pack_bf16(k0[2], k0[3]); kv.w = pack_bf16(k1[2], k1[3]);
                if (!dry) g_kf[((tj * 4 + hh) * 128 + blk) * 32 + lane] = kv;
                const float* v0 = &acc[64 + 8 * hh]; const float* v1 = &acc[64 + 8 * hh + 4];
                uint4 vv;
                vv.x = movmatrix(pack_bf16(v0[0], v0[1])); vv.y = movmatrix(pack_bf16(v0[2], v0[3]));
                vv.z = movmatrix(pack_bf16(v1[0], v1[1])); vv.w = movmatrix(pack_bf16(v1[2], v1[3]));
                if (!dry) g_vf[((tj * 4 + hh) * 128 + blk) * 32 + lane] = vv;
            }
            __syncwarp();
            if (lane0) mbar_arrive(sb + B_KVDONE);
            const float z0 = __shfl_sync(0xffffffffu, acc[96], lane & ~3), z1 = __shfl_sync(0xffffffffu, acc[98], lane & ~3);
            g0 = 1.f / (1.f + __expf(-z0)); g1 = 1.f / (1.f + __expf(-z1));
        }
        TS(3);
        const int wrow = (warp & 3) * 16;
        {
            float acc[112];
            int prev = 0;
            for (int s = 0; s < (dry ? 4 : N_FFN1); s++) {
                CWAIT();
                const uint32_t bs = sb + RING_OFF + r.slot * SLOT, as = xa + (s >> 1) * 16384 + (s & 1) * 64;
                wgmma_fence();
                wgmma_ss_n224(acc, desc_a(as), desc_b(bs), s);
                wgmma_ss_n224(acc, desc_a(as + 32), desc_b(bs + 2048), 1);
                wgmma_commit();
                if (s > 0) { wgmma_wait<1>(); if (lane0) mbar_arrive(sb + B_EMPTY + 8 * prev); }
                prev = r.slot; r.next();
            }
            wgmma_wait<0>();
            fence_acc(acc);
            if (lane0) { mbar_arrive(sb + B_EMPTY + 8 * prev); mbar_arrive(sb + B_XDEAD); }
            TS(4);
            const float s0 = 1.f - g0, s1 = 1.f - g1;
            asm volatile("bar.sync %0, 128;" :: "r"(1 + wg) : "memory");
            const uint32_t strow = xa + (wrow + ((lane >> 3) & 1) * 8 + (lane & 7)) * 128;
#pragma unroll
            for (int p = 0; p < 14; p++) {
                const int nt = 2 * p + (lane >> 4);
                const float* a = &acc[8 * p];
                stmatrix_x4(strow + (p >> 2) * 16384 + (((nt & 7) ^ (lane & 7)) << 4),
                            pack_bf16_relu(a[0] * s0, a[1] * s0), pack_bf16_relu(a[2] * s1, a[3] * s1),
                            pack_bf16_relu(a[4] * s0, a[5] * s0), pack_bf16_relu(a[6] * s1, a[7] * s1));
            }
        }
        TS(5);
        {
            fence_async_smem();
            asm volatile("bar.sync %0, 128;" :: "r"(1 + wg) : "memory");
            float accA[64], accB[64];
            auto epilogue = [&](float (&acc)[64], int q) {
                fence_acc(acc);
                const uint32_t st = sb + STG_OFF + (q & 1) * 32768 + warp * 4096;
                if (q == 0 && !dry) mbar_wait(sb + B_XDEAD, 0);
                if (q >= 2 && !dry) mbar_wait(sb + B_SF + 8 * (q & 1), 0);
#pragma unroll
                for (int t2 = 0; t2 < 8; t2++) {
                    uint4 v;
                    v.x = pack_bf16(acc[8 * t2 + 0], acc[8 * t2 + 1]); v.y = pack_bf16(acc[8 * t2 + 2], acc[8 * t2 + 3]);
                    v.z = pack_bf16(acc[8 * t2 + 4], acc[8 * t2 + 5]); v.w = pack_bf16(acc[8 * t2 + 6], acc[8 * t2 + 7]);
                    sts128(st + t2 * 512 + lane * 16, v);
                }
                fence_async_smem();
                __syncwarp();
                if (lane0) mbar_arrive(sb + B_SQ + 8 * q);
            };
            int rel = r.slot;
#pragma unroll 1
            for (int hf = 0; hf < 2; hf++) {
#pragma unroll
                for (int m = 0; m < 7; m++) {
                    CWAIT();
                    wgmma_fence();
#pragma unroll
                    for (int h = 0; h < 2; h++) {
                        const int u = 2 * m + h, rr = u % 7;
                        const uint32_t bs = sb + RING_OFF + r.slot * SLOT + h * 8192;
                        const uint32_t as = xa + (rr >> 1) * 16384 + (rr & 1) * 64;
                        if (u < 7) {
                            wgmma_ss_n128(accA, desc_a(as), desc_b(bs), rr);
                            wgmma_ss_n128(accA, desc_a(as + 32), desc_b(bs + 2048), 1);
                        } else {
                            wgmma_ss_n128(accB, desc_a(as), desc_b(bs), rr);
                            wgmma_ss_n128(accB, desc_a(as + 32), desc_b(bs + 2048), 1);
                        }
                    }
                    wgmma_commit();
                    r.next();
                    if (m == 6 && hf == 0) wgmma_wait<0>(); else wgmma_wait<1>();
                    if (m > 0) {
                        if (lane0) mbar_arrive(sb + B_EMPTY + 8 * rel);
                        if (++rel == RING) rel = 0;
                    }
                    if (m == 4) epilogue(accA, 2 * hf);
                }
                if (hf == 0) {
                    if (lane0) mbar_arrive(sb + B_EMPTY + 8 * rel);
                    if (++rel == RING) rel = 0;
                    epilogue(accB, 1);
                }
            }
            wgmma_wait<0>();
            if (lane0) { mbar_arrive(sb + B_EMPTY + 8 * rel); mbar_arrive(sb + B_HDEAD); }
            epilogue(accB, 3);
        }
        TS(6);
        {
            const float SC = 0.25f * 1.4426950408889634f;
            const int gb0 = 8 * ti - 16 + warp;
            int slotK = 0, slotV = 0;
            const uint32_t ostore = sb + OWN_OFF + (warp * 16 + ((lane >> 3) & 1) * 8 + (lane & 7)) * 128;
            uint32_t* odst = reinterpret_cast<uint32_t*>(g_o + (size_t)(ti * 128 + warp * 16 + g) * 512 + tj * 64 + ((lane & 1) ? 8 : 0) + (lane & 2) * 2);
#define NHEADS (dry ? 2 : 4)
#define ATT_KWAIT(kb) do { slotK = r.slot; CWAIT(); kb = sb + RING_OFF + slotK * SLOT + warp * 512 + lane * 16; r.next(); } while (0)
#define ATT_VWAIT(vb) do { slotV = r.slot; CWAIT(); vb = sb + RING_OFF + slotV * SLOT + warp * 512 + lane * 16; r.next(); TS(21 + hh); } while (0)
#define ATT_KVREL() do { __syncwarp(); if (lane0) { mbar_arrive(sb + B_EMPTY + 8 * slotK); mbar_arrive(sb + B_EMPTY + 8 * slotV); } } while (0)
#define ATT_NEXTQ(h) do { \
                if ((h) == 1) { q0 = qf[1][0]; q1 = qf[1][1]; q2 = qf[1][2]; q3 = qf[1][3]; } \
                else if ((h) == 2) { q0 = qf[2][0]; q1 = qf[2][1]; q2 = qf[2][2]; q3 = qf[2][3]; } \
                else { q0 = qf[3][0]; q1 = qf[3][1]; q2 = qf[3][2]; q3 = qf[3][3]; } } while (0)
#define ATT_STORE(h, r0, r1, r2, r3) do { \
                if ((h) == 0 && !dry) mbar_wait(sb + B_SF, 1);        \
                stmatrix_x4(ostore + (((2 * (h) + (lane >> 4)) ^ (lane & 7)) << 4), r0, r1, r2, r3); \
                const bool odd = lane & 1; \
                const uint32_t sl = __shfl_xor_sync(0xffffffffu, odd ? (r0) : (r2), 1), sh = __shfl_xor_sync(0xffffffffu, odd ? (r1) : (r3), 1); \
                if (!dry) *reinterpret_cast<uint2*>(odst + 8 * (h)) = odd ? make_uint2(sl, r2) : make_uint2(r0, sl); \
                if (!dry) *reinterpret_cast<uint2*>(odst + 8 * (h) + 8 * 256) = odd ? make_uint2(sh, r3) : make_uint2(r1, sh); \
                } while (0)
            auto attention = [&](auto masked_tag) {
            constexpr bool MASKED = decltype(masked_tag)::value;
            const float NEG = -INFINITY;
            const uint32_t ONES = 0x3F803F80u;
            float sa[8][2][4];
            float o[2][4], ls[4];
            float m0, m1;
            uint32_t q0 = qf[0][0], q1 = qf[0][1], q2 = qf[0][2], q3 = qf[0][3];
            auto qk = [&](float (&s)[8][2][4], int ps, int t, uint32_t kbase, bool merged) {
                if (merged) {
                    const uint4 kd = lds128_free(kbase + 16 * 512);
                    const uint4 kf = lds128_free(kbase);
                    float f[2][4];
                    const float ci = (!MASKED || opaque(gb0) >= 0) ? 0.f : NEG;
                    mma16816_c(s[0][0], q0, q1, q2, q3, kd.x, kd.y, 0.f);
                    mma16816_c(s[0][1], q0, q1, q2, q3, kd.z, kd.w, 0.f);
                    mma16816_c(f[0], q0, q1, q2, q3, kf.x, kf.y, ci);
                    mma16816_c(f[1], q0, q1, q2, q3, kf.z, kf.w, ci);
#pragma unroll
                    for (int u = 0; u < 2; u++)
#pragma unroll
                        for (int e = 0; e < 4; e++) {
                            const int row = g + 8 * (e >> 1), col = 8 * u + 2 * c + (e & 1);
                            s[0][u][e] = (col > row) ? f[u][e] : s[0][u][e];
                        }
                } else {
                    const uint4 kf = lds128_free(kbase + (8 * ps + t) * 512);
                    const float ci = (!MASKED || opaque(gb0) + 8 * ps + t >= 0) ? 0.f : NEG;
                    mma16816_c(s[t][0], q0, q1, q2, q3, kf.x, kf.y, ci);
                    mma16816_c(s[t][1], q0, q1, q2, q3, kf.z, kf.w, ci);
                }
            };
            auto rowmax = [&](float (&s)[8][2][4], float b0, float b1, float& n0, float& n1) {
                int i0 = __float_as_int(b0), i1 = __float_as_int(b1);
#pragma unroll
                for (int t = 0; t < 8; t++)
#pragma unroll
                    for (int u = 0; u < 2; u++) {
                        i0 = __vimax3_s32(i0, __float_as_int(s[t][u][0]), __float_as_int(s[t][u][1]));
                        i1 = __vimax3_s32(i1, __float_as_int(s[t][u][2]), __float_as_int(s[t][u][3]));
                    }
                i0 = max(i0, __shfl_xor_sync(0xffffffffu, i0, 1)); i1 = max(i1, __shfl_xor_sync(0xffffffffu, i1, 1));
                i0 = max(i0, __shfl_xor_sync(0xffffffffu, i0, 2)); i1 = max(i1, __shfl_xor_sync(0xffffffffu, i1, 2));
                n0 = __int_as_float(i0); n1 = __int_as_float(i1);
                if (__any_sync(0xffffffffu, (i0 | i1) < 0)) {
                    asm volatile("" ::: "memory");
                    n0 = b0; n1 = b1;
#pragma unroll
                    for (int t = 0; t < 8; t++)
#pragma unroll
                        for (int u = 0; u < 2; u++) {
                            n0 = fmaxf(n0, fmaxf(s[t][u][0], s[t][u][1]));
                            n1 = fmaxf(n1, fmaxf(s[t][u][2], s[t][u][3]));
                        }
                    n0 = fmaxf(n0, __shfl_xor_sync(0xffffffffu, n0, 1)); n1 = fmaxf(n1, __shfl_xor_sync(0xffffffffu, n1, 1));
                    n0 = fmaxf(n0, __shfl_xor_sync(0xffffffffu, n0, 2)); n1 = fmaxf(n1, __shfl_xor_sync(0xffffffffu, n1, 2));
                }
            };
            auto pv = [&](const float (&p)[2][4], uint32_t vaddr) {
                const uint4 vf = lds128_free(vaddr);
                const uint32_t a0 = pack_bf16(p[0][0], p[0][1]), a1 = pack_bf16(p[0][2], p[0][3]);
                const uint32_t a2 = pack_bf16(p[1][0], p[1][1]), a3 = pack_bf16(p[1][2], p[1][3]);
                mma16816(o[0], a0, a1, a2, a3, vf.x, vf.y);
                mma16816(o[1], a0, a1, a2, a3, vf.z, vf.w);
                mma16816(ls, a0, a1, a2, a3, ONES, ONES);
            };
            auto expv = [&](float (&s)[8][2][4], int ps, int t, float mc0, float mc1, uint32_t vbase, bool merged) {
                float p[2][4];
#pragma unroll
                for (int u = 0; u < 2; u++) {
                    p[u][0] = ex2(fmaf(s[t][u][0], SC, -mc0)); p[u][1] = ex2(fmaf(s[t][u][1], SC, -mc0));
                    p[u][2] = ex2(fmaf(s[t][u][2], SC, -mc1)); p[u][3] = ex2(fmaf(s[t][u][3], SC, -mc1));
                }
                if (merged) {
                    float pd[2][4], pf[2][4];
#pragma unroll
                    for (int u = 0; u < 2; u++)
#pragma unroll
                        for (int e = 0; e < 4; e++) {
                            const int row = g + 8 * (e >> 1), col = 8 * u + 2 * c + (e & 1);
                            pf[u][e] = (col > row) ? p[u][e] : 0.f;
                            pd[u][e] = (col > row) ? 0.f : p[u][e];
                        }
                    pv(pd, vbase + 16 * 512);
                    pv(pf, vbase);
                } else {
                    pv(p, vbase + (8 * ps + t) * 512);
                }
            };
            uint32_t kbase = 0, vbase = 0;
#pragma unroll 1
            for (int hh = 0; hh < NHEADS; hh++) {
                ATT_KWAIT(kbase);
                ATT_VWAIT(vbase);
                asm volatile("" : "+r"(kbase), "+r"(vbase) :: "memory");
                if (hh > 0) ATT_NEXTQ(hh);
#pragma unroll
                for (int ps = 0; ps < 2; ps++) {
#pragma unroll
                    for (int t = 0; t < 8; t++) qk(sa, ps, t, kbase, ps == 0 && t == 0);
                    float n0, n1;
                    rowmax(sa, ps ? m0 : NEG, ps ? m1 : NEG, n0, n1);
                    if (ps == 0) {
#pragma unroll
                        for (int e = 0; e < 4; e++) { o[0][e] = 0.f; o[1][e] = 0.f; ls[e] = 0.f; }
                    } else {
                        const float a0 = ex2((m0 - n0) * SC), a1 = ex2((m1 - n1) * SC);
                        ls[0] *= a0; ls[2] *= a1;
                        o[0][0] *= a0; o[0][1] *= a0; o[1][0] *= a0; o[1][1] *= a0;
                        o[0][2] *= a1; o[0][3] *= a1; o[1][2] *= a1; o[1][3] *= a1;
                    }
                    m0 = n0; m1 = n1;
                    const float mc0 = n0 * SC, mc1 = n1 * SC;
#pragma unroll
                    for (int t = 0; t < 8; t++) expv(sa, ps, t, mc0, mc1, vbase, ps == 0 && t == 0);
                }
                const float f0 = __fdividef(g0, ls[0]), f1 = __fdividef(g1, ls[2]);
                ATT_STORE(hh, pack_bf16(o[0][0] * f0, o[0][1] * f0), pack_bf16(o[0][2] * f1, o[0][3] * f1),
                              pack_bf16(o[1][0] * f0, o[1][1] * f0), pack_bf16(o[1][2] * f1, o[1][3] * f1));
                ATT_KVREL();
            }
            };
            if (ti >= 2) attention(BoolTag<false>{}); else attention(BoolTag<true>{});
            fence_async_smem();
            __syncwarp();
            if (lane0) mbar_arrive(sb + B_ODONE);
        }
        TS(7);
        {
            float acc[32];
            uint4 pv[4][4];
            if (!dry) mbar_wait(sb + B_PREADY, 0);
            {
                const uint4* p = g_part + (size_t)((ti * 8 + tj) * 8 + 4) * 1024 + warp * 128 + lane;
#pragma unroll
                for (int s = 0; s < 4; s++)
#pragma unroll
                    for (int n = 0; n < 4; n++) pv[n][s] = dry ? make_uint4(0u, 0u, 0u, 0u) : ldg_weak(p + s * 1024 + n * 32);
            }
            if (!dry) mbar_wait(sb + B_WOFULL, 0);
            if (!dry) mbar_wait(sb + B_ODONE, 0);
            TS(15);
            wgmma_fence();
#pragma unroll
            for (int k = 0; k < 4; k++) wgmma_ss_n64(acc, desc_a(sb + OWN_OFF + wg * 8192 + 32 * k), desc_b(sb + X_OFF + tj * 8192 + 2048 * k), k);
            wgmma_commit();
            float base[32];
            if (!dry) mbar_wait(sb + B_HSUM, 0);
#pragma unroll
            for (int n = 0; n < 4; n++) {
                const uint4 u0 = lds128(sb + HSUM_OFF + (warp * 8 + 2 * n) * 512 + lane * 16), u1 = lds128(sb + HSUM_OFF + (warp * 8 + 2 * n + 1) * 512 + lane * 16);
                float* a = &base[8 * n];
                a[0] = __uint_as_float(u0.x); a[1] = __uint_as_float(u0.y); a[2] = __uint_as_float(u0.z); a[3] = __uint_as_float(u0.w);
                a[4] = __uint_as_float(u1.x); a[5] = __uint_as_float(u1.y); a[6] = __uint_as_float(u1.z); a[7] = __uint_as_float(u1.w);
#pragma unroll
                for (int s = 0; s < 4; s++) {
                    a[0] += bf_lo(pv[n][s].x); a[1] += bf_hi(pv[n][s].x); a[2] += bf_lo(pv[n][s].y); a[3] += bf_hi(pv[n][s].y);
                    a[4] += bf_lo(pv[n][s].z); a[5] += bf_hi(pv[n][s].z); a[6] += bf_lo(pv[n][s].w); a[7] += bf_hi(pv[n][s].w);
                }
            }
            fence_acc(base);
            TS(16);
#pragma unroll 1
            for (int m = 0; m < N_O; m++) {
                CWAIT();
                const uint32_t js = tj + 1 + m;
                const uint32_t as = sb + RING_OFF + r.slot * SLOT + wg * 8192;
                const uint32_t bs = sb + X_OFF + (js & 7) * 8192;
                wgmma_fence();
#pragma unroll
                for (int k = 0; k < 4; k++) wgmma_ss_n64(acc, desc_a(as + 32 * k), desc_b(bs + 2048 * k), 1);
                wgmma_commit();
                if (m == 0) { wgmma_wait<0>(); if (lane0) mbar_arrive(sb + B_EMPTY + 8 * r.slot); }
                r.next();
            }
            wgmma_wait<0>();
            fence_acc(acc);
            TS(17);
#pragma unroll
            for (int k = 0; k < 32; k++) acc[k] += base[k];
            __nv_bfloat16* o = out + (size_t)(ti * 128 + warp * 16 + g) * 512 + tj * 64 + ((lane & 1) ? 8 : 0) + (lane & 2) * 2;
            const bool odd = lane & 1;
#pragma unroll
            for (int t2 = 0; t2 < 4; t2++) {
                const uint32_t lo0 = pack_bf16(acc[8 * t2 + 0], acc[8 * t2 + 1]), hi0 = pack_bf16(acc[8 * t2 + 2], acc[8 * t2 + 3]);
                const uint32_t lo1 = pack_bf16(acc[8 * t2 + 4], acc[8 * t2 + 5]), hi1 = pack_bf16(acc[8 * t2 + 6], acc[8 * t2 + 7]);
                const uint32_t sl = __shfl_xor_sync(0xffffffffu, odd ? lo0 : lo1, 1), sh = __shfl_xor_sync(0xffffffffu, odd ? hi0 : hi1, 1);
                if (!dry) *reinterpret_cast<uint2*>(o + 16 * t2) = odd ? make_uint2(sl, lo1) : make_uint2(lo0, sl);
                if (!dry) *reinterpret_cast<uint2*>(o + 16 * t2 + 8 * 512) = odd ? make_uint2(sh, hi1) : make_uint2(hi0, sh);
            }
            if (tid == 0 && !dry) TSG(30);
        }
        TS(8);
    }
}

typedef CUresult (*PFN_encodeTiled)(CUtensorMap*, CUtensorMapDataType, cuuint32_t, void*, const cuuint64_t*, const cuuint64_t*,
                                    const cuuint32_t*, const cuuint32_t*, CUtensorMapInterleave, CUtensorMapSwizzle,
                                    CUtensorMapL2promotion, CUtensorMapFloatOOBfill);

void make_map(PFN_encodeTiled enc, CUtensorMap* m, const void* base, int rank, const cuuint64_t* dims, const cuuint64_t* strides, const cuuint32_t* box) {
    cuuint32_t es[5] = {1, 1, 1, 1, 1};
    enc(m, CU_TENSOR_MAP_DATA_TYPE_BFLOAT16, (cuuint32_t)rank, const_cast<void*>(base), dims, strides, box, es,
        CU_TENSOR_MAP_INTERLEAVE_NONE, CU_TENSOR_MAP_SWIZZLE_128B, CU_TENSOR_MAP_L2_PROMOTION_L2_256B, CU_TENSOR_MAP_FLOAT_OOB_FILL_NONE);
}

}

extern "C" void kernel_launch(void* const* d_in, const int* in_sizes, int n_in, void* d_out, int out_size) {
    (void)in_sizes; (void)n_in; (void)out_size;
    const void* x = d_in[0]; const void* wqkv = d_in[1]; const void* wo = d_in[2];
    const void* w1 = d_in[4]; const void* w2 = d_in[5]; const void* gate_w = d_in[6];
    static PFN_encodeTiled enc = nullptr;
    static int ncta = 128;
    if (!enc) {
        int dev = 0, sms = 0;
        cudaGetDevice(&dev);
        cudaDeviceGetAttribute(&sms, cudaDevAttrMultiProcessorCount, dev);
        ncta = sms > 132 ? 132 : (sms > 128 ? sms : 128);
        void* fn = nullptr; cudaDriverEntryPointQueryResult st;
        cudaGetDriverEntryPoint("cuTensorMapEncodeTiled", &fn, cudaEnableDefault, &st);
        enc = (PFN_encodeTiled)fn;
        cudaFuncSetAttribute(fused_kernel, cudaFuncAttributeMaxDynamicSharedMemorySize, SMEM_BYTES);
    }
    CUtensorMap mx, mqkv, mw1, mw2, mwo, mw1a, mo;
    void* optr = nullptr;
    cudaGetSymbolAddress(&optr, g_o);
    { cuuint64_t d[2] = {512, 2048}, s[1] = {1024}; cuuint32_t b[2] = {64, 128}; make_map(enc, &mo, optr, 2, d, s, b); }
    { cuuint64_t d[4] = {64, 512, 3, 8}, s[3] = {3584, 128, 448}; cuuint32_t b[4] = {64, 32, 3, 1}; make_map(enc, &mw1a, w1, 4, d, s, b); }
    { cuuint64_t d[2] = {512, 2048}, s[1] = {1024}; cuuint32_t b[2] = {64, 128}; make_map(enc, &mx, x, 2, d, s, b); }
    { cuuint64_t d[4] = {64, 512, 8, 3}, s[3] = {3072, 128, 1024}; cuuint32_t b[4] = {64, 32, 1, 3}; make_map(enc, &mqkv, wqkv, 4, d, s, b); }
    { cuuint64_t d[2] = {1792, 512}, s[1] = {3584}; cuuint32_t b[2] = {64, 32}; make_map(enc, &mw1, w1, 2, d, s, b); }
    { cuuint64_t d[3] = {64, 1792, 8}, s[2] = {1024, 128}; cuuint32_t b[3] = {64, 32, 2}; make_map(enc, &mw2, w2, 3, d, s, b); }
    { cuuint64_t d[2] = {512, 512}, s[1] = {1024}; cuuint32_t b[2] = {64, 256}; make_map(enc, &mwo, wo, 2, d, s, b); }
    fused_kernel<<<ncta, 384, SMEM_BYTES, cudaStreamPerThread>>>(mx, mqkv, mw1, mw2, mwo, mw1a, mo, (const __nv_bfloat16*)gate_w, (__nv_bfloat16*)d_out,
                                           (const uint8_t*)w1, (const uint8_t*)w2, (const uint8_t*)wo);
}
```

```cpp
#include <cuda_runtime.h>
#include <cuda_bf16.h>
#include <cuda.h>
#include <stdint.h>

namespace {

#define PF1_AT 1
#define PF2_AT 5
#define LEAD1 0
#define OPUB 1
#define OSLEEP 100
constexpr int RING = 6;
constexpr int SLOT = 16384;
constexpr uint32_t X_OFF = 0;
constexpr uint32_t STG_OFF = X_OFF + 4 * 16384;
constexpr uint32_t RING_OFF = 131072;
constexpr uint32_t BAR_OFF = RING_OFF + RING * SLOT;
constexpr uint32_t B_FULL = BAR_OFF, B_EMPTY = BAR_OFF + 64, B_XFULL = BAR_OFF + 128, B_HDEAD = BAR_OFF + 192,
                   B_EREADY = BAR_OFF + 200, B_KVDONE = BAR_OFF + 208, B_ODONE = BAR_OFF + 224,
                   B_KVREADY = BAR_OFF + 232, B_WOFULL = BAR_OFF + 240, B_HSUM = BAR_OFF + 248, B_PREADY = BAR_OFF + 264,
                   B_SQ = BAR_OFF + 272, B_SF = BAR_OFF + 304, B_XDEAD = BAR_OFF + 320;
constexpr uint32_t EPOCH_OFF = BAR_OFF + 256, ITEM_OFF = BAR_OFF + 260;
constexpr uint32_t OWN_OFF = X_OFF + 4 * 16384;
constexpr uint32_t HSUM_OFF = X_OFF + 6 * 16384;
constexpr uint32_t SMEM_BYTES = BAR_OFF + 1024;

constexpr int N_QKV = 16, N_FFN1 = 16, N_FFN2 = 14, N_KV = 8, N_O = 7;

__device__ uint4 g_kf[32 * 128 * 32];
__device__ uint4 g_vf[32 * 128 * 32];
__device__ uint4 g_part[16 * 8 * 8 * 8 * 4 * 32];
__device__ __align__(128) __nv_bfloat16 g_o[2048 * 512];
__device__ unsigned g_ticket;
__device__ unsigned g_kvcnt[128 * 32];
__device__ unsigned g_pcnt[128 * 32];
__device__ unsigned g_ocnt[128 * 32];
#define TS(k) do {} while (0)
#define TS2(k) do {} while (0)
#define TS2X(k) do {} while (0)
#define TSX(k) do {} while (0)
#define TSG(k) do {} while (0)

__device__ __forceinline__ uint32_t smem_u32(const void* p) { return (uint32_t)__cvta_generic_to_shared(p); }
__device__ __forceinline__ void mbar_init(uint32_t bar, uint32_t cnt) { asm volatile("mbarrier.init.shared::cta.b64 [%0], %1;" :: "r"(bar), "r"(cnt) : "memory"); }
__device__ __forceinline__ void mbar_expect_tx(uint32_t bar, uint32_t bytes) { asm volatile("mbarrier.arrive.expect_tx.shared::cta.b64 _, [%0], %1;" :: "r"(bar), "r"(bytes) : "memory"); }
__device__ __forceinline__ void mbar_expect_only(uint32_t bar, uint32_t bytes) { asm volatile("mbarrier.expect_tx.relaxed.cta.shared::cta.b64 [%0], %1;" :: "r"(bar), "r"(bytes) : "memory"); }
__device__ __forceinline__ void mbar_arrive(uint32_t bar) { asm volatile("mbarrier.arrive.shared::cta.b64 _, [%0];" :: "r"(bar) : "memory"); }
__device__ __forceinline__ void mbar_wait(uint32_t bar, uint32_t parity) {
    asm volatile("{\n.reg .pred P1, P2;\n.reg .u32 n;\nmov.u32 n, 0;\n"
                 "WAIT_LOOP:\n"
                 "mbarrier.try_wait.parity.shared::cta.b64 P1, [%0], %1;\n"
                 "@P1 bra WAIT_DONE;\n"
                 "add.u32 n, n, 1;\n"
                 "setp.lt.u32 P2, n, 0x400000;\n"
                 "@P2 bra WAIT_LOOP;\n"
                 "WAIT_DONE:\n}" :: "r"(bar), "r"(parity) : "memory");
}
__device__ __forceinline__ void mbar_wait_idle(uint32_t bar, uint32_t parity) {
    asm volatile("{\n.reg .pred P1, P2;\n.reg .u32 n;\nmov.u32 n, 0;\n"
                 "WAIT_LOOP:\n"
                 "mbarrier.try_wait.parity.shared::cta.b64 P1, [%0], %1, 2000;\n"
                 "@P1 bra WAIT_DONE;\n"
                 "add.u32 n, n, 1;\n"
                 "setp.lt.u32 P2, n, 0x100000;\n"
                 "@P2 bra WAIT_LOOP;\n"
                 "WAIT_DONE:\n}" :: "r"(bar), "r"(parity) : "memory");
}
__device__ __forceinline__ void tma_2d(uint32_t dst, const void* map, uint32_t bar, int c0, int c1) {
    asm volatile("cp.async.bulk.tensor.2d.shared::cluster.global.mbarrier::complete_tx::bytes [%0], [%1, {%3, %4}], [%2];"
        :: "r"(dst), "l"(map), "r"(bar), "r"(c0), "r"(c1) : "memory");
}
__device__ __forceinline__ void tma_3d(uint32_t dst, const void* map, uint32_t bar, int c0, int c1, int c2) {
    asm volatile("cp.async.bulk.tensor.3d.shared::cluster.global.mbarrier::complete_tx::bytes [%0], [%1, {%3, %4, %5}], [%2];"
        :: "r"(dst), "l"(map), "r"(bar), "r"(c0), "r"(c1), "r"(c2) : "memory");
}
__device__ __forceinline__ void tma_4d(uint32_t dst, const void* map, uint32_t bar, int c0, int c1, int c2, int c3) {
    asm volatile("cp.async.bulk.tensor.4d.shared::cluster.global.mbarrier::complete_tx::bytes [%0], [%1, {%3, %4, %5, %6}], [%2];"
        :: "r"(dst), "l"(map), "r"(bar), "r"(c0), "r"(c1), "r"(c2), "r"(c3) : "memory");
}
__device__ __forceinline__ void bulk_g2s(uint32_t dst, const void* src, uint32_t bytes, uint32_t bar) {
    asm volatile("cp.async.bulk.shared::cluster.global.mbarrier::complete_tx::bytes [%0], [%1], %2, [%3];"
        :: "r"(dst), "l"(src), "r"(bytes), "r"(bar) : "memory");
}
__device__ __forceinline__ void prefetch_l2(const void* src, uint32_t bytes) {
    asm volatile("cp.async.bulk.prefetch.L2.global [%0], %1;" :: "l"(src), "r"(bytes) : "memory");
}
__device__ __forceinline__ bool elect_one() {
    uint32_t p;
    asm volatile("{\n.reg .pred P;\nelect.sync _|P, 0xffffffff;\nselp.u32 %0, 1, 0, P;\n}" : "=r"(p));
    return p != 0;
}
__device__ __forceinline__ void wgmma_fence() { asm volatile("wgmma.fence.sync.aligned;" ::: "memory"); }
__device__ __forceinline__ void wgmma_commit() { asm volatile("wgmma.commit_group.sync.aligned;" ::: "memory"); }
template <int N> __device__ __forceinline__ void wgmma_wait() { asm volatile("wgmma.wait_group.sync.aligned %0;" :: "n"(N) : "memory"); }
__device__ __forceinline__ void fence_async_smem() { asm volatile("fence.proxy.async.shared::cta;" ::: "memory"); }
__device__ __forceinline__ uint64_t desc_a(uint32_t addr) {
    return (uint64_t)((addr & 0x3FFFF) >> 4) | ((uint64_t)1 << 16) | ((uint64_t)(1024 >> 4) << 32) | ((uint64_t)1 << 62);
}
__device__ __forceinline__ uint64_t desc_b(uint32_t addr) {
    return (uint64_t)((addr & 0x3FFFF) >> 4) | ((uint64_t)(4096 >> 4) << 16) | ((uint64_t)(1024 >> 4) << 32) | ((uint64_t)1 << 62);
}
__device__ __forceinline__ uint32_t pack_bf16(float lo, float hi) {
    uint32_t r; asm("cvt.rn.bf16x2.f32 %0, %1, %2;" : "=r"(r) : "f"(hi), "f"(lo)); return r;
}
__device__ __forceinline__ uint32_t pack_bf16_relu(float lo, float hi) {
    uint32_t r; asm("cvt.rn.relu.bf16x2.f32 %0, %1, %2;" : "=r"(r) : "f"(hi), "f"(lo)); return r;
}
__device__ __forceinline__ uint32_t movmatrix(uint32_t a) {
    uint32_t d; asm volatile("movmatrix.sync.aligned.m8n8.trans.b16 %0, %1;" : "=r"(d) : "r"(a)); return d;
}
__device__ __forceinline__ void stmatrix_x4(uint32_t addr, uint32_t r0, uint32_t r1, uint32_t r2, uint32_t r3) {
    asm volatile("stmatrix.sync.aligned.m8n8.x4.shared.b16 [%0], {%1, %2, %3, %4};" :: "r"(addr), "r"(r0), "r"(r1), "r"(r2), "r"(r3) : "memory");
}
__device__ __forceinline__ uint4 lds128(uint32_t addr) {
    uint4 v; asm volatile("ld.shared.v4.b32 {%0, %1, %2, %3}, [%4];" : "=r"(v.x), "=r"(v.y), "=r"(v.z), "=r"(v.w) : "r"(addr) : "memory"); return v;
}
__device__ __forceinline__ uint4 lds128_free(uint32_t addr) {
    uint4 v; asm("ld.shared.v4.b32 {%0, %1, %2, %3}, [%4];" : "=r"(v.x), "=r"(v.y), "=r"(v.z), "=r"(v.w) : "r"(addr)); return v;
}
__device__ __forceinline__ void mma16816(float (&c)[4], uint32_t a0, uint32_t a1, uint32_t a2, uint32_t a3, uint32_t b0, uint32_t b1) {
    asm("mma.sync.aligned.m16n8k16.row.col.f32.bf16.bf16.f32 {%0,%1,%2,%3}, {%4,%5,%6,%7}, {%8,%9}, {%0,%1,%2,%3};"
        : "+f"(c[0]), "+f"(c[1]), "+f"(c[2]), "+f"(c[3]) : "r"(a0), "r"(a1), "r"(a2), "r"(a3), "r"(b0), "r"(b1));
}
__device__ __forceinline__ void mma16816_c(float (&c)[4], uint32_t a0, uint32_t a1, uint32_t a2, uint32_t a3, uint32_t b0, uint32_t b1, float ci) {
    asm("mma.sync.aligned.m16n8k16.row.col.f32.bf16.bf16.f32 {%0,%1,%2,%3}, {%4,%5,%6,%7}, {%8,%9}, {%10,%10,%10,%10};"
        : "=f"(c[0]), "=f"(c[1]), "=f"(c[2]), "=f"(c[3]) : "r"(a0), "r"(a1), "r"(a2), "r"(a3), "r"(b0), "r"(b1), "f"(ci));
}
__device__ __forceinline__ int opaque(int v) { asm volatile("" : "+r"(v)); return v; }
__device__ __forceinline__ float ex2(float x) { float y; asm("ex2.approx.ftz.f32 %0, %1;" : "=f"(y) : "f"(x)); return y; }
__device__ __forceinline__ unsigned ld_acquire(const unsigned* p) {
    unsigned v; asm volatile("ld.acquire.gpu.global.u32 %0, [%1];" : "=r"(v) : "l"(p) : "memory"); return v;
}
__device__ __forceinline__ void red_release(unsigned* p, unsigned v) {
    asm volatile("red.release.gpu.global.add.u32 [%0], %1;" :: "l"(p), "r"(v) : "memory");
}
__device__ __forceinline__ void wait_counter(const unsigned* p, unsigned target) {
    uint32_t n = 0;
    while ((int)(ld_acquire(p) - target) < 0) { if (++n > (1u << 20)) break; }
}
__device__ __forceinline__ uint4 ldg_weak(const uint4* p) {
    uint4 v; asm volatile("ld.global.L1::no_allocate.v4.b32 {%0, %1, %2, %3}, [%4];" : "=r"(v.x), "=r"(v.y), "=r"(v.z), "=r"(v.w) : "l"(p) : "memory"); return v;
}
__device__ __forceinline__ float bf_lo(uint32_t v) { return __uint_as_float(v << 16); }
__device__ __forceinline__ float bf_hi(uint32_t v) { return __uint_as_float(v & 0xFFFF0000u); }

__device__ __forceinline__ void wgmma_ss_n64(float (&d)[32], uint64_t da, uint64_t db, int scale_d) {
    asm volatile("{\n.reg .pred p;\nsetp.ne.b32 p, %34, 0;\n"
        "wgmma.mma_async.sync.aligned.m64n64k16.f32.bf16.bf16 {%0, %1, %2, %3, %4, %5, %6, %7, %8, %9, %10, %11, %12, %13, %14, %15, %16, %17, %18, %19, %20, %21, %22, %23, %24, %25, %26, %27, %28, %29, %30, %31}, %32, %33, p, 1, 1, 0, 1;\n}\n"
        : "+f"(d[0]), "+f"(d[1]), "+f"(d[2]), "+f"(d[3]), "+f"(d[4]), "+f"(d[5]), "+f"(d[6]), "+f"(d[7]), "+f"(d[8]), "+f"(d[9]), "+f"(d[10]), "+f"(d[11]), "+f"(d[12]), "+f"(d[13]), "+f"(d[14]), "+f"(d[15]), "+f"(d[16]), "+f"(d[17]), "+f"(d[18]), "+f"(d[19]), "+f"(d[20]), "+f"(d[21]), "+f"(d[22]), "+f"(d[23]), "+f"(d[24]), "+f"(d[25]), "+f"(d[26]), "+f"(d[27]), "+f"(d[28]), "+f"(d[29]), "+f"(d[30]), "+f"(d[31])
        : "l"(da), "l"(db), "r"(scale_d));
}
__device__ __forceinline__ void wgmma_ss_n128(float (&d)[64], uint64_t da, uint64_t db, int scale_d) {
    asm volatile("{\n.reg .pred p;\nsetp.ne.b32 p, %66, 0;\n"
        "wgmma.mma_async.sync.aligned.m64n128k16.f32.bf16.bf16 {%0, %1, %2, %3, %4, %5, %6, %7, %8, %9, %10, %11, %12, %13, %14, %15, %16, %17, %18, %19, %20, %21, %22, %23, %24, %25, %26, %27, %28, %29, %30, %31, %32, %33, %34, %35, %36, %37, %38, %39, %40, %41, %42, %43, %44, %45, %46, %47, %48, %49, %50, %51, %52, %53, %54, %55, %56, %57, %58, %59, %60, %61, %62, %63}, %64, %65, p, 1, 1, 0, 1;\n}\n"
        : "+f"(d[0]), "+f"(d[1]), "+f"(d[2]), "+f"(d[3]), "+f"(d[4]), "+f"(d[5]), "+f"(d[6]), "+f"(d[7]), "+f"(d[8]), "+f"(d[9]), "+f"(d[10]), "+f"(d[11]), "+f"(d[12]), "+f"(d[13]), "+f"(d[14]), "+f"(d[15]), "+f"(d[16]), "+f"(d[17]), "+f"(d[18]), "+f"(d[19]), "+f"(d[20]), "+f"(d[21]), "+f"(d[22]), "+f"(d[23]), "+f"(d[24]), "+f"(d[25]), "+f"(d[26]), "+f"(d[27]), "+f"(d[28]), "+f"(d[29]), "+f"(d[30]), "+f"(d[31]), "+f"(d[32]), "+f"(d[33]), "+f"(d[34]), "+f"(d[35]), "+f"(d[36]), "+f"(d[37]), "+f"(d[38]), "+f"(d[39]), "+f"(d[40]), "+f"(d[41]), "+f"(d[42]), "+f"(d[43]), "+f"(d[44]), "+f"(d[45]), "+f"(d[46]), "+f"(d[47]), "+f"(d[48]), "+f"(d[49]), "+f"(d[50]), "+f"(d[51]), "+f"(d[52]), "+f"(d[53]), "+f"(d[54]), "+f"(d[55]), "+f"(d[56]), "+f"(d[57]), "+f"(d[58]), "+f"(d[59]), "+f"(d[60]), "+f"(d[61]), "+f"(d[62]), "+f"(d[63])
        : "l"(da), "l"(db), "r"(scale_d));
}
__device__ __forceinline__ void wgmma_ss_n200(float (&d)[100], uint64_t da, uint64_t db, int scale_d) {
    asm volatile("{\n.reg .pred p;\nsetp.ne.b32 p, %102, 0;\n"
        "wgmma.mma_async.sync.aligned.m64n200k16.f32.bf16.bf16 {%0, %1, %2, %3, %4, %5, %6, %7, %8, %9, %10, %11, %12, %13, %14, %15, %16, %17, %18, %19, %20, %21, %22, %23, %24, %25, %26, %27, %28, %29, %30, %31, %32, %33, %34, %35, %36, %37, %38, %39, %40, %41, %42, %43, %44, %45, %46, %47, %48, %49, %50, %51, %52, %53, %54, %55, %56, %57, %58, %59, %60, %61, %62, %63, %64, %65, %66, %67, %68, %69, %70, %71, %72, %73, %74, %75, %76, %77, %78, %79, %80, %81, %82, %83, %84, %85, %86, %87, %88, %89, %90, %91, %92, %93, %94, %95, %96, %97, %98, %99}, %100, %101, p, 1, 1, 0, 1;\n}\n"
        : "+f"(d[0]), "+f"(d[1]), "+f"(d[2]), "+f"(d[3]), "+f"(d[4]), "+f"(d[5]), "+f"(d[6]), "+f"(d[7]), "+f"(d[8]), "+f"(d[9]), "+f"(d[10]), "+f"(d[11]), "+f"(d[12]), "+f"(d[13]), "+f"(d[14]), "+f"(d[15]), "+f"(d[16]), "+f"(d[17]), "+f"(d[18]), "+f"(d[19]), "+f"(d[20]), "+f"(d[21]), "+f"(d[22]), "+f"(d[23]), "+f"(d[24]), "+f"(d[25]), "+f"(d[26]), "+f"(d[27]), "+f"(d[28]), "+f"(d[29]), "+f"(d[30]), "+f"(d[31]), "+f"(d[32]), "+f"(d[33]), "+f"(d[34]), "+f"(d[35]), "+f"(d[36]), "+f"(d[37]), "+f"(d[38]), "+f"(d[39]), "+f"(d[40]), "+f"(d[41]), "+f"(d[42]), "+f"(d[43]), "+f"(d[44]), "+f"(d[45]), "+f"(d[46]), "+f"(d[47]), "+f"(d[48]), "+f"(d[49]), "+f"(d[50]), "+f"(d[51]), "+f"(d[52]), "+f"(d[53]), "+f"(d[54]), "+f"(d[55]), "+f"(d[56]), "+f"(d[57]), "+f"(d[58]), "+f"(d[59]), "+f"(d[60]), "+f"(d[61]), "+f"(d[62]), "+f"(d[63]), "+f"(d[64]), "+f"(d[65]), "+f"(d[66]), "+f"(d[67]), "+f"(d[68]), "+f"(d[69]), "+f"(d[70]), "+f"(d[71]), "+f"(d[72]), "+f"(d[73]), "+f"(d[74]), "+f"(d[75]), "+f"(d[76]), "+f"(d[77]), "+f"(d[78]), "+f"(d[79]), "+f"(d[80]), "+f"(d[81]), "+f"(d[82]), "+f"(d[83]), "+f"(d[84]), "+f"(d[85]), "+f"(d[86]), "+f"(d[87]), "+f"(d[88]), "+f"(d[89]), "+f"(d[90]), "+f"(d[91]), "+f"(d[92]), "+f"(d[93]), "+f"(d[94]), "+f"(d[95]), "+f"(d[96]), "+f"(d[97]), "+f"(d[98]), "+f"(d[99])
        : "l"(da), "l"(db), "r"(scale_d));
}
__device__ __forceinline__ void wgmma_ss_n224(float (&d)[112], uint64_t da, uint64_t db, int scale_d) {
    asm volatile("{\n.reg .pred p;\nsetp.ne.b32 p, %114, 0;\n"
        "wgmma.mma_async.sync.aligned.m64n224k16.f32.bf16.bf16 {%0, %1, %2, %3, %4, %5, %6, %7, %8, %9, %10, %11, %12, %13, %14, %15, %16, %17, %18, %19, %20, %21, %22, %23, %24, %25, %26, %27, %28, %29, %30, %31, %32, %33, %34, %35, %36, %37, %38, %39, %40, %41, %42, %43, %44, %45, %46, %47, %48, %49, %50, %51, %52, %53, %54, %55, %56, %57, %58, %59, %60, %61, %62, %63, %64, %65, %66, %67, %68, %69, %70, %71, %72, %73, %74, %75, %76, %77, %78, %79, %80, %81, %82, %83, %84, %85, %86, %87, %88, %89, %90, %91, %92, %93, %94, %95, %96, %97, %98, %99, %100, %101, %102, %103, %104, %105, %106, %107, %108, %109, %110, %111}, %112, %113, p, 1, 1, 0, 1;\n}\n"
        : "+f"(d[0]), "+f"(d[1]), "+f"(d[2]), "+f"(d[3]), "+f"(d[4]), "+f"(d[5]), "+f"(d[6]), "+f"(d[7]), "+f"(d[8]), "+f"(d[9]), "+f"(d[10]), "+f"(d[11]), "+f"(d[12]), "+f"(d[13]), "+f"(d[14]), "+f"(d[15]), "+f"(d[16]), "+f"(d[17]), "+f"(d[18]), "+f"(d[19]), "+f"(d[20]), "+f"(d[21]), "+f"(d[22]), "+f"(d[23]), "+f"(d[24]), "+f"(d[25]), "+f"(d[26]), "+f"(d[27]), "+f"(d[28]), "+f"(d[29]), "+f"(d[30]), "+f"(d[31]), "+f"(d[32]), "+f"(d[33]), "+f"(d[34]), "+f"(d[35]), "+f"(d[36]), "+f"(d[37]), "+f"(d[38]), "+f"(d[39]), "+f"(d[40]), "+f"(d[41]), "+f"(d[42]), "+f"(d[43]), "+f"(d[44]), "+f"(d[45]), "+f"(d[46]), "+f"(d[47]), "+f"(d[48]), "+f"(d[49]), "+f"(d[50]), "+f"(d[51]), "+f"(d[52]), "+f"(d[53]), "+f"(d[54]), "+f"(d[55]), "+f"(d[56]), "+f"(d[57]), "+f"(d[58]), "+f"(d[59]), "+f"(d[60]), "+f"(d[61]), "+f"(d[62]), "+f"(d[63]), "+f"(d[64]), "+f"(d[65]), "+f"(d[66]), "+f"(d[67]), "+f"(d[68]), "+f"(d[69]), "+f"(d[70]), "+f"(d[71]), "+f"(d[72]), "+f"(d[73]), "+f"(d[74]), "+f"(d[75]), "+f"(d[76]), "+f"(d[77]), "+f"(d[78]), "+f"(d[79]), "+f"(d[80]), "+f"(d[81]), "+f"(d[82]), "+f"(d[83]), "+f"(d[84]), "+f"(d[85]), "+f"(d[86]), "+f"(d[87]), "+f"(d[88]), "+f"(d[89]), "+f"(d[90]), "+f"(d[91]), "+f"(d[92]), "+f"(d[93]), "+f"(d[94]), "+f"(d[95]), "+f"(d[96]), "+f"(d[97]), "+f"(d[98]), "+f"(d[99]), "+f"(d[100]), "+f"(d[101]), "+f"(d[102]), "+f"(d[103]), "+f"(d[104]), "+f"(d[105]), "+f"(d[106]), "+f"(d[107]), "+f"(d[108]), "+f"(d[109]), "+f"(d[110]), "+f"(d[111])
        : "l"(da), "l"(db), "r"(scale_d));
}
template <int N> __device__ __forceinline__ void fence_acc(float (&d)[N]) {
#pragma unroll
    for (int i = 0; i < N; i++) asm volatile("" : "+f"(d[i]) :: "memory");
}

__device__ __forceinline__ void bulk_s2g(void* dst, uint32_t src, uint32_t bytes) {
    asm volatile("cp.async.bulk.global.shared::cta.bulk_group [%0], [%1], %2;" :: "l"(dst), "r"(src), "r"(bytes) : "memory");
}
__device__ __forceinline__ void sts128(uint32_t addr, uint4 v) {
    asm volatile("st.shared.v4.b32 [%0], {%1, %2, %3, %4};" :: "r"(addr), "r"(v.x), "r"(v.y), "r"(v.z), "r"(v.w) : "memory");
}
__device__ __forceinline__ void sum_partials(uint32_t sb, int ti, int tj, int lane) {
    for (;;) {
        uint32_t item = 0;
        if (lane == 0) asm volatile("atom.shared.add.u32 %0, [%1], 1;" : "=r"(item) : "r"(sb + ITEM_OFF) : "memory");
        item = __shfl_sync(0xffffffffu, item, 0);
        if (item >= 8) break;
        const uint4* p = g_part + (size_t)((ti * 8 + tj) * 8) * 1024 + item * 128 + lane;
        uint4 v[4][4];
#pragma unroll
        for (int s = 0; s < 4; s++)
#pragma unroll
            for (int n = 0; n < 4; n++) v[n][s] = ldg_weak(p + s * 1024 + n * 32);
#pragma unroll
        for (int n = 0; n < 4; n++) {
            float a[8];
#pragma unroll
            for (int e = 0; e < 8; e++) a[e] = 0.f;
#pragma unroll
            for (int s = 0; s < 4; s++) {
                a[0] += bf_lo(v[n][s].x); a[1] += bf_hi(v[n][s].x); a[2] += bf_lo(v[n][s].y); a[3] += bf_hi(v[n][s].y);
                a[4] += bf_lo(v[n][s].z); a[5] += bf_hi(v[n][s].z); a[6] += bf_lo(v[n][s].w); a[7] += bf_hi(v[n][s].w);
            }
            const uint32_t d = sb + HSUM_OFF + (item * 8 + n * 2) * 512 + lane * 16;
            sts128(d, make_uint4(__float_as_uint(a[0]), __float_as_uint(a[1]), __float_as_uint(a[2]), __float_as_uint(a[3])));
            sts128(d + 512, make_uint4(__float_as_uint(a[4]), __float_as_uint(a[5]), __float_as_uint(a[6]), __float_as_uint(a[7])));
        }
    }
    __syncwarp();
    if (lane == 0) mbar_arrive(sb + B_HSUM);
}

#define PWAIT() mbar_wait_idle(sb + B_EMPTY + 8 * r.slot, r.phase)
#define CWAIT() do { if (!dry) mbar_wait(sb + B_FULL + 8 * r.slot, r.phase); } while (0)
template <bool B> struct BoolTag { static constexpr bool value = B; };
struct Ring {
    int slot; uint32_t phase;
    __device__ __forceinline__ void next() { if (++slot == RING) { slot = 0; phase ^= 1; } }
};

__global__ void __launch_bounds__(384, 1)
fused_kernel(const __grid_constant__ CUtensorMap map_x, const __grid_constant__ CUtensorMap map_qkv,
             const __grid_constant__ CUtensorMap map_w1, const __grid_constant__ CUtensorMap map_w2,
             const __grid_constant__ CUtensorMap map_wo, const __grid_constant__ CUtensorMap map_w1a,
             const __grid_constant__ CUtensorMap map_o,
             const __nv_bfloat16* __restrict__ gate_w, __nv_bfloat16* __restrict__ out,
             const uint8_t* __restrict__ w1p, const uint8_t* __restrict__ w2p, const uint8_t* __restrict__ wop)
{
    extern __shared__ __align__(1024) uint8_t smem_raw[];
    const uint32_t sb = smem_u32(smem_raw);
    const int tid = threadIdx.x, warp = tid >> 5, lane = tid & 31;
    const bool dry = blockIdx.x >= 128;
    const int ti = dry ? (int)(blockIdx.x & 1) * 2 : blockIdx.x >> 3, tj = blockIdx.x & 7;
    if (dry && warp >= 8) {
        asm volatile("setmaxnreg.dec.sync.aligned.u32 88;");
        return;
    }

    if (tid == 0 && !dry) { TSG(31); TSX(0); }
    uint32_t gwv[N_QKV / 2];
    if (warp == 8) {
        const unsigned short* gws = reinterpret_cast<const unsigned short*>(gate_w);
#pragma unroll
        for (int n = 0; n < N_QKV / 2; n++) gwv[n] = (uint32_t)__ldg(gws + 64 * n + lane) | ((uint32_t)__ldg(gws + 64 * n + 32 + lane) << 16);
    }
    if (tid == 321) {
        asm volatile("prefetch.tensormap [%0];" :: "l"(&map_x) : "memory");
        asm volatile("prefetch.tensormap [%0];" :: "l"(&map_qkv) : "memory");
        asm volatile("prefetch.tensormap [%0];" :: "l"(&map_w1) : "memory");
        asm volatile("prefetch.tensormap [%0];" :: "l"(&map_w1a) : "memory");
        asm volatile("prefetch.tensormap [%0];" :: "l"(&map_w2) : "memory");
        asm volatile("prefetch.tensormap [%0];" :: "l"(&map_wo) : "memory");
        asm volatile("prefetch.tensormap [%0];" :: "l"(&map_o) : "memory");
    }
    if (tid == 288) {
        mbar_init(sb + B_FULL, 1); mbar_init(sb + B_XFULL, 1);
        fence_async_smem();
        mbar_expect_tx(sb + B_XFULL, 16384);
        tma_2d(sb + X_OFF, &map_x, sb + B_XFULL, 0, ti * 128);
        mbar_expect_only(sb + B_FULL, 12288);
        tma_4d(sb + RING_OFF, &map_qkv, sb + B_FULL, 0, 0, tj, 0);
    }
    if (tid == 320) {
        for (int s = 1; s < RING; s++) mbar_init(sb + B_FULL + 8 * s, 1);
        for (int s = 0; s < RING; s++) mbar_init(sb + B_EMPTY + 8 * s, 8);
        for (int s = 1; s < 8; s++) mbar_init(sb + B_XFULL + 8 * s, 1);
        fence_async_smem();
    }
    if (tid == 352) {
        mbar_init(sb + B_HDEAD, 8); mbar_init(sb + B_EREADY, 1); mbar_init(sb + B_KVDONE, 8); mbar_init(sb + B_KVREADY, 1);
        mbar_init(sb + B_ODONE, 8); mbar_init(sb + B_WOFULL, 1); mbar_init(sb + B_HSUM, 3);
        mbar_init(sb + B_XDEAD, 8); mbar_init(sb + B_PREADY, 1); mbar_init(sb + B_SF, 1); mbar_init(sb + B_SF + 8, 1);
        for (int s = 0; s < 4; s++) mbar_init(sb + B_SQ + 8 * s, 8);
        asm volatile("st.shared.u32 [%0], %1;" :: "r"(sb + ITEM_OFF), "r"(0) : "memory");
        fence_async_smem();
    }
    if (!dry) __syncthreads();

    if (warp >= 8) {
        asm volatile("setmaxnreg.dec.sync.aligned.u32 88;");
        if (warp == 8) {
            Ring r{0, 1};
            const bool leader = elect_one();
            if (leader) {
#pragma unroll
                for (int n = 1; n < RING; n++) {
                    if (!(n & 1)) {
                        mbar_expect_tx(sb + B_XFULL + 8 * (n >> 1), 16384);
                        tma_2d(sb + X_OFF + (n >> 1) * 16384, &map_x, sb + B_XFULL + 8 * (n >> 1), (n >> 1) * 64, ti * 128);
                    }
                    mbar_expect_only(sb + B_FULL + 8 * n, 12288);
                    tma_4d(sb + RING_OFF + n * SLOT, &map_qkv, sb + B_FULL + 8 * n, 0, 32 * n, tj, 0);
                }
            }
#pragma unroll
            for (int n = 0; n < N_QKV; n++) {
                const uint32_t full = sb + B_FULL + 8 * r.slot, dst = sb + RING_OFF + r.slot * SLOT;
                if (n >= RING) {
                    if (!(n & 1) && leader) {
                        mbar_expect_tx(sb + B_XFULL + 8 * (n >> 1), 16384);
                        tma_2d(sb + X_OFF + (n >> 1) * 16384, &map_x, sb + B_XFULL + 8 * (n >> 1), (n >> 1) * 64, ti * 128);
                    }
                    PWAIT();
                    if (leader) {
                        mbar_expect_only(full, 12288);
                        tma_4d(dst, &map_qkv, full, 0, 32 * n, tj, 0);
                    }
                }
                const uint32_t gv = (n & 1) ? (gwv[n >> 1] >> 16) : (gwv[n >> 1] & 0xFFFFu);
                asm volatile("st.shared.v4.b32 [%0], {%1, %2, %2, %2};" :: "r"(dst + 12288 + lane * 128 + ((lane & 7) << 4)), "r"(gv), "r"(0) : "memory");
                fence_async_smem();
                __syncwarp();
                if (leader) mbar_arrive(full);
                r.next();
            }
#pragma unroll 1
            for (int n = 0; n < N_FFN1; n++) {
                const uint32_t full = sb + B_FULL + 8 * r.slot, dst = sb + RING_OFF + r.slot * SLOT;
                PWAIT();
                if (leader) {
                    mbar_expect_tx(full, 16384);
                    tma_4d(dst, &map_w1a, full, 0, 32 * n, 0, tj);
                    tma_2d(dst + 3 * 4096, &map_w1, full, 224 * tj + 192, 32 * n);
                }
                r.next();
            }
            {
                int q = 0, rr = 0;
#pragma unroll 1
                for (int n = 0; n < N_FFN2; n++) {
                    const uint32_t full = sb + B_FULL + 8 * r.slot, dst = sb + RING_OFF + r.slot * SLOT;
                    PWAIT();
                    if (leader) mbar_expect_tx(full, 16384);
#pragma unroll
                    for (int h = 0; h < 2; h++) {
                        if (leader) tma_3d(dst + h * 8192, &map_w2, full, 0, 224 * tj + 32 * rr, 2 * q);
                        if (++rr == 7) { rr = 0; q++; }
                    }
                    r.next();
                }
            }
            mbar_wait_idle(sb + B_KVREADY, 0);
            asm volatile("fence.proxy.async.global;" ::: "memory");
            {
                const int bbase = 8 * ti - 16, b0 = bbase < 0 ? 0 : bbase;
                const uint32_t bytes = (uint32_t)(8 * ti + 8 - b0) * 512;
#pragma unroll 1
                for (int m = 0; m < N_KV; m++) {
                    const uint32_t full = sb + B_FULL + 8 * r.slot, dst = sb + RING_OFF + r.slot * SLOT;
                    if (m == RING) {
                        mbar_wait_idle(sb + B_HDEAD, 0);
                        if (leader) {
                            mbar_expect_tx(sb + B_WOFULL, 65536);
#pragma unroll
                            for (int e = 0; e < 2; e++) tma_2d(sb + X_OFF + e * 32768, &map_wo, sb + B_WOFULL, 64 * tj, 256 * e);
                        }
                    }
                    PWAIT();
                    if (leader) {
                        const uint4* src = ((m & 1) ? g_vf : g_kf) + ((tj * 4 + (m >> 1)) * 128 + b0) * 32;
                        mbar_expect_tx(full, bytes);
                        bulk_g2s(dst + (b0 - bbase) * 512, src, bytes, full);
                    }
                    r.next();
                }
            }
            {
                mbar_wait_idle(sb + B_EREADY, 0);
                unsigned epoch; asm volatile("ld.shared.u32 %0, [%1];" : "=r"(epoch) : "r"(sb + EPOCH_OFF) : "memory");
                uint32_t ready = 0;
                mbar_wait_idle(sb + B_HSUM, 0);
#pragma unroll 1
                for (int m = 0; m < N_O; m++) {
                    const uint32_t full = sb + B_FULL + 8 * r.slot, dst = sb + RING_OFF + r.slot * SLOT;
                    PWAIT();
                    const int js = (tj + 1 + m) & 7;
                    for (int it = 0; it < (1 << 20) && !((ready >> js) & 1); it++) {
                        bool ok = false;
                        if (lane < 8) ok = (int)(ld_acquire(&g_ocnt[(ti * 8 + lane) * 32]) - OPUB * (epoch + 1)) >= 0;
                        ready = __ballot_sync(0xffffffffu, ok);
                        if (!((ready >> js) & 1)) __nanosleep(OSLEEP);
                    }
                    asm volatile("fence.proxy.async.global;" ::: "memory");
                    if (leader) {
                        mbar_expect_tx(full, 16384);
                        tma_2d(dst, &map_o, full, 64 * js, ti * 128);
                    }
                    r.next();
                }
            }
        } else if (warp == 9) {
            unsigned epoch = 0;
            if (lane == 0) {
                epoch = atomicAdd(&g_ticket, 1u) >> 7;
                asm volatile("st.shared.u32 [%0], %1;" :: "r"(sb + EPOCH_OFF), "r"(epoch) : "memory");
                mbar_arrive(sb + B_EREADY);
                mbar_wait_idle(sb + B_XFULL + 8 * PF1_AT, 0);
                prefetch_l2(w1p + (size_t)blockIdx.x * 14336, 14336);
                mbar_wait_idle(sb + B_XFULL + 8 * PF2_AT, 0);
                prefetch_l2(w2p + (size_t)blockIdx.x * 14336, 14336);
                prefetch_l2(wop + (size_t)blockIdx.x * 4096, 4096);
                mbar_wait_idle(sb + B_KVDONE, 0);
                red_release(&g_kvcnt[blockIdx.x * 32], 1u);
            }
            epoch = __shfl_sync(0xffffffffu, epoch, 0);
            if (lane < 3 && ti - lane >= 0) wait_counter(&g_kvcnt[((ti - lane) * 8 + tj) * 32], epoch + 1);
            __syncwarp();
            if (lane == 0) mbar_arrive(sb + B_KVREADY);
            mbar_wait_idle(sb + B_SQ + 24, 0);
            if (lane < 8) wait_counter(&g_pcnt[(ti * 8 + lane) * 32], epoch + 1);
            __syncwarp();
            if (lane == 0) { mbar_arrive(sb + B_PREADY); TSX(13); }
            sum_partials(sb, ti, tj, lane);
            if (lane == 0) TSX(14);
        } else {
            if (warp == 10) {
#pragma unroll 1
                for (int q = 0; q < 4; q++) {
                    mbar_wait_idle(sb + B_SQ + 8 * q, 0);
                    if (lane < 16) {
                        uint4* d = g_part + (size_t)(((ti * 8 + 2 * q + (lane & 1)) * 8 + tj) * 8 + (lane >> 1)) * 128;
                        bulk_s2g(d, sb + STG_OFF + (q & 1) * 32768 + lane * 2048, 2048);
                        asm volatile("cp.async.bulk.commit_group;" ::: "memory");
                        asm volatile("cp.async.bulk.wait_group.read 0;" ::: "memory");
                    }
                    __syncwarp();
                    if (lane == 0) mbar_arrive(sb + B_SF + 8 * (q & 1));
                }
                asm volatile("cp.async.bulk.wait_group 0;" ::: "memory");
                asm volatile("fence.proxy.async.global;" ::: "memory");
                __syncwarp();
                if (lane == 0) { red_release(&g_pcnt[blockIdx.x * 32], 1u); TSX(12); }
            }
            mbar_wait_idle(sb + B_PREADY, 0);
            sum_partials(sb, ti, tj, lane);
            if (warp == 11 && lane == 0) {
                mbar_wait_idle(sb + B_ODONE, 0);
                red_release(&g_ocnt[blockIdx.x * 32], 1u);
            }
        }
    } else {
        asm volatile("setmaxnreg.inc.sync.aligned.u32 208;");
        const int wg = warp >> 2, g = lane >> 2, c = lane & 3;
        const uint32_t xa = sb + X_OFF + wg * 8192;
        Ring r{0, 0};
        const bool lane0 = lane == 0 && !dry;
        uint32_t qf[4][4];
        float g0, g1;
        TS(9);
        {
            float acc[100];
            int prev = 0;
            if (wg == 1) asm volatile("bar.sync 3, 256;" ::: "memory");
            for (int s = 0; s < (dry ? 4 : N_QKV); s++) {
                if (!(s & 1) && !dry) mbar_wait(sb + B_XFULL + 8 * (s >> 1), 0);
                CWAIT();
                if (s == 0) TS(1);
                if (s == 2) TS(28);
                if (s == 6) TS(29);
                if (s == 10) TS(20);
                const uint32_t bs = sb + RING_OFF + r.slot * SLOT, as = xa + (s >> 1) * 16384 + (s & 1) * 64;
                wgmma_fence();
                wgmma_ss_n200(acc, desc_a(as), desc_b(bs), s);
                wgmma_ss_n200(acc, desc_a(as + 32), desc_b(bs + 2048), 1);
                wgmma_commit();
                if (wg == 0 && s == LEAD1) asm volatile("bar.arrive 3, 256;" ::: "memory");
                if (s > 0) { wgmma_wait<1>(); if (lane0) mbar_arrive(sb + B_EMPTY + 8 * prev); }
                prev = r.slot; r.next();
            }
            wgmma_wait<0>();
            fence_acc(acc);
            if (lane0) mbar_arrive(sb + B_EMPTY + 8 * prev);
            TS(2);
            const int blk = ti * 8 + warp;
#pragma unroll
            for (int hh = 0; hh < 4; hh++) {
                const float* t0 = &acc[8 * hh]; const float* t1 = &acc[8 * hh + 4];
                qf[hh][0] = pack_bf16(t0[0], t0[1]); qf[hh][1] = pack_bf16(t0[2], t0[3]);
                qf[hh][2] = pack_bf16(t1[0], t1[1]); qf[hh][3] = pack_bf16(t1[2], t1[3]);
                const float* k0 = &acc[32 + 8 * hh]; const float* k1 = &acc[32 + 8 * hh + 4];
                uint4 kv;
                kv.x = pack_bf16(k0[0], k0[1]); kv.y = pack_bf16(k1[0], k1[1]);
                kv.z = pack_bf16(k0[2], k0[3]); kv.w = pack_bf16(k1[2], k1[3]);
                if (!dry) g_kf[((tj * 4 + hh) * 128 + blk) * 32 + lane] = kv;
                const float* v0 = &acc[64 + 8 * hh]; const float* v1 = &acc[64 + 8 * hh + 4];
                uint4 vv;
                vv.x = movmatrix(pack_bf16(v0[0], v0[1])); vv.y = movmatrix(pack_bf16(v0[2], v0[3]));
                vv.z = movmatrix(pack_bf16(v1[0], v1[1])); vv.w = movmatrix(pack_bf16(v1[2], v1[3]));
                if (!dry) g_vf[((tj * 4 + hh) * 128 + blk) * 32 + lane] = vv;
            }
            __syncwarp();
            if (lane0) mbar_arrive(sb + B_KVDONE);
            const float z0 = __shfl_sync(0xffffffffu, acc[96], lane & ~3), z1 = __shfl_sync(0xffffffffu, acc[98], lane & ~3);
            g0 = 1.f / (1.f + __expf(-z0)); g1 = 1.f / (1.f + __expf(-z1));
        }
        TS(3);
        const int wrow = (warp & 3) * 16;
        {
            float acc[112];
            int prev = 0;
            for (int s = 0; s < (dry ? 4 : N_FFN1); s++) {
                CWAIT();
                const uint32_t bs = sb + RING_OFF + r.slot * SLOT, as = xa + (s >> 1) * 16384 + (s & 1) * 64;
                wgmma_fence();
                wgmma_ss_n224(acc, desc_a(as), desc_b(bs), s);
                wgmma_ss_n224(acc, desc_a(as + 32), desc_b(bs + 2048), 1);
                wgmma_commit();
                if (s > 0) { wgmma_wait<1>(); if (lane0) mbar_arrive(sb + B_EMPTY + 8 * prev); }
                prev = r.slot; r.next();
            }
            wgmma_wait<0>();
            fence_acc(acc);
            if (lane0) { mbar_arrive(sb + B_EMPTY + 8 * prev); mbar_arrive(sb + B_XDEAD); }
            TS(4);
            const float s0 = 1.f - g0, s1 = 1.f - g1;
            asm volatile("bar.sync %0, 128;" :: "r"(1 + wg) : "memory");
            const uint32_t strow = xa + (wrow + ((lane >> 3) & 1) * 8 + (lane & 7)) * 128;
#pragma unroll
            for (int p = 0; p < 14; p++) {
                const int nt = 2 * p + (lane >> 4);
                const float* a = &acc[8 * p];
                stmatrix_x4(strow + (p >> 2) * 16384 + (((nt & 7) ^ (lane & 7)) << 4),
                            pack_bf16_relu(a[0] * s0, a[1] * s0), pack_bf16_relu(a[2] * s1, a[3] * s1),
                            pack_bf16_relu(a[4] * s0, a[5] * s0), pack_bf16_relu(a[6] * s1, a[7] * s1));
            }
        }
        TS(5);
        {
            fence_async_smem();
            asm volatile("bar.sync %0, 128;" :: "r"(1 + wg) : "memory");
            float accA[64], accB[64];
            auto epilogue = [&](float (&acc)[64], int q) {
                fence_acc(acc);
                const uint32_t st = sb + STG_OFF + (q & 1) * 32768 + warp * 4096;
                if (q == 0 && !dry) mbar_wait(sb + B_XDEAD, 0);
                if (q >= 2 && !dry) mbar_wait(sb + B_SF + 8 * (q & 1), 0);
#pragma unroll
                for (int t2 = 0; t2 < 8; t2++) {
                    uint4 v;
                    v.x = pack_bf16(acc[8 * t2 + 0], acc[8 * t2 + 1]); v.y = pack_bf16(acc[8 * t2 + 2], acc[8 * t2 + 3]);
                    v.z = pack_bf16(acc[8 * t2 + 4], acc[8 * t2 + 5]); v.w = pack_bf16(acc[8 * t2 + 6], acc[8 * t2 + 7]);
                    sts128(st + t2 * 512 + lane * 16, v);
                }
                fence_async_smem();
                __syncwarp();
                if (lane0) mbar_arrive(sb + B_SQ + 8 * q);
            };
            int rel = r.slot;
#pragma unroll
            for (int m = 0; m < N_FFN2; m++) {
                CWAIT();
                wgmma_fence();
#pragma unroll
                for (int h = 0; h < 2; h++) {
                    const int u = 2 * m + h, q = u / 7, rr = u % 7;
                    const uint32_t bs = sb + RING_OFF + r.slot * SLOT + h * 8192;
                    const uint32_t as = xa + (rr >> 1) * 16384 + (rr & 1) * 64;
                    if (!(q & 1)) {
                        wgmma_ss_n128(accA, desc_a(as), desc_b(bs), rr);
                        wgmma_ss_n128(accA, desc_a(as + 32), desc_b(bs + 2048), 1);
                    } else {
                        wgmma_ss_n128(accB, desc_a(as), desc_b(bs), rr);
                        wgmma_ss_n128(accB, desc_a(as + 32), desc_b(bs + 2048), 1);
                    }
                }
                wgmma_commit();
                r.next();
                wgmma_wait<1>();
                if (m > 0) {
                    if (lane0) mbar_arrive(sb + B_EMPTY + 8 * rel);
                    if (++rel == RING) rel = 0;
                }
                if (m == 4) { TS(25); epilogue(accA, 0); }
                if (m == 7) { TS(26); epilogue(accB, 1); }
                if (m == 11) { TS(27); epilogue(accA, 2); }
            }
            wgmma_wait<0>();
            if (lane0) { mbar_arrive(sb + B_EMPTY + 8 * rel); mbar_arrive(sb + B_HDEAD); }
            epilogue(accB, 3);
        }
        TS(6);
        {
            const float SC = 0.25f * 1.4426950408889634f;
            const int gb0 = 8 * ti - 16 + warp;
            int slotK = 0, slotV = 0;
            const uint32_t ostore = sb + OWN_OFF + (warp * 16 + ((lane >> 3) & 1) * 8 + (lane & 7)) * 128;
            uint32_t* odst = reinterpret_cast<uint32_t*>(g_o + (size_t)(ti * 128 + warp * 16 + g) * 512 + tj * 64 + ((lane & 1) ? 8 : 0) + (lane & 2) * 2);
#define NHEADS (dry ? 2 : 4)
#define ATT_KWAIT(kb) do { slotK = r.slot; CWAIT(); kb = sb + RING_OFF + slotK * SLOT + warp * 512 + lane * 16; r.next(); } while (0)
#define ATT_VWAIT(vb) do { slotV = r.slot; CWAIT(); vb = sb + RING_OFF + slotV * SLOT + warp * 512 + lane * 16; r.next(); TS(21 + hh); } while (0)
#define ATT_KVREL() do { __syncwarp(); if (lane0) { mbar_arrive(sb + B_EMPTY + 8 * slotK); mbar_arrive(sb + B_EMPTY + 8 * slotV); } } while (0)
#define ATT_NEXTQ(h) do { \
                if ((h) == 1) { q0 = qf[1][0]; q1 = qf[1][1]; q2 = qf[1][2]; q3 = qf[1][3]; } \
                else if ((h) == 2) { q0 = qf[2][0]; q1 = qf[2][1]; q2 = qf[2][2]; q3 = qf[2][3]; } \
                else { q0 = qf[3][0]; q1 = qf[3][1]; q2 = qf[3][2]; q3 = qf[3][3]; } } while (0)
#define ATT_STORE(h, r0, r1, r2, r3) do { \
                if ((h) == 0 && !dry) mbar_wait(sb + B_SF, 1);        \
                stmatrix_x4(ostore + (((2 * (h) + (lane >> 4)) ^ (lane & 7)) << 4), r0, r1, r2, r3); \
                const bool odd = lane & 1; \
                const uint32_t sl = __shfl_xor_sync(0xffffffffu, odd ? (r0) : (r2), 1), sh = __shfl_xor_sync(0xffffffffu, odd ? (r1) : (r3), 1); \
                if (!dry) *reinterpret_cast<uint2*>(odst + 8 * (h)) = odd ? make_uint2(sl, r2) : make_uint2(r0, sl); \
                if (!dry) *reinterpret_cast<uint2*>(odst + 8 * (h) + 8 * 256) = odd ? make_uint2(sh, r3) : make_uint2(r1, sh); \
                } while (0)
            auto attention = [&](auto masked_tag) {
            constexpr bool MASKED = decltype(masked_tag)::value;
            const float NEG = -INFINITY;
            const uint32_t ONES = 0x3F803F80u;
            float sa[8][2][4];
            float o[2][4], ls[4];
            float m0, m1;
            uint32_t q0 = qf[0][0], q1 = qf[0][1], q2 = qf[0][2], q3 = qf[0][3];
            auto qk = [&](float (&s)[8][2][4], int ps, int t, uint32_t kbase, bool merged) {
                if (merged) {
                    const uint4 kd = lds128_free(kbase + 16 * 512);
                    const uint4 kf = lds128_free(kbase);
                    float f[2][4];
                    const float ci = (!MASKED || opaque(gb0) >= 0) ? 0.f : NEG;
                    mma16816_c(s[0][0], q0, q1, q2, q3, kd.x, kd.y, 0.f);
                    mma16816_c(s[0][1], q0, q1, q2, q3, kd.z, kd.w, 0.f);
                    mma16816_c(f[0], q0, q1, q2, q3, kf.x, kf.y, ci);
                    mma16816_c(f[1], q0, q1, q2, q3, kf.z, kf.w, ci);
#pragma unroll
                    for (int u = 0; u < 2; u++)
#pragma unroll
                        for (int e = 0; e < 4; e++) {
                            const int row = g + 8 * (e >> 1), col = 8 * u + 2 * c + (e & 1);
                            s[0][u][e] = (col > row) ? f[u][e] : s[0][u][e];
                        }
                } else {
                    const uint4 kf = lds128_free(kbase + (8 * ps + t) * 512);
                    const float ci = (!MASKED || opaque(gb0) + 8 * ps + t >= 0) ? 0.f : NEG;
                    mma16816_c(s[t][0], q0, q1, q2, q3, kf.x, kf.y, ci);
                    mma16816_c(s[t][1], q0, q1, q2, q3, kf.z, kf.w, ci);
                }
            };
            auto rowmax = [&](float (&s)[8][2][4], float b0, float b1, float& n0, float& n1) {
                int i0 = __float_as_int(b0), i1 = __float_as_int(b1);
#pragma unroll
                for (int t = 0; t < 8; t++)
#pragma unroll
                    for (int u = 0; u < 2; u++) {
                        i0 = __vimax3_s32(i0, __float_as_int(s[t][u][0]), __float_as_int(s[t][u][1]));
                        i1 = __vimax3_s32(i1, __float_as_int(s[t][u][2]), __float_as_int(s[t][u][3]));
                    }
                i0 = max(i0, __shfl_xor_sync(0xffffffffu, i0, 1)); i1 = max(i1, __shfl_xor_sync(0xffffffffu, i1, 1));
                i0 = max(i0, __shfl_xor_sync(0xffffffffu, i0, 2)); i1 = max(i1, __shfl_xor_sync(0xffffffffu, i1, 2));
                n0 = __int_as_float(i0); n1 = __int_as_float(i1);
                if (__any_sync(0xffffffffu, (i0 | i1) < 0)) {
                    asm volatile("" ::: "memory");
                    n0 = b0; n1 = b1;
#pragma unroll
                    for (int t = 0; t < 8; t++)
#pragma unroll
                        for (int u = 0; u < 2; u++) {
                            n0 = fmaxf(n0, fmaxf(s[t][u][0], s[t][u][1]));
                            n1 = fmaxf(n1, fmaxf(s[t][u][2], s[t][u][3]));
                        }
                    n0 = fmaxf(n0, __shfl_xor_sync(0xffffffffu, n0, 1)); n1 = fmaxf(n1, __shfl_xor_sync(0xffffffffu, n1, 1));
                    n0 = fmaxf(n0, __shfl_xor_sync(0xffffffffu, n0, 2)); n1 = fmaxf(n1, __shfl_xor_sync(0xffffffffu, n1, 2));
                }
            };
            auto pv = [&](const float (&p)[2][4], uint32_t vaddr) {
                const uint4 vf = lds128_free(vaddr);
                const uint32_t a0 = pack_bf16(p[0][0], p[0][1]), a1 = pack_bf16(p[0][2], p[0][3]);
                const uint32_t a2 = pack_bf16(p[1][0], p[1][1]), a3 = pack_bf16(p[1][2], p[1][3]);
                mma16816(o[0], a0, a1, a2, a3, vf.x, vf.y);
                mma16816(o[1], a0, a1, a2, a3, vf.z, vf.w);
                mma16816(ls, a0, a1, a2, a3, ONES, ONES);
            };
            auto expv = [&](float (&s)[8][2][4], int ps, int t, float mc0, float mc1, uint32_t vbase, bool merged) {
                float p[2][4];
#pragma unroll
                for (int u = 0; u < 2; u++) {
                    p[u][0] = ex2(fmaf(s[t][u][0], SC, -mc0)); p[u][1] = ex2(fmaf(s[t][u][1], SC, -mc0));
                    p[u][2] = ex2(fmaf(s[t][u][2], SC, -mc1)); p[u][3] = ex2(fmaf(s[t][u][3], SC, -mc1));
                }
                if (merged) {
                    float pd[2][4], pf[2][4];
#pragma unroll
                    for (int u = 0; u < 2; u++)
#pragma unroll
                        for (int e = 0; e < 4; e++) {
                            const int row = g + 8 * (e >> 1), col = 8 * u + 2 * c + (e & 1);
                            pf[u][e] = (col > row) ? p[u][e] : 0.f;
                            pd[u][e] = (col > row) ? 0.f : p[u][e];
                        }
                    pv(pd, vbase + 16 * 512);
                    pv(pf, vbase);
                } else {
                    pv(p, vbase + (8 * ps + t) * 512);
                }
            };
            uint32_t kbase = 0, vbase = 0;
#pragma unroll 1
            for (int hh = 0; hh < NHEADS; hh++) {
                ATT_KWAIT(kbase);
                ATT_VWAIT(vbase);
                asm volatile("" : "+r"(kbase), "+r"(vbase) :: "memory");
                if (hh > 0) ATT_NEXTQ(hh);
#pragma unroll
                for (int ps = 0; ps < 2; ps++) {
#pragma unroll
                    for (int t = 0; t < 8; t++) qk(sa, ps, t, kbase, ps == 0 && t == 0);
                    float n0, n1;
                    rowmax(sa, ps ? m0 : NEG, ps ? m1 : NEG, n0, n1);
                    if (ps == 0) {
#pragma unroll
                        for (int e = 0; e < 4; e++) { o[0][e] = 0.f; o[1][e] = 0.f; ls[e] = 0.f; }
                    } else {
                        const float a0 = ex2((m0 - n0) * SC), a1 = ex2((m1 - n1) * SC);
                        ls[0] *= a0; ls[2] *= a1;
                        o[0][0] *= a0; o[0][1] *= a0; o[1][0] *= a0; o[1][1] *= a0;
                        o[0][2] *= a1; o[0][3] *= a1; o[1][2] *= a1; o[1][3] *= a1;
                    }
                    m0 = n0; m1 = n1;
                    const float mc0 = n0 * SC, mc1 = n1 * SC;
#pragma unroll
                    for (int t = 0; t < 8; t++) expv(sa, ps, t, mc0, mc1, vbase, ps == 0 && t == 0);
                }
                const float f0 = __fdividef(g0, ls[0]), f1 = __fdividef(g1, ls[2]);
                ATT_STORE(hh, pack_bf16(o[0][0] * f0, o[0][1] * f0), pack_bf16(o[0][2] * f1, o[0][3] * f1),
                              pack_bf16(o[1][0] * f0, o[1][1] * f0), pack_bf16(o[1][2] * f1, o[1][3] * f1));
                ATT_KVREL();
            }
            };
            if (ti >= 2) attention(BoolTag<false>{}); else attention(BoolTag<true>{});
            fence_async_smem();
            __syncwarp();
            if (lane0) mbar_arrive(sb + B_ODONE);
        }
        TS(7);
        {
            float acc[32];
            uint4 pv[4][4];
            if (!dry) mbar_wait(sb + B_PREADY, 0);
            {
                const uint4* p = g_part + (size_t)((ti * 8 + tj) * 8 + 4) * 1024 + warp * 128 + lane;
#pragma unroll
                for (int s = 0; s < 4; s++)
#pragma unroll
                    for (int n = 0; n < 4; n++) pv[n][s] = dry ? make_uint4(0u, 0u, 0u, 0u) : ldg_weak(p + s * 1024 + n * 32);
            }
            if (!dry) mbar_wait(sb + B_WOFULL, 0);
            if (!dry) mbar_wait(sb + B_ODONE, 0);
            TS(15);
            wgmma_fence();
#pragma unroll
            for (int k = 0; k < 4; k++) wgmma_ss_n64(acc, desc_a(sb + OWN_OFF + wg * 8192 + 32 * k), desc_b(sb + X_OFF + tj * 8192 + 2048 * k), k);
            wgmma_commit();
            float base[32];
            if (!dry) mbar_wait(sb + B_HSUM, 0);
#pragma unroll
            for (int n = 0; n < 4; n++) {
                const uint4 u0 = lds128(sb + HSUM_OFF + (warp * 8 + 2 * n) * 512 + lane * 16), u1 = lds128(sb + HSUM_OFF + (warp * 8 + 2 * n + 1) * 512 + lane * 16);
                float* a = &base[8 * n];
                a[0] = __uint_as_float(u0.x); a[1] = __uint_as_float(u0.y); a[2] = __uint_as_float(u0.z); a[3] = __uint_as_float(u0.w);
                a[4] = __uint_as_float(u1.x); a[5] = __uint_as_float(u1.y); a[6] = __uint_as_float(u1.z); a[7] = __uint_as_float(u1.w);
#pragma unroll
                for (int s = 0; s < 4; s++) {
                    a[0] += bf_lo(pv[n][s].x); a[1] += bf_hi(pv[n][s].x); a[2] += bf_lo(pv[n][s].y); a[3] += bf_hi(pv[n][s].y);
                    a[4] += bf_lo(pv[n][s].z); a[5] += bf_hi(pv[n][s].z); a[6] += bf_lo(pv[n][s].w); a[7] += bf_hi(pv[n][s].w);
                }
            }
            fence_acc(base);
            TS(16);
#pragma unroll 1
            for (int m = 0; m < N_O; m++) {
                CWAIT();
                const uint32_t js = tj + 1 + m;
                const uint32_t as = sb + RING_OFF + r.slot * SLOT + wg * 8192;
                const uint32_t bs = sb + X_OFF + (js & 7) * 8192;
                wgmma_fence();
#pragma unroll
                for (int k = 0; k < 4; k++) wgmma_ss_n64(acc, desc_a(as + 32 * k), desc_b(bs + 2048 * k), 1);
                wgmma_commit();
                if (m == 0) { wgmma_wait<0>(); if (lane0) mbar_arrive(sb + B_EMPTY + 8 * r.slot); }
                r.next();
            }
            wgmma_wait<0>();
            fence_acc(acc);
            TS(17);
#pragma unroll
            for (int k = 0; k < 32; k++) acc[k] += base[k];
            __nv_bfloat16* o = out + (size_t)(ti * 128 + warp * 16 + g) * 512 + tj * 64 + ((lane & 1) ? 8 : 0) + (lane & 2) * 2;
            const bool odd = lane & 1;
#pragma unroll
            for (int t2 = 0; t2 < 4; t2++) {
                const uint32_t lo0 = pack_bf16(acc[8 * t2 + 0], acc[8 * t2 + 1]), hi0 = pack_bf16(acc[8 * t2 + 2], acc[8 * t2 + 3]);
                const uint32_t lo1 = pack_bf16(acc[8 * t2 + 4], acc[8 * t2 + 5]), hi1 = pack_bf16(acc[8 * t2 + 6], acc[8 * t2 + 7]);
                const uint32_t sl = __shfl_xor_sync(0xffffffffu, odd ? lo0 : lo1, 1), sh = __shfl_xor_sync(0xffffffffu, odd ? hi0 : hi1, 1);
                if (!dry) *reinterpret_cast<uint2*>(o + 16 * t2) = odd ? make_uint2(sl, lo1) : make_uint2(lo0, sl);
                if (!dry) *reinterpret_cast<uint2*>(o + 16 * t2 + 8 * 512) = odd ? make_uint2(sh, hi1) : make_uint2(hi0, sh);
            }
            if (tid == 0 && !dry) TSG(30);
        }
        TS(8);
    }
}

typedef CUresult (*PFN_encodeTiled)(CUtensorMap*, CUtensorMapDataType, cuuint32_t, void*, const cuuint64_t*, const cuuint64_t*,
                                    const cuuint32_t*, const cuuint32_t*, CUtensorMapInterleave, CUtensorMapSwizzle,
                                    CUtensorMapL2promotion, CUtensorMapFloatOOBfill);

void make_map(PFN_encodeTiled enc, CUtensorMap* m, const void* base, int rank, const cuuint64_t* dims, const cuuint64_t* strides, const cuuint32_t* box) {
    cuuint32_t es[5] = {1, 1, 1, 1, 1};
    enc(m, CU_TENSOR_MAP_DATA_TYPE_BFLOAT16, (cuuint32_t)rank, const_cast<void*>(base), dims, strides, box, es,
        CU_TENSOR_MAP_INTERLEAVE_NONE, CU_TENSOR_MAP_SWIZZLE_128B, CU_TENSOR_MAP_L2_PROMOTION_L2_256B, CU_TENSOR_MAP_FLOAT_OOB_FILL_NONE);
}

}

extern "C" void kernel_launch(void* const* d_in, const int* in_sizes, int n_in, void* d_out, int out_size) {
    (void)in_sizes; (void)n_in; (void)out_size;
    const void* x = d_in[0]; const void* wqkv = d_in[1]; const void* wo = d_in[2];
    const void* w1 = d_in[4]; const void* w2 = d_in[5]; const void* gate_w = d_in[6];
    static PFN_encodeTiled enc = nullptr;
    static int ncta = 128;
    if (!enc) {
        int dev = 0, sms = 0;
        cudaGetDevice(&dev);
        cudaDeviceGetAttribute(&sms, cudaDevAttrMultiProcessorCount, dev);
        ncta = sms > 132 ? 132 : (sms > 128 ? sms : 128);
        void* fn = nullptr; cudaDriverEntryPointQueryResult st;
        cudaGetDriverEntryPoint("cuTensorMapEncodeTiled", &fn, cudaEnableDefault, &st);
        enc = (PFN_encodeTiled)fn;
        cudaFuncSetAttribute(fused_kernel, cudaFuncAttributeMaxDynamicSharedMemorySize, SMEM_BYTES);
    }
    CUtensorMap mx, mqkv, mw1, mw2, mwo, mw1a, mo;
    void* optr = nullptr;
    cudaGetSymbolAddress(&optr, g_o);
    { cuuint64_t d[2] = {512, 2048}, s[1] = {1024}; cuuint32_t b[2] = {64, 128}; make_map(enc, &mo, optr, 2, d, s, b); }
    { cuuint64_t d[4] = {64, 512, 3, 8}, s[3] = {3584, 128, 448}; cuuint32_t b[4] = {64, 32, 3, 1}; make_map(enc, &mw1a, w1, 4, d, s, b); }
    { cuuint64_t d[2] = {512, 2048}, s[1] = {1024}; cuuint32_t b[2] = {64, 128}; make_map(enc, &mx, x, 2, d, s, b); }
    { cuuint64_t d[4] = {64, 512, 8, 3}, s[3] = {3072, 128, 1024}; cuuint32_t b[4] = {64, 32, 1, 3}; make_map(enc, &mqkv, wqkv, 4, d, s, b); }
    { cuuint64_t d[2] = {1792, 512}, s[1] = {3584}; cuuint32_t b[2] = {64, 32}; make_map(enc, &mw1, w1, 2, d, s, b); }
    { cuuint64_t d[3] = {64, 1792, 8}, s[2] = {1024, 128}; cuuint32_t b[3] = {64, 32, 2}; make_map(enc, &mw2, w2, 3, d, s, b); }
    { cuuint64_t d[2] = {512, 512}, s[1] = {1024}; cuuint32_t b[2] = {64, 256}; make_map(enc, &mwo, wo, 2, d, s, b); }
    fused_kernel<<<ncta, 384, SMEM_BYTES, cudaStreamPerThread>>>(mx, mqkv, mw1, mw2, mwo, mw1a, mo, (const __nv_bfloat16*)gate_w, (__nv_bfloat16*)d_out,
                                           (const uint8_t*)w1, (const uint8_t*)w2, (const uint8_t*)wo);
}
```
